```python
import torch

def _softmax(x, axis=-1):
    return torch.softmax(x, dim=axis)
def _gelu(x):
    return torch.nn.functional.gelu(x, approximate="tanh")
def _silu(x):
    return torch.nn.functional.silu(x)
def _sigmoid(x):
    return torch.sigmoid(x)
def _layernorm(x, axis=-1, eps=1e-5):
    m = x.mean(dim=axis, keepdim=True)
    v = x.var(dim=axis, keepdim=True, unbiased=False)
    return (x - m) / torch.sqrt(v + eps)
def _scatter_add(tgt, idx, src, axis=0):
    return tgt.clone().index_add_(axis, idx, src)
def _segment_sum(src, seg, n):
    out = torch.zeros((n,) + src.shape[1:], dtype=src.dtype)
    return out.index_add_(0, seg, src)
def _pad(x, pw):
    flat = tuple(v for pair in reversed(pw) for v in pair)
    return torch.nn.functional.pad(x, flat)

kernel_name = 'standalone__detection_seg_fpn_lateral__vision'

def setup_inputs():

    _w = (lambda a: (lambda t: t.to(torch.bfloat16) if t.is_floating_point() else t)(torch.as_tensor(a)))
    H = W = (384 // 2) * 2
    C = 384
    k = 1
    return {
        "c_fine": _w((lambda *s: torch.randn(*s, dtype=torch.bfloat16) * 0.05)(1, H, W, C)),
        "p_coarse": _w((lambda *s: torch.randn(*s, dtype=torch.bfloat16) * 0.05)(1, H // 2, W // 2, C)),
        "w_lat": _w((lambda *s: torch.randn(*s, dtype=torch.bfloat16) * 0.05)(C, C)),
        "w_out": _w((lambda *s: torch.randn(*s, dtype=torch.bfloat16) * 0.05)(k, k, C, C)),
    }

def reference(c_fine, p_coarse, w_lat, w_out):
    B, H, W, C = c_fine.shape
    k = 1
    lat = torch.einsum("bhwc,cd->bhwd", c_fine, w_lat)
    up = (lambda x, n, axis: torch.repeat_interleave(x, n, dim=axis))((lambda x, n, axis: torch.repeat_interleave(x, n, dim=axis))(p_coarse, 2, axis=1), 2, axis=2)
    m = lat + up
    pad = k // 2
    mp = _pad(m, ((0, 0), (pad, pad), (pad, pad), (0, 0)))
    o = None
    for di in range(k):
        for dj in range(k):
            t = torch.einsum("bhwc,cd->bhwd", mp[:, di:di + H, dj:dj + W, :], w_out[di, dj])
            o = t if o is None else o + t
    return o
```

```cpp
#include <cuda_runtime.h>
#include <cuda_bf16.h>
#include <cuda.h>
#include <stdint.h>

#define PF_DIST 4
#define PF_COLS 2
#define PF_INIT 2
#define NPW 2
#define L2PROMO CU_TENSOR_MAP_L2_PROMOTION_L2_128B
#define NO_MMA 0
#define PROF_REC(row, idx) do {} while (0)

namespace {

constexpr int kC = 384;
constexpr int kFinePix = 384 * 384;
constexpr int kCoarsePix = 192 * 192;
constexpr int kUnits = kCoarsePix / 64;
constexpr int kStages = 7;
constexpr int kChunk = 8192;
constexpr int kTileBytes = 6 * kChunk;
constexpr int kWSlice = kC * 128;
constexpr int kOffStage = 3 * kWSlice;
constexpr int kOffOut = kOffStage + kStages * kChunk;
constexpr int kOffBar = kOffOut + 3 * kChunk;
constexpr int kSmemBytes = kOffBar + 256;
constexpr int kBarFull = 0, kBarEmpty = 8 * kStages, kBarW = 16 * kStages;

__device__ __forceinline__ uint32_t smem_u32(const void* p) { return (uint32_t)__cvta_generic_to_shared(p); }

__device__ __forceinline__ void mbar_init(uint32_t bar, uint32_t count) {
    asm volatile("mbarrier.init.shared::cta.b64 [%0], %1;" ::"r"(bar), "r"(count) : "memory");
}
__device__ __forceinline__ void mbar_expect_tx(uint32_t bar, uint32_t bytes) {
    asm volatile("mbarrier.arrive.expect_tx.shared::cta.b64 _, [%0], %1;" ::"r"(bar), "r"(bytes) : "memory");
}
__device__ __forceinline__ void mbar_wait(uint32_t bar, uint32_t parity) {
    asm volatile(
        "{\n"
        ".reg .pred p;\n"
        ".reg .u32 n;\n"
        "mov.u32 n, 0;\n"
        "WAIT_LOOP:\n"
        "mbarrier.try_wait.parity.shared::cta.b64 p, [%0], %1;\n"
        "@p bra WAIT_DONE;\n"
        "add.u32 n, n, 1;\n"
        "setp.lt.u32 p, n, 0x400000;\n"
        "@p bra WAIT_LOOP;\n"
        "trap;\n"
        "WAIT_DONE:\n"
        "}\n" ::"r"(bar), "r"(parity) : "memory");
}
__device__ __forceinline__ void mbar_arrive_cluster(uint32_t bar) {
    asm volatile("mbarrier.arrive.shared::cluster.b64 _, [%0];" ::"r"(bar) : "memory");
}
__device__ __forceinline__ void tma_load_2d(uint32_t dst, const CUtensorMap* tm, int c0, int c1, uint32_t bar) {
    asm volatile("cp.async.bulk.tensor.2d.shared::cluster.global.mbarrier::complete_tx::bytes [%0], [%1, {%2, %3}], [%4];"
                 ::"r"(dst), "l"(tm), "r"(c0), "r"(c1), "r"(bar) : "memory");
}
__device__ __forceinline__ void tma_load_2d_mc(uint32_t dst, const CUtensorMap* tm, int c0, int c1, uint32_t bar) {
    asm volatile("cp.async.bulk.tensor.2d.shared::cluster.global.mbarrier::complete_tx::bytes.multicast::cluster [%0], [%1, {%2, %3}], [%4], %5;"
                 ::"r"(dst), "l"(tm), "r"(c0), "r"(c1), "r"(bar), "h"((uint16_t)3) : "memory");
}
__device__ __forceinline__ void tma_load_4d_mc(uint32_t dst, const CUtensorMap* tm, int c0, int c3, uint32_t bar) {
    asm volatile("cp.async.bulk.tensor.4d.shared::cluster.global.mbarrier::complete_tx::bytes.multicast::cluster [%0], [%1, {%2, %3, %3, %4}], [%5], %6;"
                 ::"r"(dst), "l"(tm), "r"(c0), "r"(0), "r"(c3), "r"(bar), "h"((uint16_t)3) : "memory");
}
__device__ __forceinline__ void tma_store_2d(const CUtensorMap* tm, uint32_t src, int c0, int c1) {
    asm volatile("cp.async.bulk.tensor.2d.global.shared::cta.bulk_group [%0, {%2, %3}], [%1];"
                 ::"l"(tm), "r"(src), "r"(c0), "r"(c1) : "memory");
}
__device__ __forceinline__ void l2_prefetch(const void* p, uint32_t bytes) {
    asm volatile("cp.async.bulk.prefetch.L2.global [%0], %1;" ::"l"(p), "r"(bytes) : "memory");
}

__device__ __forceinline__ void prefetch_l2(const void* p) {
    asm volatile("prefetch.global.L2 [%0];" ::"l"(p) : "memory");
}
__device__ __forceinline__ bool elect_one() {
    uint32_t p;
    asm volatile("{\n.reg .pred p;\nelect.sync _|p, 0xffffffff;\nselp.u32 %0, 1, 0, p;\n}\n" : "=r"(p));
    return p != 0;
}

#define WG_FENCE() asm volatile("wgmma.fence.sync.aligned;" ::: "memory")
#define WG_COMMIT() asm volatile("wgmma.commit_group.sync.aligned;" ::: "memory")
#define WG_WAIT(n) asm volatile("wgmma.wait_group.sync.aligned %0;" ::"n"(n) : "memory")

#define ACC32 "{%0,%1,%2,%3,%4,%5,%6,%7,%8,%9,%10,%11,%12,%13,%14,%15,%16,%17,%18,%19,%20,%21,%22,%23,%24,%25,%26,%27,%28,%29,%30,%31}"
#define ACC8(b) "+f"(d[b]), "+f"(d[b + 1]), "+f"(d[b + 2]), "+f"(d[b + 3]), "+f"(d[b + 4]), "+f"(d[b + 5]), "+f"(d[b + 6]), "+f"(d[b + 7])

#define DESC_HI "0x40000040"
template <int BOFF>
__device__ __forceinline__ void wgmma_rs(float (&d)[32], uint32_t a0, uint32_t a1, uint32_t a2, uint32_t a3, uint32_t b_lo) {
    asm volatile("{\n.reg .b32 tb;\n.reg .b64 db;\nadd.u32 tb, %36, %37;\nmov.b64 db, {tb, " DESC_HI "};\n"
                 "wgmma.mma_async.sync.aligned.m64n64k16.f32.bf16.bf16 " ACC32 ", {%32,%33,%34,%35}, db, 1, 1, 1, 0;\n}\n"
                 : ACC8(0), ACC8(8), ACC8(16), ACC8(24)
                 : "r"(a0), "r"(a1), "r"(a2), "r"(a3), "r"(b_lo), "n"(BOFF));
}
template <int ACCUM, int AOFF, int BOFF>
__device__ __forceinline__ void wgmma_ss(float (&d)[32], uint32_t a_lo, uint32_t b_lo) {
    asm volatile("{\n.reg .b32 ta, tb;\n.reg .b64 da, db;\nadd.u32 ta, %32, %35;\nadd.u32 tb, %33, %36;\n"
                 "mov.b64 da, {ta, " DESC_HI "};\nmov.b64 db, {tb, " DESC_HI "};\n"
                 "wgmma.mma_async.sync.aligned.m64n64k16.f32.bf16.bf16 " ACC32 ", da, db, %34, 1, 1, 1, 0;\n}\n"
                 : ACC8(0), ACC8(8), ACC8(16), ACC8(24)
                 : "r"(a_lo), "r"(b_lo), "n"(ACCUM), "n"(AOFF), "n"(BOFF));
}

__device__ __forceinline__ uint32_t pack_bf16(float lo, float hi) {
    uint32_t r;
    asm("cvt.rn.bf16x2.f32 %0, %1, %2;" : "=r"(r) : "f"(hi), "f"(lo));
    return r;
}

struct Pipe {
    uint32_t s8, phase;
    template <int STEP>
    __device__ __forceinline__ void advance() {
        s8 += 8 * STEP;
        if (s8 >= 8 * kStages) { s8 -= 8 * kStages; phase ^= 1; }
    }
};

template <int C, bool RS, bool FIRST>
__device__ __forceinline__ void chunk_mma(float (&acc)[32], const uint32_t (&w)[96], Pipe& pp, uint32_t& prev, uint32_t bars,
                                          uint32_t a_lo, uint32_t b_lo0, uint32_t rel_bar, bool rel) {
    if (FIRST) mbar_wait(bars + kBarW + 8 * C, 0);
    mbar_wait(bars + kBarFull + pp.s8, pp.phase);
    const uint32_t b_lo = b_lo0 + pp.s8 * 64;
    if (!NO_MMA) {
        WG_FENCE();
        if (RS) {
            wgmma_rs<0>(acc, w[16 * C + 0], w[16 * C + 1], w[16 * C + 2], w[16 * C + 3], b_lo);
            wgmma_rs<2>(acc, w[16 * C + 4], w[16 * C + 5], w[16 * C + 6], w[16 * C + 7], b_lo);
            wgmma_rs<4>(acc, w[16 * C + 8], w[16 * C + 9], w[16 * C + 10], w[16 * C + 11], b_lo);
            wgmma_rs<6>(acc, w[16 * C + 12], w[16 * C + 13], w[16 * C + 14], w[16 * C + 15], b_lo);
        } else {
            wgmma_ss<(C > 0), 512 * C, 0>(acc, a_lo, b_lo);
            wgmma_ss<1, 512 * C + 128, 2>(acc, a_lo, b_lo);
            wgmma_ss<1, 512 * C + 256, 4>(acc, a_lo, b_lo);
            wgmma_ss<1, 512 * C + 384, 6>(acc, a_lo, b_lo);
        }
        WG_COMMIT();
    }
    if (C > 0) {
        if (!NO_MMA) WG_WAIT(1);
        if (rel) mbar_arrive_cluster(rel_bar + prev);
    }
    prev = pp.s8;
    pp.advance<1>();
}

template <bool RS, bool FIRST>
__device__ __forceinline__ void tile_mma(float (&acc)[32], const uint32_t (&w)[96], Pipe& pp, uint32_t& prev, uint32_t bars,
                                         uint32_t a_lo, uint32_t b_lo0, uint32_t rel_bar, bool rel) {
    chunk_mma<0, RS, FIRST>(acc, w, pp, prev, bars, a_lo, b_lo0, rel_bar, rel);
    chunk_mma<1, RS, FIRST>(acc, w, pp, prev, bars, a_lo, b_lo0, rel_bar, rel);
    chunk_mma<2, RS, FIRST>(acc, w, pp, prev, bars, a_lo, b_lo0, rel_bar, rel);
    chunk_mma<3, RS, FIRST>(acc, w, pp, prev, bars, a_lo, b_lo0, rel_bar, rel);
    chunk_mma<4, RS, FIRST>(acc, w, pp, prev, bars, a_lo, b_lo0, rel_bar, rel);
    chunk_mma<5, RS, FIRST>(acc, w, pp, prev, bars, a_lo, b_lo0, rel_bar, rel);
}

__global__ void __cluster_dims__(2, 1, 1) __launch_bounds__(512, 1)
fpn_lateral_kernel(const __grid_constant__ CUtensorMap tm_fine, const __grid_constant__ CUtensorMap tm_coarse,
                   const __grid_constant__ CUtensorMap tm_wlat, const __grid_constant__ CUtensorMap tm_wout,
                   const __grid_constant__ CUtensorMap tm_out, const char* __restrict__ fine, const char* __restrict__ coarse) {
    extern __shared__ __align__(1024) unsigned char smem_raw[];
    const uint32_t sbase = smem_u32(smem_raw);
    const uint32_t bars = sbase + kOffBar;
    const int warp_id = __shfl_sync(0xffffffffu, (int)(threadIdx.x >> 5), 0);
    const int wg = warp_id >> 2;
    const int rank = blockIdx.x & 1;
    const int cid = blockIdx.x >> 1;
    const int ncl = gridDim.x >> 1;

    if (threadIdx.x == 0) {
        if (sbase & 1023) __trap();
        for (int s = 0; s < kStages; s++) {
            mbar_init(bars + kBarFull + 8 * s, 1);
            mbar_init(bars + kBarEmpty + 8 * s, 6);
        }
        for (int c = 0; c < 6; c++) mbar_init(bars + kBarW + 8 * c, 1);
        asm volatile("fence.mbarrier_init.release.cluster;" ::: "memory");
        asm volatile("fence.proxy.async.shared::cta;" ::: "memory");
    }
    asm volatile("barrier.cluster.arrive.release.aligned;" ::: "memory");
    asm volatile("barrier.cluster.wait.acquire.aligned;" ::: "memory");
    if (threadIdx.x == 0) PROF_REC(0, 0);

    if (wg == 3) {
        asm volatile("setmaxnreg.dec.sync.aligned.u32 32;");
        const int j = warp_id & 3;
        if (j < NPW) {
            const int lane = threadIdx.x & 31;
            const bool lead = elect_one();
            const uint32_t dst0 = sbase + kOffStage + rank * 4096;
            Pipe pp;
            pp.s8 = 8 * j; pp.phase = 1;
            auto tile_ptr = [&](int u, int r) -> const char* {
                if (r == 0) return coarse + (size_t)u * kTileBytes + rank * (kTileBytes / 2);
                const int y = u / 3, xb = u - y * 3;
                const int row0 = (2 * y + ((r - 1) >> 1)) * 384 + xb * 128 + ((r - 1) & 1) * 64 + rank * 32;
                return fine + (size_t)row0 * 768;
            };
            for (int t = 0; t < 6; t++) {
#pragma unroll
                for (int cc = 0; cc < 6; cc += NPW) {
                    const int c = cc + j;
                    if (t == 0 && lead) {
                        const uint32_t wb = bars + kBarW + 8 * c;
                        mbar_expect_tx(wb, 3 * kChunk);
                        for (int g = 0; g < 3; g++) tma_load_2d(sbase + g * kWSlice + c * kChunk, &tm_wout, rank * 192 + g * 64, c * 64, wb);
                    }
                    mbar_wait(bars + kBarEmpty + pp.s8, pp.phase);
                    if (lead) {
                        if (t) PROF_REC(0, pp.n);
                        mbar_expect_tx(bars + kBarFull + pp.s8, kChunk);
                        tma_load_2d_mc(dst0 + pp.s8 * 1024, &tm_wlat, c * 64, t * 64 + rank * 32, bars + kBarFull + pp.s8);
                    }
                    pp.advance<NPW>();
                }
                if (t == 0 && PF_COLS) {
                    for (int i = 0; i < PF_INIT; i++) {
                        const int u = cid + (i / 5) * ncl;
                        if (u < kUnits) {
                            const char* p = tile_ptr(u, i % 5);
                            for (int l = j; l < 6; l += NPW) prefetch_l2(p + l * 4096 + lane * 128);
                        }
                    }
                }
            }
            constexpr int PFA = PF_DIST / 6, PFB = PF_DIST % 6;
            int pu = cid + (PFA / 5) * ncl, pr = PFA % 5, pt = PFA;
            for (int u = cid; u < kUnits; u += ncl) {
                const int y = u / 3, xb = u - y * 3;
                for (int r = 0; r < 5; r++) {
                    const int row0 = (2 * y + ((r - 1) >> 1)) * 384 + xb * 128 + ((r - 1) & 1) * 64 + rank * 32;
                    const char* pp0 = (pu < kUnits && pt >= PF_INIT) ? tile_ptr(pu, pr) : nullptr;
                    if (++pr == 5) { pr = 0; pu += ncl; }
                    pt++;
                    const char* pp1 = (pu < kUnits && pt >= PF_INIT) ? tile_ptr(pu, pr) : nullptr;
#pragma unroll
                    for (int cc = 0; cc < 6; cc += NPW) {
                        const int c = cc + j;
                        mbar_wait(bars + kBarEmpty + pp.s8, pp.phase);
                        if (lead) {
                            PROF_REC(0, pp.n);
                            const uint32_t fb = bars + kBarFull + pp.s8;
                            mbar_expect_tx(fb, kChunk);
                            if (r == 0) tma_load_4d_mc(dst0 + pp.s8 * 1024, &tm_coarse, c * 64, 8 * u + 4 * rank, fb);
                            else tma_load_2d_mc(dst0 + pp.s8 * 1024, &tm_fine, c * 64, row0, fb);
                        }
                        pp.advance<NPW>();
                        if (PF_COLS) {
                            int pc = c + PFB;
                            const char* p = pp0;
                            if (pc >= 6) { pc -= 6; p = pp1; }
                            if (p != nullptr && pc % (PF_COLS ? PF_COLS : 1) == 0) {
#pragma unroll
                                for (int i = 0; i < PF_COLS; i++) {
                                    const int idx = i * 32 + lane;
                                    const int row = idx / (PF_COLS ? PF_COLS : 1), col = idx - row * PF_COLS;
                                    prefetch_l2(p + row * 768 + (pc + col) * 128);
                                }
                            }
                        }
                    }
                }
            }
        }
    } else {
        asm volatile("setmaxnreg.inc.sync.aligned.u32 160;");
        const int tid = threadIdx.x & 127;
        const int lane = tid & 31, warp = tid >> 5;
        const bool rel = tid < 2;
        const bool leader = tid == 0;
        uint32_t rel_bar;
        asm("mapa.shared::cluster.u32 %0, %1, %2;" : "=r"(rel_bar) : "r"(bars + kBarEmpty), "r"(tid & 1));
        const uint32_t a_lo = ((sbase + wg * kWSlice) & 0x3FFFF) >> 4;
        const uint32_t b_lo0 = (((sbase + kOffStage) & 0x3FFFF) >> 4) | 0x10000u;
        const uint32_t out_smem = sbase + kOffOut + wg * kChunk;
        const uint32_t st_addr = out_smem + ((lane >> 4) * 8 + (lane & 7)) * 128 + (((2 * warp + ((lane >> 3) & 1)) ^ (lane & 7)) << 4);

        Pipe pp;
        pp.s8 = 0; pp.phase = 0;
        uint32_t prev = 0;
        float acc[32];
        uint32_t w[96];
        uint32_t pc[16];
#pragma unroll
        for (int t = 0; t < 6; t++) {
            if (t == 0) tile_mma<false, true>(acc, w, pp, prev, bars, a_lo, b_lo0, rel_bar, rel);
            else tile_mma<false, false>(acc, w, pp, prev, bars, a_lo, b_lo0, rel_bar, rel);
            if (!NO_MMA) WG_WAIT(0);
            if (rel) mbar_arrive_cluster(rel_bar + prev);
#pragma unroll
            for (int i = 0; i < 16; i++) w[16 * t + i] = pack_bf16(acc[2 * i], acc[2 * i + 1]);
        }
        for (int u = cid; u < kUnits; u += ncl) {
            tile_mma<false, false>(acc, w, pp, prev, bars, a_lo, b_lo0, rel_bar, rel);
            if (!NO_MMA) WG_WAIT(0);
            if (rel) mbar_arrive_cluster(rel_bar + prev);
#pragma unroll
            for (int j = 0; j < 16; j++) pc[j] = pack_bf16(acc[4 * (j >> 1) + (j & 1)], acc[4 * (j >> 1) + 2 + (j & 1)]);
#pragma unroll 1
            for (int ry = 0; ry < 2; ry++) {
#pragma unroll
                for (int h = 0; h < 2; h++) {
#pragma unroll
                    for (int j = 0; j < 8; j++) {
                        const float lo = __uint_as_float(pc[8 * h + j] << 16);
                        const float hi = __uint_as_float(pc[8 * h + j] & 0xffff0000u);
                        acc[4 * j] = lo; acc[4 * j + 1] = lo; acc[4 * j + 2] = hi; acc[4 * j + 3] = hi;
                    }
                    tile_mma<true, false>(acc, w, pp, prev, bars, a_lo, b_lo0, rel_bar, rel);
                    if (threadIdx.x == 0) PROF_REC(4, pp.n);
                    if (leader) asm volatile("cp.async.bulk.wait_group.read 0;" ::: "memory");
                    if (threadIdx.x == 0) PROF_REC(5, pp.n);
                    asm volatile("bar.sync %0, 128;" ::"r"(wg + 1) : "memory");
                    if (!NO_MMA) WG_WAIT(0);
                    if (threadIdx.x == 0) PROF_REC(6, pp.n);
                    if (rel) mbar_arrive_cluster(rel_bar + prev);
#pragma unroll
                    for (int jp = 0; jp < 4; jp++) {
                        const uint32_t r0 = pack_bf16(acc[8 * jp + 0], acc[8 * jp + 1]);
                        const uint32_t r1 = pack_bf16(acc[8 * jp + 2], acc[8 * jp + 3]);
                        const uint32_t r2 = pack_bf16(acc[8 * jp + 4], acc[8 * jp + 5]);
                        const uint32_t r3 = pack_bf16(acc[8 * jp + 6], acc[8 * jp + 7]);
                        asm volatile("stmatrix.sync.aligned.m8n8.x4.trans.shared.b16 [%0], {%1,%2,%3,%4};"
                                     ::"r"(st_addr + jp * 2048), "r"(r0), "r"(r1), "r"(r2), "r"(r3) : "memory");
                    }
                    asm volatile("fence.proxy.async.shared::cta;" ::: "memory");
                    asm volatile("bar.sync %0, 128;" ::"r"(wg + 1) : "memory");
                    if (leader) {
                        const int y = u / 3, xb = u - y * 3;
                        const int row0 = (2 * y + ry) * 384 + xb * 128 + h * 64;
                        tma_store_2d(&tm_out, out_smem, rank * 192 + wg * 64, row0);
                        asm volatile("cp.async.bulk.commit_group;" ::: "memory");
                    }
                    if (threadIdx.x == 0) PROF_REC(7, pp.n);
                }
            }
        }
        if (leader) asm volatile("cp.async.bulk.wait_group.read 0;" ::: "memory");
    }
    asm volatile("barrier.cluster.arrive.release.aligned;" ::: "memory");
    asm volatile("barrier.cluster.wait.acquire.aligned;" ::: "memory");
}

typedef CUresult (*EncodeFn)(CUtensorMap*, CUtensorMapDataType, cuuint32_t, void*, const cuuint64_t*, const cuuint64_t*,
                             const cuuint32_t*, const cuuint32_t*, CUtensorMapInterleave, CUtensorMapSwizzle,
                             CUtensorMapL2promotion, CUtensorMapFloatOOBfill);

void encode_2d(EncodeFn enc, CUtensorMap* tm, const void* ptr, uint64_t rows, uint32_t box_rows, CUtensorMapL2promotion promo) {
    cuuint64_t dims[2] = {(cuuint64_t)kC, rows};
    cuuint64_t strides[1] = {(cuuint64_t)kC * 2};
    cuuint32_t box[2] = {64, box_rows};
    cuuint32_t es[2] = {1, 1};
    enc(tm, CU_TENSOR_MAP_DATA_TYPE_BFLOAT16, 2, const_cast<void*>(ptr), dims, strides, box, es, CU_TENSOR_MAP_INTERLEAVE_NONE,
        CU_TENSOR_MAP_SWIZZLE_128B, promo, CU_TENSOR_MAP_FLOAT_OOB_FILL_NONE);
}

}

extern "C" void kernel_launch(void* const* d_in, const int* in_sizes, int n_in, void* d_out, int out_size) {
    (void)in_sizes; (void)n_in; (void)out_size;
    static EncodeFn enc = nullptr;
    static int grid = 0;
    if (!enc) {
        void* fn = nullptr;
        cudaDriverEntryPointQueryResult qr;
        cudaGetDriverEntryPoint("cuTensorMapEncodeTiled", &fn, cudaEnableDefault, &qr);
        enc = (EncodeFn)fn;
        cudaFuncSetAttribute(fpn_lateral_kernel, cudaFuncAttributeMaxDynamicSharedMemorySize, kSmemBytes);
        cudaLaunchConfig_t cfg = {};
        cfg.gridDim = dim3(2);
        cfg.blockDim = dim3(512);
        cfg.dynamicSmemBytes = kSmemBytes;
        cudaLaunchAttribute at;
        at.id = cudaLaunchAttributeClusterDimension;
        at.val.clusterDim.x = 2; at.val.clusterDim.y = 1; at.val.clusterDim.z = 1;
        cfg.attrs = &at; cfg.numAttrs = 1;
        int ncl = 0;
        if (cudaOccupancyMaxActiveClusters(&ncl, fpn_lateral_kernel, &cfg) != cudaSuccess || ncl < 1) { (void)cudaGetLastError(); ncl = 64; }
        if (ncl > kUnits) ncl = kUnits;
        grid = 2 * ncl;
    }
    CUtensorMap tm_fine, tm_coarse, tm_wlat, tm_wout, tm_out;
    encode_2d(enc, &tm_fine, d_in[0], kFinePix, 32, L2PROMO);
    encode_2d(enc, &tm_wlat, d_in[2], kC, 32, CU_TENSOR_MAP_L2_PROMOTION_L2_256B);
    encode_2d(enc, &tm_wout, d_in[3], kC, 64, CU_TENSOR_MAP_L2_PROMOTION_L2_256B);
    encode_2d(enc, &tm_out, d_out, kFinePix, 64, CU_TENSOR_MAP_L2_PROMOTION_NONE);
    {
        cuuint64_t dims[4] = {(cuuint64_t)kC, 2, 4, (cuuint64_t)kCoarsePix / 8};
        cuuint64_t strides[3] = {4 * 768, 768, 8 * 768};
        cuuint32_t box[4] = {64, 2, 4, 4};
        cuuint32_t es[4] = {1, 1, 1, 1};
        enc(&tm_coarse, CU_TENSOR_MAP_DATA_TYPE_BFLOAT16, 4, d_in[1], dims, strides, box, es, CU_TENSOR_MAP_INTERLEAVE_NONE,
            CU_TENSOR_MAP_SWIZZLE_128B, L2PROMO, CU_TENSOR_MAP_FLOAT_OOB_FILL_NONE);
    }
    fpn_lateral_kernel<<<grid, 512, kSmemBytes>>>(tm_fine, tm_coarse, tm_wlat, tm_wout, tm_out, (const char*)d_in[0], (const char*)d_in[1]);
}
```

```cpp
#include <cuda_runtime.h>
#include <cuda_bf16.h>
#include <cuda.h>
#include <stdint.h>

#define PF_INIT 2
#define PF_DIST 6
#define PF_COLS 2
#define LD_EF 0
#define ST_EF 0
#define PACE 1
#define TOKEN_K 3
#define EARLY_TEST 1
#define FENCE_ALL 1
#define PF_W 1
#define STAGGER 0
#define L2PROMO CU_TENSOR_MAP_L2_PROMOTION_L2_128B
#define NO_MMA 0
#define PROF_REC(row, idx) do {} while (0)
#define PROF_GT(k) do {} while (0)
#define PROF_REC2(row, idx) do {} while (0)

namespace {

constexpr int kC = 384;
constexpr int kFinePix = 384 * 384;
constexpr int kCoarsePix = 192 * 192;
constexpr int kUnits = kCoarsePix / 64;
#define GROUP 3
constexpr int kGroup = GROUP;
constexpr int kStages = 25 - 3 * kGroup;
constexpr int kChunk = 8192;
constexpr int kTileBytes = 6 * kChunk;
constexpr int kOffP = kStages * kChunk;
constexpr int kOffOut = kOffP + kGroup * 3 * kChunk;
constexpr int kOffBar = kOffOut + 3 * kChunk;
constexpr int kSmemBytes = kOffBar + 512;
constexpr int kOffW = kOffBar - 3 * kTileBytes;
constexpr int kFreeSlots = kOffW / kChunk;
constexpr int kBarFull = 0, kBarEmpty = 8 * kStages, kBarW = 16 * kStages, kBarReady = kBarW + 24;
constexpr int kBarStaged = kBarReady + 8, kBarFree = kBarStaged + 24;
constexpr uint32_t kReadyCount = 7 * 24;

__device__ uint4 g_wfrag[2][2][3][24][128];
__device__ uint32_t g_ready;
__device__ uint32_t g_done;
__device__ uint32_t g_progress;

__device__ __forceinline__ uint32_t smem_u32(const void* p) { return (uint32_t)__cvta_generic_to_shared(p); }

__device__ __forceinline__ void mbar_init(uint32_t bar, uint32_t count) {
    asm volatile("mbarrier.init.shared::cta.b64 [%0], %1;" ::"r"(bar), "r"(count) : "memory");
}
__device__ __forceinline__ void mbar_expect_tx(uint32_t bar, uint32_t bytes) {
    asm volatile("mbarrier.arrive.expect_tx.shared::cta.b64 _, [%0], %1;" ::"r"(bar), "r"(bytes) : "memory");
}
__device__ __forceinline__ void mbar_wait(uint32_t bar, uint32_t parity) {
    asm volatile(
        "{\n"
        ".reg .pred p;\n"
        ".reg .u32 n;\n"
        "mov.u32 n, 0;\n"
        "WAIT_LOOP:\n"
        "mbarrier.try_wait.parity.shared::cta.b64 p, [%0], %1;\n"
        "@p bra WAIT_DONE;\n"
        "add.u32 n, n, 1;\n"
        "setp.lt.u32 p, n, 0x400000;\n"
        "@p bra WAIT_LOOP;\n"
        "trap;\n"
        "WAIT_DONE:\n"
        "}\n" ::"r"(bar), "r"(parity) : "memory");
}
__device__ __forceinline__ bool mbar_test(uint32_t bar, uint32_t parity) {
    uint32_t r;
    asm volatile("{\n.reg .pred p;\nmbarrier.test_wait.parity.shared::cta.b64 p, [%1], %2;\nselp.u32 %0, 1, 0, p;\n}\n" : "=r"(r) : "r"(bar), "r"(parity) : "memory");
    return r != 0;
}
__device__ __forceinline__ void mbar_arrive_cluster(uint32_t bar) {
    asm volatile("mbarrier.arrive.shared::cluster.b64 _, [%0];" ::"r"(bar) : "memory");
}
__device__ __forceinline__ void tma_load_2d(uint32_t dst, const CUtensorMap* tm, int c0, int c1, uint32_t bar) {
    asm volatile("cp.async.bulk.tensor.2d.shared::cluster.global.mbarrier::complete_tx::bytes [%0], [%1, {%2, %3}], [%4];"
                 ::"r"(dst), "l"(tm), "r"(c0), "r"(c1), "r"(bar) : "memory");
}
constexpr uint64_t kEvictNormal = 0x1000000000000000ull, kEvictFirst = 0x12F0000000000000ull;
__device__ __forceinline__ void tma_load_2d_mc(uint32_t dst, const CUtensorMap* tm, int c0, int c1, uint32_t bar) {
    asm volatile("cp.async.bulk.tensor.2d.shared::cluster.global.mbarrier::complete_tx::bytes.multicast::cluster.L2::cache_hint [%0], [%1, {%2, %3}], [%4], %5, %6;"
                 ::"r"(dst), "l"(tm), "r"(c0), "r"(c1), "r"(bar), "h"((uint16_t)3), "l"(LD_EF ? kEvictFirst : kEvictNormal) : "memory");
}
__device__ __forceinline__ void tma_load_4d_mc(uint32_t dst, const CUtensorMap* tm, int c0, int c3, uint32_t bar) {
    asm volatile("cp.async.bulk.tensor.4d.shared::cluster.global.mbarrier::complete_tx::bytes.multicast::cluster.L2::cache_hint [%0], [%1, {%2, %3, %3, %4}], [%5], %6, %7;"
                 ::"r"(dst), "l"(tm), "r"(c0), "r"(0), "r"(c3), "r"(bar), "h"((uint16_t)3), "l"(LD_EF ? kEvictFirst : kEvictNormal) : "memory");
}
__device__ __forceinline__ void tma_store_2d(const CUtensorMap* tm, uint32_t src, int c0, int c1) {
    asm volatile("cp.async.bulk.tensor.2d.global.shared::cta.bulk_group.L2::cache_hint [%0, {%2, %3}], [%1], %4;"
                 ::"l"(tm), "r"(src), "r"(c0), "r"(c1), "l"(ST_EF ? kEvictFirst : kEvictNormal) : "memory");
}
__device__ __forceinline__ void prefetch_l2(const void* p) {
    asm volatile("prefetch.global.L2 [%0];" ::"l"(p) : "memory");
}
__device__ __forceinline__ bool elect_one() {
    uint32_t p;
    asm volatile("{\n.reg .pred p;\nelect.sync _|p, 0xffffffff;\nselp.u32 %0, 1, 0, p;\n}\n" : "=r"(p));
    return p != 0;
}

#define WG_FENCE() asm volatile("wgmma.fence.sync.aligned;" ::: "memory")
#define WG_COMMIT() asm volatile("wgmma.commit_group.sync.aligned;" ::: "memory")
#define WG_WAIT(n) asm volatile("wgmma.wait_group.sync.aligned %0;" ::"n"(n) : "memory")

#define ACC32 "{%0,%1,%2,%3,%4,%5,%6,%7,%8,%9,%10,%11,%12,%13,%14,%15,%16,%17,%18,%19,%20,%21,%22,%23,%24,%25,%26,%27,%28,%29,%30,%31}"
#define ACC8(b) "+f"(d[b]), "+f"(d[b + 1]), "+f"(d[b + 2]), "+f"(d[b + 3]), "+f"(d[b + 4]), "+f"(d[b + 5]), "+f"(d[b + 6]), "+f"(d[b + 7])

#define DESC_HI "0x40000040"
template <int ACCUM, int BOFF>
__device__ __forceinline__ void wgmma_rs(float (&d)[32], uint32_t a0, uint32_t a1, uint32_t a2, uint32_t a3, uint32_t b_lo) {
    asm volatile("{\n.reg .b32 tb;\n.reg .b64 db;\nadd.u32 tb, %36, %37;\nmov.b64 db, {tb, " DESC_HI "};\n"
                 "wgmma.mma_async.sync.aligned.m64n64k16.f32.bf16.bf16 " ACC32 ", {%32,%33,%34,%35}, db, %38, 1, 1, 0;\n}\n"
                 : ACC8(0), ACC8(8), ACC8(16), ACC8(24)
                 : "r"(a0), "r"(a1), "r"(a2), "r"(a3), "r"(b_lo), "n"(BOFF), "n"(ACCUM));
}

__device__ __forceinline__ uint32_t pack_bf16(float lo, float hi) {
    uint32_t r;
    asm("cvt.rn.bf16x2.f32 %0, %1, %2;" : "=r"(r) : "f"(hi), "f"(lo));
    return r;
}

__device__ __forceinline__ uint32_t slot8(uint32_t n) { return (n % kStages) * 8; }
__device__ __forceinline__ uint32_t parity(uint32_t n) { return (n / kStages) & 1; }

template <int C>
__device__ __forceinline__ void reload_w(uint32_t (&w)[96], const uint4* p) {
#define W4(i) "+r"(w[16 * C + 4 * i]), "+r"(w[16 * C + 4 * i + 1]), "+r"(w[16 * C + 4 * i + 2]), "+r"(w[16 * C + 4 * i + 3])
    asm volatile("{\n.reg .pred p;\nsetp.ne.u64 p, %16, 0;\n"
                 "@p ld.global.cg.v4.u32 {%0,%1,%2,%3}, [%16 + %17];\n"
                 "@p ld.global.cg.v4.u32 {%4,%5,%6,%7}, [%16 + %17 + 2048];\n"
                 "@p ld.global.cg.v4.u32 {%8,%9,%10,%11}, [%16 + %17 + 4096];\n"
                 "@p ld.global.cg.v4.u32 {%12,%13,%14,%15}, [%16 + %17 + 6144];\n}\n"
                 : W4(0), W4(1), W4(2), W4(3)
                 : "l"(p), "n"(C * 8192) : "memory");
#undef W4
}

template <int C>
__device__ __forceinline__ bool issue_chunk(float (&acc)[32], const uint32_t (&w)[96], uint32_t n, uint32_t bars, uint32_t b_lo0, bool ready) {
    if (!ready) mbar_wait(bars + kBarFull + slot8(n + C), parity(n + C));
    if ((threadIdx.x & 127) == 0) PROF_REC2(1 + (threadIdx.x >> 7), n + C);
    const bool next = EARLY_TEST ? mbar_test(bars + kBarFull + slot8(n + C + 1), parity(n + C + 1)) : false;
    const uint32_t b_lo = b_lo0 + slot8(n + C) * 64;
    if (!NO_MMA) {
        if (C == 0 || FENCE_ALL) WG_FENCE();
        wgmma_rs<(C > 0), 0>(acc, w[16 * C + 0], w[16 * C + 1], w[16 * C + 2], w[16 * C + 3], b_lo);
        wgmma_rs<1, 2>(acc, w[16 * C + 4], w[16 * C + 5], w[16 * C + 6], w[16 * C + 7], b_lo);
        wgmma_rs<1, 4>(acc, w[16 * C + 8], w[16 * C + 9], w[16 * C + 10], w[16 * C + 11], b_lo);
        wgmma_rs<1, 6>(acc, w[16 * C + 12], w[16 * C + 13], w[16 * C + 14], w[16 * C + 15], b_lo);
        WG_COMMIT();
    }
    return next;
}
template <int C, int PENDING>
__device__ __forceinline__ void retire_chunk(uint32_t (&w)[96], uint32_t n, uint32_t rel_bar, bool rel, const uint4* swap) {
    if (!NO_MMA) WG_WAIT(PENDING);
    if (rel) mbar_arrive_cluster(rel_bar + slot8(n + C));
    reload_w<C>(w, swap);
}

struct TileSeq {
    int left, gs, t, u;
    __device__ __forceinline__ void next(int ncl) {
        if (++t == 5 * gs) {
            left -= gs;
            u += gs * ncl;
            gs = min(kGroup, left);
            t = 0;
        }
    }
    __device__ __forceinline__ int row(int ncl) const {
        if (t < gs) return (u + t * ncl) * 64;
        const int f = t - gs, v = u + (f >> 2) * ncl, y = v / 3, xb = v - y * 3;
        return (2 * y + ((f >> 1) & 1)) * 384 + xb * 128 + (f & 1) * 64;
    }
};

__device__ __forceinline__ void publish_warp() {
    __threadfence();
    __syncwarp();
    if ((threadIdx.x & 31) == 0) asm volatile("red.release.gpu.global.add.u32 [%0], 1;" ::"l"(&g_ready) : "memory");
}

__global__ void __cluster_dims__(2, 1, 1) __launch_bounds__(512, 1)
fpn_lateral_kernel(const __grid_constant__ CUtensorMap tm_fine, const __grid_constant__ CUtensorMap tm_coarse,
                   const __grid_constant__ CUtensorMap tm_wlat, const __grid_constant__ CUtensorMap tm_wout,
                   const __grid_constant__ CUtensorMap tm_out, const char* __restrict__ fine, const char* __restrict__ coarse
                   ) {
    extern __shared__ __align__(1024) unsigned char smem_raw[];
    const uint32_t sbase = smem_u32(smem_raw);
    const uint32_t bars = sbase + kOffBar;
    const int warp_id = __shfl_sync(0xffffffffu, (int)(threadIdx.x >> 5), 0);
    const int wg = warp_id >> 2;
    const int rank = blockIdx.x & 1;
    const int cid = blockIdx.x >> 1;
    const int ncl = gridDim.x >> 1;
    const int u0 = ncl - 1 - cid;
    const int nunits = (kUnits - u0 + ncl - 1) / ncl;
    const int first_group = STAGGER ? kGroup - cid % kGroup : kGroup;

    if (threadIdx.x == 0) {
        if (sbase & 1023) __trap();
        for (int s = 0; s < kStages; s++) {
            mbar_init(bars + kBarFull + 8 * s, 1);
            mbar_init(bars + kBarEmpty + 8 * s, 6);
            if (s < kFreeSlots) asm volatile("mbarrier.arrive.shared::cta.b64 _, [%0], 6;" ::"r"(bars + kBarEmpty + 8 * s) : "memory");
        }
        for (int c = 0; c < 4; c++) mbar_init(bars + kBarW + 8 * c, 1);
        for (int c = 0; c < 3; c++) {
            mbar_init(bars + kBarStaged + 8 * c, 4);
            mbar_init(bars + kBarFree + 8 * c, 1);
        }
        asm volatile("fence.mbarrier_init.release.cluster;" ::: "memory");
        asm volatile("fence.proxy.async.shared::cta;" ::: "memory");
    }
    asm volatile("barrier.cluster.arrive.release.aligned;" ::: "memory");
    asm volatile("barrier.cluster.wait.acquire.aligned;" ::: "memory");
    if (threadIdx.x == 0) PROF_REC(0, 0);

    if (wg == 3) {
        asm volatile("setmaxnreg.dec.sync.aligned.u32 32;");
        const int j = warp_id & 3;
        const int lane = threadIdx.x & 31;
        if (j == 0) {
            const bool lead = elect_one();
            const uint32_t dst0 = sbase + rank * 4096;
            uint32_t n = 0;
            auto load_tile = [&](const CUtensorMap* tm, int row, bool perm, const char* pf0, const char* pf1) {
#pragma unroll
                for (int c = 0; c < 6; c++, n++) {
                    mbar_wait(bars + kBarEmpty + slot8(n), parity(n));
                    if (lead) {
                        if (n) PROF_REC(0, n);
                        const uint32_t fb = bars + kBarFull + slot8(n);
                        mbar_expect_tx(fb, kChunk);
                        if (perm) tma_load_4d_mc(dst0 + slot8(n) * 1024, tm, c * 64, row >> 3, fb);
                        else tma_load_2d_mc(dst0 + slot8(n) * 1024, tm, c * 64, row, fb);
                    }
                    constexpr int cols = PF_COLS ? PF_COLS : 1;
                    const int pc = (c + PF_DIST) % 6;
                    const char* p = c + PF_DIST % 6 >= 6 ? pf1 : pf0;
                    if (PF_COLS && pc % cols == 0 && p != nullptr) {
#pragma unroll
                        for (int i = 0; i < cols; i++) {
                            const int idx = i * 32 + lane, r = idx / cols, col = idx - r * cols;
                            prefetch_l2(p + r * 768 + (pc + col) * 128);
                        }
                    }
                }
            };
            for (int t = cid; t < 6; t += ncl) load_tile(&tm_wlat, t * 64 + rank * 32, false, nullptr, nullptr);
            TileSeq ts = {nunits, min(first_group, nunits), 0, u0}, pf = ts;
            int pn = 0;
            auto pf_ptr = [&]() -> const char* {
                const char* p = nullptr;
                if (pf.left > 0) {
                    if (pn >= 2 + PF_INIT) p = (pf.t < pf.gs ? coarse : fine) + (size_t)(pf.row(ncl) + rank * 32) * 768;
                    pf.next(ncl);
                    pn++;
                }
                return p;
            };
            for (int i = 0; i < PF_DIST / 6; i++) pf_ptr();
            const char* pf0 = pf_ptr();
            uint32_t g = 0, mine = 0;
            for (; ts.left > 0; ts.next(ncl)) {
                if (PACE && rank == 0 && lead) {
                    if (mine > (g + ncl + PACE * ncl / 4) * nunits) {
                        for (int it = 0; it < 0x100000; it++) {
                            asm volatile("ld.relaxed.gpu.global.u32 %0, [%1];" : "=r"(g) : "l"(&g_progress) : "memory");
                            if (mine <= (g + PACE * ncl / 4) * nunits) break;
                            __nanosleep(50);
                        }
                    }
                    mine += kUnits;
                    g = atomicInc(&g_progress, 5 * kUnits - 1);
                }
                __syncwarp();
                if (PF_W == 2 && mbar_test(bars + kBarReady, 0)) {
                    for (uint32_t l = blockIdx.x * 32 + lane; l < sizeof(g_wfrag) / 128; l += gridDim.x * 32) prefetch_l2((const char*)g_wfrag + l * 128);
                }
                const char* pf1 = pf_ptr();
                load_tile(ts.t < ts.gs ? &tm_coarse : &tm_fine, ts.row(ncl) + rank * 32, ts.t < ts.gs, pf0, pf1);
                pf0 = pf1;
            }
        } else {
          if (j == 3) {
            if (lane < 3) {
                const uint32_t wb = bars + kBarW + 8 * lane;
                mbar_expect_tx(wb, kTileBytes);
                for (int c = 0; c < 6; c++) tma_load_2d(sbase + kOffW + lane * kTileBytes + c * kChunk, &tm_wout, rank * 192 + lane * 64, c * 64, wb);
            }
            __syncwarp();
            TileSeq pf = {nunits, min(first_group, nunits), 0, u0};
            for (int t = 1; t < 2 + PF_INIT; t++) {
                pf.next(ncl);
                if (pf.left <= 0) break;
                const char* p = (pf.t < pf.gs ? coarse : fine) + (size_t)(pf.row(ncl) + rank * 32) * 768;
                for (int l = t == 1 ? 4 : 0; l < 6; l++) prefetch_l2(p + lane * 768 + l * 128);
            }
            if (lane == 0) PROF_GT(5);
            if (lane == 0) {
                uint32_t v, n = 0;
                do {
                    asm volatile("ld.acquire.gpu.global.u32 %0, [%1];" : "=r"(v) : "l"(&g_ready) : "memory");
                    if (v >= kReadyCount) break;
                    __nanosleep(100);
                } while (++n < 0x100000);
                if (v < kReadyCount) __trap();
                PROF_GT(4);
                asm volatile("mbarrier.arrive.shared::cta.b64 _, [%0];" ::"r"(bars + kBarReady) : "memory");
                if (atomicAdd(&g_done, 1) == gridDim.x - 1) {
                    g_ready = 0;
                    g_done = 0;
                }
            }
            __syncwarp();
          }
            const int g = j - 1;
            const char* wf = (const char*)&g_wfrag[0][rank][g][0][0] + lane * 128;
            uint32_t k = 0;
            for (int i0 = 0, i1 = min(first_group, nunits); i0 < nunits; i0 = i1, i1 = min(i1 + kGroup, nunits)) {
                const int nf = 4 * (i1 - i0);
                for (int f = 0; f < nf; f++, k++) {
                    const int u = u0 + (i0 + (f >> 2)) * ncl, y = u / 3, xb = u - y * 3;
                    const int row0 = (2 * y + ((f >> 1) & 1)) * 384 + xb * 128 + (f & 1) * 64;
                    mbar_wait(bars + kBarStaged + 8 * g, k & 1);
                    if (lane == 0) {
                        asm volatile("fence.proxy.async.shared::cta;" ::: "memory");
                        tma_store_2d(&tm_out, sbase + kOffOut + g * kChunk, rank * 192 + g * 64, row0);
                        asm volatile("cp.async.bulk.commit_group;" ::: "memory");
                    }
                    if (PF_W == 1 && i1 < nunits && (f == nf - 3 || f == nf - 1)) {
                        const char* p = wf + (f == nf - 1 ? sizeof(g_wfrag) / 2 : 0);
#pragma unroll
                        for (int l = 0; l < 12; l++) prefetch_l2(p + l * 4096);
                    }
                    if (lane == 0) {
                        asm volatile("cp.async.bulk.wait_group.read 0;" ::: "memory");
                        asm volatile("mbarrier.arrive.shared::cta.b64 _, [%0];" ::"r"(bars + kBarFree + 8 * g) : "memory");
                    }
                    __syncwarp();
                }
            }
        }
    } else {
        asm volatile("setmaxnreg.inc.sync.aligned.u32 160;");
        const int tid = threadIdx.x & 127;
        const int lane = tid & 31, warp = tid >> 5;
        const bool rel = tid < 2;
        uint32_t rel_bar;
        asm("mapa.shared::cluster.u32 %0, %1, %2;" : "=r"(rel_bar) : "r"(bars + kBarEmpty), "r"(tid & 1));
        const uint32_t b_lo0 = ((sbase & 0x3FFFF) >> 4) | 0x10000u;
        const uint32_t frag_off = ((lane >> 4) * 8 + (lane & 7)) * 128 + (((2 * warp + ((lane >> 3) & 1)) ^ (lane & 7)) << 4);
        const uint32_t st_addr = sbase + kOffOut + wg * kChunk + frag_off;
        const uint32_t p_addr = sbase + kOffP + wg * kChunk + tid * 16;
        uint4* const wf = &g_wfrag[0][rank][wg][0][tid];
        constexpr int kSet = 2 * 3 * 24 * 128;

        uint32_t n = 0;
        float acc[32];
        uint32_t w[96];

        mbar_wait(bars + kBarW + 8 * wg, 0);
#pragma unroll
        for (int s = 0; s < 24; s++)
            asm volatile("ldmatrix.sync.aligned.m8n8.x4.trans.shared.b16 {%0,%1,%2,%3}, [%4];"
                         : "=r"(w[4 * s]), "=r"(w[4 * s + 1]), "=r"(w[4 * s + 2]), "=r"(w[4 * s + 3])
                         : "r"(sbase + kOffW + wg * kTileBytes + frag_off + s * 2048) : "memory");
        if (threadIdx.x == 0) PROF_GT(0);
        asm volatile("bar.sync 4, 384;" ::: "memory");
        if (threadIdx.x == 0) PROF_GT(1);
        if (rel)
            for (int s = kFreeSlots; s < kStages; s++) mbar_arrive_cluster(rel_bar + 8 * s);
        if (cid == 6 % ncl) {
#pragma unroll
            for (int s = 0; s < 24; s++) wf[s * 128] = make_uint4(w[4 * s], w[4 * s + 1], w[4 * s + 2], w[4 * s + 3]);
            publish_warp();
            if (threadIdx.x == 0) PROF_GT(3);
        }
        for (int t = cid; t < 6; t += ncl, n += 6) {
            issue_chunk<0>(acc, w, n, bars, b_lo0, false);
            issue_chunk<1>(acc, w, n, bars, b_lo0, false);
            issue_chunk<2>(acc, w, n, bars, b_lo0, false);
            issue_chunk<3>(acc, w, n, bars, b_lo0, false);
            issue_chunk<4>(acc, w, n, bars, b_lo0, false);
            issue_chunk<5>(acc, w, n, bars, b_lo0, false);
            if (!NO_MMA) WG_WAIT(0);
            if (rel)
                for (int c = 0; c < 6; c++) mbar_arrive_cluster(rel_bar + slot8(n + c));
            if (threadIdx.x == 0) PROF_GT(2);
#pragma unroll
            for (int s = 0; s < 4; s++)
                wf[kSet + (4 * t + s) * 128] = make_uint4(pack_bf16(acc[8 * s], acc[8 * s + 1]), pack_bf16(acc[8 * s + 2], acc[8 * s + 3]),
                                                          pack_bf16(acc[8 * s + 4], acc[8 * s + 5]), pack_bf16(acc[8 * s + 6], acc[8 * s + 7]));
            publish_warp();
            if (threadIdx.x == 0) PROF_GT(3);
        }
        const int tok_in = 1 + wg, tok_out = wg == 2 ? 1 : wg + 2;
        if (TOKEN_K && wg == 2) asm volatile("bar.arrive 1, 256;" ::: "memory");
        uint32_t nstore = 0;
        int left = nunits, gs = min(first_group, nunits), t = 0;
        bool rdy = false;
#pragma unroll 1
        while (left > 0) {
            const uint4* swap = nullptr;
            if (t == gs - 1) {
                mbar_wait(bars + kBarReady, 0);
                swap = wf + kSet;
            } else if (t == 5 * gs - 1 && left > gs) {
                swap = wf;
            }
            const bool pass = TOKEN_K && !(wg == 2 && t == 5 * gs - 1 && left == gs);
            if (TOKEN_K) asm volatile("bar.sync %0, 256;" ::"r"(tok_in) : "memory");
            rdy = issue_chunk<0>(acc, w, n, bars, b_lo0, rdy);
            if (TOKEN_K == 1 && pass) asm volatile("bar.arrive %0, 256;" ::"r"(tok_out) : "memory");
            rdy = issue_chunk<1>(acc, w, n, bars, b_lo0, rdy);
            if (TOKEN_K == 2 && pass) asm volatile("bar.arrive %0, 256;" ::"r"(tok_out) : "memory");
            retire_chunk<0, 1>(w, n, rel_bar, rel, swap);
            rdy = issue_chunk<2>(acc, w, n, bars, b_lo0, rdy);
            if (TOKEN_K == 3 && pass) asm volatile("bar.arrive %0, 256;" ::"r"(tok_out) : "memory");
            retire_chunk<1, 1>(w, n, rel_bar, rel, swap);
            rdy = issue_chunk<3>(acc, w, n, bars, b_lo0, rdy);
            retire_chunk<2, 1>(w, n, rel_bar, rel, swap);
            rdy = issue_chunk<4>(acc, w, n, bars, b_lo0, rdy);
            retire_chunk<3, 1>(w, n, rel_bar, rel, swap);
            if (t >= gs) {
                const int f = t - gs;
                uint32_t v[8];
#pragma unroll
                for (int q = 0; q < 2; q++)
                    asm volatile("ld.shared.v4.u32 {%0,%1,%2,%3}, [%4];" : "=r"(v[4 * q]), "=r"(v[4 * q + 1]), "=r"(v[4 * q + 2]), "=r"(v[4 * q + 3])
                                 : "r"(p_addr + (f >> 2) * 3 * kChunk + (f & 1) * 4096 + q * 2048) : "memory");
                const bool free_ok = mbar_test(bars + kBarFree + 8 * wg, (nstore & 1) ^ 1);
                rdy = issue_chunk<5>(acc, w, n, bars, b_lo0, rdy);
                retire_chunk<4, 1>(w, n, rel_bar, rel, swap);
                float pl[8], ph[8];
#pragma unroll
                for (int j = 0; j < 8; j++) {
                    pl[j] = __uint_as_float(v[j] << 16);
                    ph[j] = __uint_as_float(v[j] & 0xffff0000u);
                    asm volatile("" : "+f"(pl[j]), "+f"(ph[j]));
                }
                if (!free_ok) mbar_wait(bars + kBarFree + 8 * wg, (nstore & 1) ^ 1);
                nstore++;
                retire_chunk<5, 0>(w, n, rel_bar, rel, swap);
                if (threadIdx.x == 0) PROF_REC2(6, n + 7);
#pragma unroll
                for (int q = 0; q < 4; q++)
                    asm volatile("stmatrix.sync.aligned.m8n8.x4.trans.shared.b16 [%0], {%1,%2,%3,%4};" ::"r"(st_addr + q * 2048),
                                 "r"(pack_bf16(acc[8 * q] + pl[2 * q], acc[8 * q + 1] + pl[2 * q])),
                                 "r"(pack_bf16(acc[8 * q + 2] + ph[2 * q], acc[8 * q + 3] + ph[2 * q])),
                                 "r"(pack_bf16(acc[8 * q + 4] + pl[2 * q + 1], acc[8 * q + 5] + pl[2 * q + 1])),
                                 "r"(pack_bf16(acc[8 * q + 6] + ph[2 * q + 1], acc[8 * q + 7] + ph[2 * q + 1])) : "memory");
                __syncwarp();
                if (lane == 0) asm volatile("mbarrier.arrive.shared::cta.b64 _, [%0];" ::"r"(bars + kBarStaged + 8 * wg) : "memory");
            } else {
                rdy = issue_chunk<5>(acc, w, n, bars, b_lo0, rdy);
                retire_chunk<4, 1>(w, n, rel_bar, rel, swap);
                retire_chunk<5, 0>(w, n, rel_bar, rel, swap);
#pragma unroll
                for (int q = 0; q < 4; q++)
                    asm volatile("st.shared.v4.u32 [%0], {%1,%2,%3,%4};" ::"r"(p_addr + t * 3 * kChunk + q * 2048),
                                 "r"(pack_bf16(acc[8 * q], acc[8 * q + 2])), "r"(pack_bf16(acc[8 * q + 1], acc[8 * q + 3])),
                                 "r"(pack_bf16(acc[8 * q + 4], acc[8 * q + 6])), "r"(pack_bf16(acc[8 * q + 5], acc[8 * q + 7])) : "memory");
            }
            if (threadIdx.x == 0) PROF_REC2(7, n + 7);
            n += 6;
            if (++t == 5 * gs) {
                left -= gs;
                gs = min(kGroup, left);
                t = 0;
            }
        }
    }
    asm volatile("barrier.cluster.arrive.release.aligned;" ::: "memory");
    asm volatile("barrier.cluster.wait.acquire.aligned;" ::: "memory");
}

typedef CUresult (*EncodeFn)(CUtensorMap*, CUtensorMapDataType, cuuint32_t, void*, const cuuint64_t*, const cuuint64_t*,
                             const cuuint32_t*, const cuuint32_t*, CUtensorMapInterleave, CUtensorMapSwizzle,
                             CUtensorMapL2promotion, CUtensorMapFloatOOBfill);

void encode_2d(EncodeFn enc, CUtensorMap* tm, const void* ptr, uint64_t rows, uint32_t box_rows, CUtensorMapL2promotion promo) {
    cuuint64_t dims[2] = {(cuuint64_t)kC, rows};
    cuuint64_t strides[1] = {(cuuint64_t)kC * 2};
    cuuint32_t box[2] = {64, box_rows};
    cuuint32_t es[2] = {1, 1};
    enc(tm, CU_TENSOR_MAP_DATA_TYPE_BFLOAT16, 2, const_cast<void*>(ptr), dims, strides, box, es, CU_TENSOR_MAP_INTERLEAVE_NONE,
        CU_TENSOR_MAP_SWIZZLE_128B, promo, CU_TENSOR_MAP_FLOAT_OOB_FILL_NONE);
}

}

extern "C" void kernel_launch(void* const* d_in, const int* in_sizes, int n_in, void* d_out, int out_size) {
    (void)in_sizes; (void)n_in; (void)out_size;
    static EncodeFn enc = nullptr;
    static int grid = 0;
    if (!enc) {
        void* fn = nullptr;
        cudaDriverEntryPointQueryResult qr;
        cudaGetDriverEntryPoint("cuTensorMapEncodeTiled", &fn, cudaEnableDefault, &qr);
        enc = (EncodeFn)fn;
        cudaFuncSetAttribute(fpn_lateral_kernel, cudaFuncAttributeMaxDynamicSharedMemorySize, kSmemBytes);
        cudaLaunchConfig_t cfg = {};
        cfg.gridDim = dim3(2);
        cfg.blockDim = dim3(512);
        cfg.dynamicSmemBytes = kSmemBytes;
        cudaLaunchAttribute at;
        at.id = cudaLaunchAttributeClusterDimension;
        at.val.clusterDim.x = 2; at.val.clusterDim.y = 1; at.val.clusterDim.z = 1;
        cfg.attrs = &at; cfg.numAttrs = 1;
        int ncl = 0;
        if (cudaOccupancyMaxActiveClusters(&ncl, fpn_lateral_kernel, &cfg) != cudaSuccess || ncl < 1) { (void)cudaGetLastError(); ncl = 64; }
        if (ncl > 64) ncl = 64;
        grid = 2 * ncl;
    }
    CUtensorMap tm_fine, tm_coarse, tm_wlat, tm_wout, tm_out;
    encode_2d(enc, &tm_fine, d_in[0], kFinePix, 32, L2PROMO);
    encode_2d(enc, &tm_wlat, d_in[2], kC, 32, CU_TENSOR_MAP_L2_PROMOTION_L2_256B);
    encode_2d(enc, &tm_wout, d_in[3], kC, 64, CU_TENSOR_MAP_L2_PROMOTION_L2_256B);
    encode_2d(enc, &tm_out, d_out, kFinePix, 64, CU_TENSOR_MAP_L2_PROMOTION_NONE);
    {
        cuuint64_t dims[4] = {(cuuint64_t)kC, 2, 4, (cuuint64_t)kCoarsePix / 8};
        cuuint64_t strides[3] = {4 * 768, 768, 8 * 768};
        cuuint32_t box[4] = {64, 2, 4, 4};
        cuuint32_t es[4] = {1, 1, 1, 1};
        enc(&tm_coarse, CU_TENSOR_MAP_DATA_TYPE_BFLOAT16, 4, d_in[1], dims, strides, box, es, CU_TENSOR_MAP_INTERLEAVE_NONE,
            CU_TENSOR_MAP_SWIZZLE_128B, L2PROMO, CU_TENSOR_MAP_FLOAT_OOB_FILL_NONE);
    }
    fpn_lateral_kernel<<<grid, 512, kSmemBytes>>>(tm_fine, tm_coarse, tm_wlat, tm_wout, tm_out, (const char*)d_in[0], (const char*)d_in[1]
                                                  );
}
```

```cpp
#include <cuda_runtime.h>
#include <cuda_bf16.h>
#include <cuda.h>
#include <stdint.h>
#include <string.h>

#define PF_INIT 2
#define LD_EF 0
#define PACE 32
#define PACE_FROM 12
#define TOKEN_K 3
#define PAT_A 54
#define PAT_B 45
#define TAKE -2, 0, 2
#define GIVE -4, -2, 0
#define PW0 2
#define PW1 0
#define PF0 1
#define PF_WAIT 2
#define NOGIVE_FROM 99
#define DROP_FROM 99
#define DROP_EVERY 4
#define LEAD_FROM 4
#define LEAD_MAX 4
#define LEAD_HOLD 10
#define LEAD_DECAY 3
#define W_FIRST 1
#define L_POS 0
#define NO_MMA 0
#define CURVE_REC(k, i) do {} while (0)

namespace {

constexpr int kC = 384;
constexpr int kFinePix = 384 * 384;
constexpr int kCoarsePix = 192 * 192;
constexpr int kClusters = 64;
constexpr int kTiles = 45;
constexpr int kSlots = 25;
constexpr int kChunk = 8192;
constexpr int kTileBytes = 6 * kChunk;
constexpr int kOffOut = kSlots * kChunk;
constexpr int kOffBar = kOffOut + 3 * kChunk;
constexpr int kSmemBytes = kOffBar + 1024;
constexpr int kSlotL = 8;
constexpr int kSlotW = 10;
constexpr int kBarFull = 0, kBarEmpty = 8 * kSlots, kBarW = 16 * kSlots, kBarL = kBarW + 24;
constexpr int kBarPiece = kBarL + 8, kBarReady = kBarPiece + 8, kBarGo = kBarReady + 8, kBarFree = kBarGo + 8, kBarStaged = kBarFree + 24;
constexpr int kStarted = kBarStaged + 24;
constexpr int kPieces = 24;

enum : uint32_t { F_FINE = 1, F_P = 2, F_SHIFT = 4, F_SWAP = 8, F_READY = 16 };
struct alignas(16) Tile {
    uint8_t chunk[7];
    uint8_t flags;
    uint8_t p[3];
    uint8_t unit, f;
    uint8_t pf[2];
    uint8_t pad;
};
struct Schedule {
    Tile tile[2][kTiles + 1];
    int pw[2][2];
};

__device__ uint4 g_wfrag[2][2][3][24][128];
__device__ uint32_t g_ready;
__device__ uint32_t g_done;
__device__ uint32_t g_progress;

__device__ __forceinline__ uint32_t smem_u32(const void* p) { return (uint32_t)__cvta_generic_to_shared(p); }

__device__ __forceinline__ void mbar_init(uint32_t bar, uint32_t count) {
    asm volatile("mbarrier.init.shared::cta.b64 [%0], %1;" ::"r"(bar), "r"(count) : "memory");
}
__device__ __forceinline__ void mbar_expect_tx(uint32_t bar, uint32_t bytes) {
    asm volatile("mbarrier.arrive.expect_tx.shared::cta.b64 _, [%0], %1;" ::"r"(bar), "r"(bytes) : "memory");
}
__device__ __forceinline__ void mbar_wait(uint32_t bar, uint32_t parity) {
    asm volatile(
        "{\n"
        ".reg .pred p;\n"
        ".reg .u32 n;\n"
        "mov.u32 n, 0;\n"
        "WAIT_LOOP:\n"
        "mbarrier.try_wait.parity.shared::cta.b64 p, [%0], %1;\n"
        "@p bra WAIT_DONE;\n"
        "add.u32 n, n, 1;\n"
        "setp.lt.u32 p, n, 0x400000;\n"
        "@p bra WAIT_LOOP;\n"
        "trap;\n"
        "WAIT_DONE:\n"
        "}\n" ::"r"(bar), "r"(parity) : "memory");
}
__device__ __forceinline__ bool mbar_test(uint32_t bar, uint32_t parity) {
    uint32_t r;
    asm volatile("{\n.reg .pred p;\nmbarrier.test_wait.parity.shared::cta.b64 p, [%1], %2;\nselp.u32 %0, 1, 0, p;\n}\n" : "=r"(r) : "r"(bar), "r"(parity) : "memory");
    return r != 0;
}
__device__ __forceinline__ void mbar_arrive(uint32_t bar) {
    asm volatile("mbarrier.arrive.shared::cta.b64 _, [%0];" ::"r"(bar) : "memory");
}
__device__ __forceinline__ void mbar_arrive_cluster(uint32_t bar) {
    asm volatile("mbarrier.arrive.shared::cluster.b64 _, [%0];" ::"r"(bar) : "memory");
}
__device__ __forceinline__ void mbar_arrive_cluster3(uint32_t bar) {
    asm volatile("mbarrier.arrive.shared::cluster.b64 _, [%0], 3;" ::"r"(bar) : "memory");
}
__device__ __forceinline__ void tma_load_2d(uint32_t dst, const CUtensorMap* tm, int c0, int c1, uint32_t bar) {
    asm volatile("cp.async.bulk.tensor.2d.shared::cluster.global.mbarrier::complete_tx::bytes [%0], [%1, {%2, %3}], [%4];"
                 ::"r"(dst), "l"(tm), "r"(c0), "r"(c1), "r"(bar) : "memory");
}
__device__ __forceinline__ void tma_load_3d(uint32_t dst, const CUtensorMap* tm, int c1, uint32_t bar) {
    asm volatile("cp.async.bulk.tensor.3d.shared::cluster.global.mbarrier::complete_tx::bytes [%0], [%1, {%2, %3, %2}], [%4];"
                 ::"r"(dst), "l"(tm), "r"(0), "r"(c1), "r"(bar) : "memory");
}
constexpr uint64_t kEvictNormal = 0x1000000000000000ull, kEvictFirst = 0x12F0000000000000ull;
__device__ __forceinline__ void tma_load_2d_mc(uint32_t dst, const CUtensorMap* tm, int c0, int c1, uint32_t bar) {
    asm volatile("cp.async.bulk.tensor.2d.shared::cluster.global.mbarrier::complete_tx::bytes.multicast::cluster.L2::cache_hint [%0], [%1, {%2, %3}], [%4], %5, %6;"
                 ::"r"(dst), "l"(tm), "r"(c0), "r"(c1), "r"(bar), "h"((uint16_t)3), "l"(LD_EF ? kEvictFirst : kEvictNormal) : "memory");
}
__device__ __forceinline__ void tma_load_4d_mc(uint32_t dst, const CUtensorMap* tm, int c0, int c3, uint32_t bar) {
    asm volatile("cp.async.bulk.tensor.4d.shared::cluster.global.mbarrier::complete_tx::bytes.multicast::cluster.L2::cache_hint [%0], [%1, {%2, %3, %3, %4}], [%5], %6, %7;"
                 ::"r"(dst), "l"(tm), "r"(c0), "r"(0), "r"(c3), "r"(bar), "h"((uint16_t)3), "l"(LD_EF ? kEvictFirst : kEvictNormal) : "memory");
}
__device__ __forceinline__ void tma_store_2d(const CUtensorMap* tm, uint32_t src, int c0, int c1) {
    asm volatile("cp.async.bulk.tensor.2d.global.shared::cta.bulk_group [%0, {%2, %3}], [%1];"
                 ::"l"(tm), "r"(src), "r"(c0), "r"(c1) : "memory");
}
__device__ __forceinline__ void prefetch_l2(const void* p) {
    asm volatile("prefetch.global.L2 [%0];" ::"l"(p) : "memory");
}
__device__ __forceinline__ void prefetch_tm(const CUtensorMap* tm) {
    asm volatile("prefetch.tensormap [%0];" ::"l"(tm) : "memory");
}
__device__ __forceinline__ bool elect_one() {
    uint32_t p;
    asm volatile("{\n.reg .pred p;\nelect.sync _|p, 0xffffffff;\nselp.u32 %0, 1, 0, p;\n}\n" : "=r"(p));
    return p != 0;
}
__device__ __forceinline__ void wait_started(uint32_t bars, uint32_t t) {
    uint32_t v;
    for (uint32_t n = 0;; n++) {
        asm volatile("ld.volatile.shared.u32 %0, [%1];" : "=r"(v) : "r"(bars + kStarted) : "memory");
        if (v > t) break;
        if (n == 0x1000000) __trap();
        __nanosleep(40);
    }
}
#define CLUSTER_ARRIVE() asm volatile("barrier.cluster.arrive.relaxed.aligned;" ::: "memory")
#define CLUSTER_WAIT() asm volatile("barrier.cluster.wait.acquire.aligned;" ::: "memory")

#define WG_FENCE() asm volatile("wgmma.fence.sync.aligned;" ::: "memory")
#define WG_COMMIT() asm volatile("wgmma.commit_group.sync.aligned;" ::: "memory")
#define WG_WAIT(n) asm volatile("wgmma.wait_group.sync.aligned %0;" ::"n"(n) : "memory")

#define ACC32 "{%0,%1,%2,%3,%4,%5,%6,%7,%8,%9,%10,%11,%12,%13,%14,%15,%16,%17,%18,%19,%20,%21,%22,%23,%24,%25,%26,%27,%28,%29,%30,%31}"
#define ACC8(b) "+f"(d[b]), "+f"(d[b + 1]), "+f"(d[b + 2]), "+f"(d[b + 3]), "+f"(d[b + 4]), "+f"(d[b + 5]), "+f"(d[b + 6]), "+f"(d[b + 7])

#define DESC_HI "0x40000040"
template <int BOFF>
__device__ __forceinline__ void wgmma_rs(float (&d)[32], const uint32_t* a, uint32_t b_lo) {
    asm volatile("{\n.reg .b32 tb;\n.reg .b64 db;\nadd.u32 tb, %36, %37;\nmov.b64 db, {tb, " DESC_HI "};\n"
                 "wgmma.mma_async.sync.aligned.m64n64k16.f32.bf16.bf16 " ACC32 ", {%32,%33,%34,%35}, db, 1, 1, 1, 0;\n}\n"
                 : ACC8(0), ACC8(8), ACC8(16), ACC8(24)
                 : "r"(a[0]), "r"(a[1]), "r"(a[2]), "r"(a[3]), "r"(b_lo), "n"(BOFF));
}
__device__ __forceinline__ void wgmma_rs_first(float (&d)[32], const uint32_t* a, uint32_t b_lo, uint32_t accum) {
    asm volatile("{\n.reg .pred p;\n.reg .b64 db;\nsetp.ne.u32 p, %37, 0;\nmov.b64 db, {%36, " DESC_HI "};\n"
                 "wgmma.mma_async.sync.aligned.m64n64k16.f32.bf16.bf16 " ACC32 ", {%32,%33,%34,%35}, db, p, 1, 1, 0;\n}\n"
                 : ACC8(0), ACC8(8), ACC8(16), ACC8(24)
                 : "r"(a[0]), "r"(a[1]), "r"(a[2]), "r"(a[3]), "r"(b_lo), "r"(accum));
}
template <int ACCUM, int BOFF>
__device__ __forceinline__ void wgmma_rs16(float (&d)[32], const uint32_t* a, uint32_t b_lo) {
    asm volatile("{\n.reg .b32 tb;\n.reg .b64 db;\nadd.u32 tb, %12, %13;\nmov.b64 db, {tb, " DESC_HI "};\n"
                 "wgmma.mma_async.sync.aligned.m64n16k16.f32.bf16.bf16 {%0,%1,%2,%3,%4,%5,%6,%7}, {%8,%9,%10,%11}, db, %14, 1, 1, 0;\n}\n"
                 : ACC8(0)
                 : "r"(a[0]), "r"(a[1]), "r"(a[2]), "r"(a[3]), "r"(b_lo), "n"(BOFF), "n"(ACCUM));
}
template <int S>
__device__ __forceinline__ void piece_steps(float (&d)[32], const uint32_t (&w)[96], uint32_t b_lo) {
    if constexpr (S < 24) {
        wgmma_rs16<(S > 0), (S >> 2) * 128 + (S & 3) * 2>(d, &w[4 * S], b_lo);
        piece_steps<S + 1>(d, w, b_lo);
    }
}

__device__ __forceinline__ uint32_t pack_bf16(float lo, float hi) {
    uint32_t r;
    asm("cvt.rn.bf16x2.f32 %0, %1, %2;" : "=r"(r) : "f"(hi), "f"(lo));
    return r;
}

template <int C>
__device__ __forceinline__ void reload_w(uint32_t (&w)[96], const char* base, uint32_t tid16, uint32_t on) {
#define W4(i) "+r"(w[16 * C + 4 * i]), "+r"(w[16 * C + 4 * i + 1]), "+r"(w[16 * C + 4 * i + 2]), "+r"(w[16 * C + 4 * i + 3])
    asm volatile("{\n.reg .pred p;\n.reg .b64 a;\nsetp.ne.u32 p, %19, 0;\ncvt.u64.u32 a, %18;\nadd.u64 a, a, %16;\n"
                 "@p ld.global.cg.v4.u32 {%0,%1,%2,%3}, [a + %17];\n"
                 "@p ld.global.cg.v4.u32 {%4,%5,%6,%7}, [a + %17 + 2048];\n"
                 "@p ld.global.cg.v4.u32 {%8,%9,%10,%11}, [a + %17 + 4096];\n"
                 "@p ld.global.cg.v4.u32 {%12,%13,%14,%15}, [a + %17 + 6144];\n}\n"
                 : W4(0), W4(1), W4(2), W4(3)
                 : "l"(base), "n"(C * 8192), "r"(tid16), "r"(on) : "memory");
#undef W4
}

template <int C>
__device__ __forceinline__ uint32_t entry(uint2 e) { return C < 4 ? e.x >> (8 * C) : e.y >> (8 * (C - 4)); }

template <int C>
__device__ __forceinline__ bool issue_chunk(float (&acc)[32], const uint32_t (&w)[96], uint2 e, uint32_t bars, uint32_t b_lo0, bool ready) {
    if (!ready) mbar_wait(bars + kBarFull + (entry<C>(e) & 0xF8), entry<C>(e) & 1);
    const bool next = mbar_test(bars + kBarFull + (entry<C + 1>(e) & 0xF8), entry<C + 1>(e) & 1);
    const uint32_t b_lo = b_lo0 + (entry<C>(e) & 0xF8) * 64;
    if (!NO_MMA) {
        WG_FENCE();
        if (C == 0) wgmma_rs_first(acc, &w[0], b_lo, e.y & (F_FINE << 24));
        else wgmma_rs<0>(acc, &w[16 * C], b_lo);
        wgmma_rs<2>(acc, &w[16 * C + 4], b_lo);
        wgmma_rs<4>(acc, &w[16 * C + 8], b_lo);
        wgmma_rs<6>(acc, &w[16 * C + 12], b_lo);
        WG_COMMIT();
    }
    return next;
}
template <int C, int PENDING>
__device__ __forceinline__ void retire_chunk(uint32_t (&w)[96], uint2 e, uint32_t rel_bar, bool rel, const char* swap, uint32_t tid16) {
    if (!NO_MMA) WG_WAIT(PENDING);
    if (rel) mbar_arrive_cluster(rel_bar + (entry<C>(e) & 0xF8));
    reload_w<C>(w, swap, tid16, e.y & (F_SWAP << 24));
}

__device__ __forceinline__ int tile_row(const Tile& t, int cid) {
    const int u = cid + kClusters * t.unit;
    if (!(t.flags & F_FINE)) return u * 64;
    const int y = u / 3, xb = u - y * 3;
    return (2 * y + (t.f & 1)) * 384 + xb * 128 + (t.f >> 1) * 64;
}

__global__ void __cluster_dims__(2, 1, 1) __launch_bounds__(512, 1)
fpn_lateral_kernel(const __grid_constant__ CUtensorMap tm_fine, const __grid_constant__ CUtensorMap tm_coarse,
                   const __grid_constant__ CUtensorMap tm_wlat, const __grid_constant__ CUtensorMap tm_wout,
                   const __grid_constant__ CUtensorMap tm_out, const __grid_constant__ Schedule sched,
                   const char* __restrict__ fine, const char* __restrict__ coarse,
                   const char* __restrict__ wlat, const char* __restrict__ wout, int pace) {
    extern __shared__ __align__(1024) unsigned char smem_raw[];
    if (threadIdx.x == 0) CURVE_REC(0, 0);
    const uint32_t sbase = smem_u32(smem_raw);
    const uint32_t bars = sbase + kOffBar;
    const int warp_id = __shfl_sync(0xffffffffu, (int)(threadIdx.x >> 5), 0);
    const int lane = threadIdx.x & 31;
    const int wg = warp_id >> 2;
    const int rank = blockIdx.x & 1;
    const int cid = blockIdx.x >> 1;
    const Tile* const tiles = sched.tile[cid & 1];

    if (wg == 3) {
        asm volatile("setmaxnreg.dec.sync.aligned.u32 32;");
        const int j = warp_id & 3;
        const bool lead = elect_one();
        if (j == 3) {
            if (lead) {
                for (int i = 0; i < 4; i++) mbar_init(bars + kBarW + 8 * i, 1);
                asm volatile("fence.mbarrier_init.release.cluster;" ::: "memory");
            }
            __syncwarp();
            if (!W_FIRST) CLUSTER_ARRIVE();
            if (lead) {
                asm volatile("fence.proxy.async.shared::cta;" ::: "memory");
#pragma unroll 1
                for (int g = 0; g < 3; g++) {
                    mbar_expect_tx(bars + kBarW + 8 * g, kTileBytes);
                    for (int c = 0; c < 2; c++) tma_load_2d(sbase + (kSlotW + 6 * g + 3 * c) * kChunk, &tm_wout, rank * 192 + g * 64, c * 192, bars + kBarW + 8 * g);
                    if (g == L_POS && cid < kPieces) {
                        mbar_expect_tx(bars + kBarL, 6 * 2048);
                        tma_load_3d(sbase + kSlotL * kChunk, &tm_wlat, cid * 16, bars + kBarL);
                    }
                }
            }
            __syncwarp();
            if (W_FIRST) CLUSTER_ARRIVE();
            CLUSTER_WAIT();
            if (lead && cid < kPieces) {
                mbar_wait(bars + kBarPiece, 0);
                asm volatile("fence.acq_rel.gpu;" ::: "memory");
                asm volatile("red.relaxed.gpu.global.add.u32 [%0], 1;" ::"l"(&g_ready) : "memory");
                CURVE_REC(2, 61);
            }
            __syncwarp();
#pragma unroll 1
            for (int s = 0; s < 2; s++) {
                wait_started(bars, sched.pw[cid & 1][s]);
                const char* p = (const char*)&g_wfrag[s][rank][0][0][0] + lane * 128;
#pragma unroll 4
                for (int l = 0; l < 36; l++) prefetch_l2(p + l * 4096);
            }
        } else if (j == 2) {
            CLUSTER_ARRIVE();
            for (uint32_t l = blockIdx.x * 32 + lane; l < 2 * 2304; l += gridDim.x * 32) prefetch_l2(l < 2304 ? wout + l * 128 : wlat + (l - 2304) * 128);
            if (lead) prefetch_tm(&tm_coarse);
#pragma unroll 1
            for (int t = 0; t < 2 + PF_INIT; t++) {
                if (t == PF0) {
                    if (lead) {
                        prefetch_tm(&tm_fine);
                        prefetch_tm(&tm_out);
                    }
                    __syncwarp();
                    CLUSTER_WAIT();
                    mbar_wait(bars + kBarW + 8 * PF_WAIT, 0);
                }
                const char* p = (tiles[t].flags & F_FINE ? fine : coarse) + (size_t)(tile_row(tiles[t], cid) + rank * 32 + lane) * 768;
                for (int l = 0; l < 6; l++) prefetch_l2(p + l * 128);
            }
            if (lead) {
                uint32_t v, n = 0;
                for (;;) {
                    asm volatile("ld.acquire.gpu.global.u32 %0, [%1];" : "=r"(v) : "l"(&g_ready) : "memory");
                    if (v >= 2 * kPieces) break;
                    if (++n == 0x100000) __trap();
                    __nanosleep(50);
                }
                CURVE_REC(2, 62);
                mbar_arrive(bars + kBarReady);
                if (atomicAdd(&g_done, 1) == gridDim.x - 1) {
                    g_ready = 0;
                    g_done = 0;
                }
                if (rank == 0) {
#pragma unroll 1
                    for (uint32_t t = PACE_FROM; t < kTiles; t++) {
                        wait_started(bars, t - 1);
                        v = atomicInc(&g_progress, (kTiles - PACE_FROM) * kClusters - 1) + 1;
                        const int need = (t - PACE_FROM + 1) * kClusters - pace;
                        for (n = 0; n < 0x4000 && (int)v < need && (v != 0 || t < kTiles - 1); n++) {
                            __nanosleep(50);
                            asm volatile("ld.relaxed.gpu.global.u32 %0, [%1];" : "=r"(v) : "l"(&g_progress) : "memory");
                        }
                        mbar_arrive(bars + kBarGo);
                    }
                }
            }
        } else if (j == 1) {
            if (sbase & 1023) __trap();
            if (lead) {
                asm volatile("st.shared.u32 [%0], %1;" ::"r"(bars + kStarted), "r"(0) : "memory");
                mbar_init(bars + kBarFull + 8 * 24, 1);
                mbar_init(bars + kBarEmpty + 8 * 24, 6);
                for (int i = 0; i < 9; i++) mbar_init(bars + kBarPiece + 8 * i, i == 0 ? 12 : i < 6 ? 1 : 4);
                asm volatile("fence.acq_rel.cta;" ::: "memory");
                asm volatile("fence.mbarrier_init.release.cluster;" ::: "memory");
            }
            __syncwarp();
            CLUSTER_ARRIVE();
            CLUSTER_WAIT();
            if (lead) {
                uint32_t k = 0;
#pragma unroll 1
                for (int t = 0; t < kTiles; t++) {
                    if (!(tiles[t].flags & F_FINE)) continue;
                    const int row = tile_row(tiles[t], cid);
#pragma unroll
                    for (int g = 0; g < 3; g++) {
                        mbar_wait(bars + kBarStaged + 8 * g, k & 1);
                        if (g == 2) CURVE_REC(1, t);
                        asm volatile("fence.proxy.async.shared::cta;" ::: "memory");
                        tma_store_2d(&tm_out, sbase + kOffOut + g * kChunk, rank * 192 + g * 64, row);
                        asm volatile("cp.async.bulk.commit_group;" ::: "memory");
                        if (g > 0) {
                            asm volatile("cp.async.bulk.wait_group.read 1;" ::: "memory");
                            mbar_arrive(bars + kBarFree + 8 * g - 8);
                        }
                    }
                    asm volatile("cp.async.bulk.wait_group.read 0;" ::: "memory");
                    mbar_arrive(bars + kBarFree + 16);
                    CURVE_REC(3, t);
                    k++;
                }
            }
        } else {
            CLUSTER_ARRIVE();
            const uint32_t dst0 = sbase + rank * 4096;
            auto pf_ptr = [&](int i) -> const char* {
                if (i == 0) return nullptr;
                return (tiles[i].flags & F_FINE ? fine : coarse) + (size_t)(tile_row(tiles[i], cid) + rank * 32 + (lane >> 1)) * 768 + (lane & 1) * 128;
            };
            CLUSTER_WAIT();
#pragma unroll 1
            for (int t = 0; t < kTiles; t++) {
                const uint2 e = *(const uint2*)&tiles[t];
                const int row = tile_row(tiles[t], cid) + rank * 32;
                const char *pf = pf_ptr(tiles[t].pf[0]), *pf2 = pf_ptr(tiles[t].pf[1]);
                if (t >= PACE_FROM && rank == 0) mbar_wait(bars + kBarGo, (t - PACE_FROM) & 1);
                if (lead) {
                    asm volatile("st.volatile.shared.u32 [%0], %1;" ::"r"(bars + kStarted), "r"(t + 1) : "memory");
                    if (t) CURVE_REC(0, t);
                }
#pragma unroll
                for (int c = 0; c < 6; c++) {
                    const uint32_t x = c < 4 ? e.x >> (8 * c) : e.y >> (8 * (c - 4)), s8 = x & 0xF8;
                    mbar_wait(bars + kBarEmpty + s8, (x >> 1) & 1);
                    if (lead) {
                        mbar_expect_tx(bars + kBarFull + s8, kChunk);
                        if (e.y & (F_FINE << 24)) tma_load_2d_mc(dst0 + s8 * 1024, &tm_fine, c * 64, row, bars + kBarFull + s8);
                        else tma_load_4d_mc(dst0 + s8 * 1024, &tm_coarse, c * 64, row >> 3, bars + kBarFull + s8);
                    }
                    if (pf2 != nullptr) {
                        const char* q = (c < 3 ? pf : pf2) + c % 3 * 256;
                        prefetch_l2(q);
                        prefetch_l2(q + 16 * 768);
                    } else if (c % 2 == 0 && pf != nullptr) {
                        prefetch_l2(pf + c * 128);
                        prefetch_l2(pf + c * 128 + 16 * 768);
                    }
                }
            }
        }
        __syncwarp();
    } else {
        if (elect_one()) {
            for (int i = 2 * warp_id; i < 2 * warp_id + 2; i++) {
                mbar_init(bars + kBarFull + 8 * i, 1);
                mbar_init(bars + kBarEmpty + 8 * i, 6);
            }
            asm volatile("fence.mbarrier_init.release.cluster;" ::: "memory");
        }
        __syncwarp();
        CLUSTER_ARRIVE();
        asm volatile("setmaxnreg.inc.sync.aligned.u32 160;");
        const int tid = threadIdx.x & 127;
        const int warp = tid >> 5;
        const bool rel = tid < 2;
        uint32_t rel_bar;
        asm("mapa.shared::cluster.u32 %0, %1, %2;" : "=r"(rel_bar) : "r"(bars + kBarEmpty), "r"(tid & 1));
        const uint32_t b_lo0 = ((sbase & 0x3FFFF) >> 4) | 0x10000u;
        const uint32_t frag_off = ((lane >> 4) * 8 + (lane & 7)) * 128 + (((2 * warp + ((lane >> 3) & 1)) ^ (lane & 7)) << 4);
        uint32_t st_addr = sbase + kOffOut + wg * kChunk + frag_off, tid16 = tid * 16;
        asm volatile("" : "+r"(st_addr), "+r"(tid16));
        uint4* const wf = &g_wfrag[0][rank][wg][0][tid];
        constexpr int kSet = 2 * 3 * 24 * 128;

        float acc[32];
        uint32_t w[96], p[16];

        CLUSTER_WAIT();
        mbar_wait(bars + kBarW + 8 * wg, 0);
        const uint32_t w_addr = sbase + (kSlotW + 6 * wg) * kChunk + frag_off;
#pragma unroll
        for (int s = 0; s < 24; s++)
            asm volatile("ldmatrix.sync.aligned.m8n8.x4.trans.shared.b16 {%0,%1,%2,%3}, [%4];"
                         : "=r"(w[4 * s]), "=r"(w[4 * s + 1]), "=r"(w[4 * s + 2]), "=r"(w[4 * s + 3]) : "r"(w_addr + s * 2048) : "memory");
        if (cid < kPieces) {
            asm volatile("ldmatrix.sync.aligned.m8n8.x4.trans.shared.b16 {%0,%1,%2,%3}, [%4];"
                         : "=r"(p[0]), "=r"(p[1]), "=r"(p[2]), "=r"(p[3]) : "r"(w_addr + cid * 2048) : "memory");
            wf[cid * 128] = make_uint4(p[0], p[1], p[2], p[3]);
        }
        asm volatile("bar.sync %0, 128;" ::"r"(4 + wg) : "memory");
        if (tid < 12 && kSlotW + 6 * wg + (tid >> 1) < kSlots) mbar_arrive_cluster3(rel_bar + 8 * (kSlotW + 6 * wg + (tid >> 1)));
        if (threadIdx.x == 0) CURVE_REC(2, 59);
        if (cid < kPieces) {
            mbar_wait(bars + kBarL, 0);
            WG_FENCE();
            piece_steps<0>(acc, w, b_lo0 + kSlotL * 512);
            WG_COMMIT();
            WG_WAIT(0);
            wf[kSet + cid * 128] = make_uint4(pack_bf16(acc[0], acc[1]), pack_bf16(acc[2], acc[3]), pack_bf16(acc[4], acc[5]), pack_bf16(acc[6], acc[7]));
            __syncwarp();
            if (lane == 0) mbar_arrive(bars + kBarPiece);
        }
        if (tid < 4) mbar_arrive_cluster(rel_bar + 8 * (kSlotL + (tid >> 1)));
        if (threadIdx.x == 256) CURVE_REC(2, 60);
#pragma unroll
        for (int i = 0; i < 16; i++) p[i] = 0;

        const int tok_in = 1 + wg, tok_out = wg == 2 ? 1 : wg + 2;
        if (TOKEN_K && wg == 2) asm volatile("bar.arrive 1, 256;" ::: "memory");
        uint32_t nstore = 1;
        bool rdy = false;
#pragma unroll 1
        for (int t = 0; t < kTiles; t++) {
            const uint2 e = *(const uint2*)&tiles[t];
            const uint32_t fl = e.y >> 24, pe = tiles[t].p[wg];
            const uint32_t p_addr = sbase + (pe & 0xF8) * 1024 + tid16;
            if ((~fl & (F_FINE | F_P)) == 0) {
#pragma unroll
                for (int q = 0; q < 4; q++)
                    asm volatile("ld.shared.v4.u32 {%0,%1,%2,%3}, [%4];" : "=r"(p[4 * q]), "=r"(p[4 * q + 1]), "=r"(p[4 * q + 2]), "=r"(p[4 * q + 3])
                                 : "r"(p_addr + q * 2048) : "memory");
            }
            if (fl & F_SHIFT) {
#pragma unroll
                for (int i = 0; i < 8; i++) p[i] = p[8 + i];
            }
#pragma unroll
            for (int i = 0; i < 8; i++)
                asm volatile("shl.b32 %0, %4, 16;\nshl.b32 %1, %4, 16;\nand.b32 %2, %4, 0xffff0000;\nand.b32 %3, %4, 0xffff0000;"
                             : "=f"(acc[4 * i]), "=f"(acc[4 * i + 1]), "=f"(acc[4 * i + 2]), "=f"(acc[4 * i + 3]) : "r"(p[i]));
            if (fl & F_READY) mbar_wait(bars + kBarReady, 0);
            const char* swap = (const char*)&g_wfrag[~fl & F_FINE][rank][wg][0][0];
            if (TOKEN_K) asm volatile("bar.sync %0, 256;" ::"r"(tok_in) : "memory");
            rdy = issue_chunk<0>(acc, w, e, bars, b_lo0, rdy);
            if (TOKEN_K == 1) asm volatile("bar.arrive %0, 256;" ::"r"(tok_out) : "memory");
            rdy = issue_chunk<1>(acc, w, e, bars, b_lo0, rdy);
            if (TOKEN_K == 2) asm volatile("bar.arrive %0, 256;" ::"r"(tok_out) : "memory");
            retire_chunk<0, 1>(w, e, rel_bar, rel, swap, tid16);
            if (rel && (~fl & (F_FINE | F_P)) == 0) mbar_arrive_cluster3(rel_bar + (pe & 0xF8));
            rdy = issue_chunk<2>(acc, w, e, bars, b_lo0, rdy);
            if (TOKEN_K == 3) asm volatile("bar.arrive %0, 256;" ::"r"(tok_out) : "memory");
            retire_chunk<1, 1>(w, e, rel_bar, rel, swap, tid16);
            rdy = issue_chunk<3>(acc, w, e, bars, b_lo0, rdy);
            retire_chunk<2, 1>(w, e, rel_bar, rel, swap, tid16);
            rdy = issue_chunk<4>(acc, w, e, bars, b_lo0, rdy);
            retire_chunk<3, 1>(w, e, rel_bar, rel, swap, tid16);
            rdy = issue_chunk<5>(acc, w, e, bars, b_lo0, rdy);
            retire_chunk<4, 1>(w, e, rel_bar, rel, swap, tid16);
            if (fl & F_FINE) {
                mbar_wait(bars + kBarFree + 8 * wg, nstore & 1);
                nstore++;
                retire_chunk<5, 0>(w, e, rel_bar, rel, swap, tid16);
#pragma unroll
                for (int q = 0; q < 4; q++)
                    asm volatile("stmatrix.sync.aligned.m8n8.x4.trans.shared.b16 [%0], {%1,%2,%3,%4};" ::"r"(st_addr + q * 2048),
                                 "r"(pack_bf16(acc[8 * q], acc[8 * q + 1])), "r"(pack_bf16(acc[8 * q + 2], acc[8 * q + 3])),
                                 "r"(pack_bf16(acc[8 * q + 4], acc[8 * q + 5])), "r"(pack_bf16(acc[8 * q + 6], acc[8 * q + 7])) : "memory");
                __syncwarp();
                if (elect_one()) mbar_arrive(bars + kBarStaged + 8 * wg);
            } else {
                if (fl & F_P) mbar_wait(bars + kBarEmpty + (pe & 0xF8), (pe >> 1) & 1);
                retire_chunk<5, 0>(w, e, rel_bar, rel, swap, tid16);
#pragma unroll
                for (int q = 0; q < 4; q++) {
                    p[4 * q] = pack_bf16(acc[8 * q], acc[8 * q + 2]);
                    p[4 * q + 1] = pack_bf16(acc[8 * q + 1], acc[8 * q + 3]);
                    p[4 * q + 2] = pack_bf16(acc[8 * q + 4], acc[8 * q + 6]);
                    p[4 * q + 3] = pack_bf16(acc[8 * q + 5], acc[8 * q + 7]);
                    if (fl & F_P)
                        asm volatile("st.shared.v4.u32 [%0], {%1,%2,%3,%4};" ::"r"(p_addr + q * 2048),
                                     "r"(p[4 * q]), "r"(p[4 * q + 1]), "r"(p[4 * q + 2]), "r"(p[4 * q + 3]) : "memory");
                }
            }
        }
        if (TOKEN_K && wg == 0) asm volatile("bar.sync 1, 256;" ::: "memory");
    }
    CLUSTER_ARRIVE();
    CLUSTER_WAIT();
    if (threadIdx.x == 0) CURVE_REC(0, 63);
}

void build_schedule(Tile* tl, int* pw, const int* gs) {
    const int take[3] = {TAKE}, give[3] = {GIVE};
    int coarse_of[16];
    int n = 0;
    for (int g = 0, i0 = 0; gs[g]; i0 += gs[g], g++) {
        for (int i = 1; i <= gs[g]; i++, n++) {
            tl[n].unit = i0 + i % gs[g];
            tl[n].flags = i < gs[g] ? F_P : F_SWAP | (g == 0 ? F_READY : 0);
            coarse_of[tl[n].unit] = n;
            if (i == gs[g] && g > 0) pw[1] = n + PW1;
        }
        for (int i = 0; i < 4 * gs[g]; i++, n++) {
            tl[n].unit = i0 + i / 4;
            tl[n].f = i & 3;
            tl[n].flags = F_FINE | (i >= 4 && (i & 3) == 0 ? F_P : 0) | ((i & 3) == 2 ? F_SHIFT : 0);
            if (i == 4 * gs[g] - 1 && gs[g + 1]) tl[n].flags |= F_SWAP, pw[0] = n + PW0;
        }
    }
    for (int t = 0, next = 2 + PF_INIT; t < kTiles; t++) {
        int lead = t < LEAD_FROM ? 1 : t < LEAD_HOLD ? LEAD_MAX : LEAD_MAX - 1 - (t - LEAD_HOLD) / LEAD_DECAY;
        if (lead < 1) lead = 1;
        for (int i = 0; i < 2; i++)
            if (next <= t + lead && next < kTiles) tl[t].pf[i] = next++;
    }
    int uses[kSlots], loads[kSlots], queue[512], head = 0, tail = 0, slot_of[6 * kTiles];
    for (int s = 0; s < kSlots; s++) uses[s] = s >= kSlotL, loads[s] = 0;
    auto take_p = [&](int t, int w, int s) { tl[t].p[w] = s * 8 + ((uses[s] + 1) & 1) * 2; uses[s]++; };
    bool taken[kSlots] = {};
    for (int w = 0; w < 3; w++)
        if (take[w] < 0 && (tl[0].flags & F_P)) take_p(0, w, kSlotW + 6 * w + 2), taken[kSlotW + 6 * w + 2] = true;
    for (int s = 0; s < kSlotL; s++) queue[tail++] = s;
    for (int s = kSlotW; s < kSlots; s++) if (!taken[s]) queue[tail++] = s;
    for (int s = kSlotL; s < kSlotW; s++) queue[tail++] = s;
    for (int c = 0, r = 0; c < 6 * kTiles; c++) {
        for (; head == tail; r++) {
            bool to_p = false;
            for (int w = 0; w < 3; w++) {
                int x = r - take[w];
                if (x >= 0 && x % 6 == 0 && x / 6 < kTiles && (tl[x / 6].flags & (F_FINE | F_P)) == F_P) take_p(x / 6, w, slot_of[r]), to_p = true;
            }
            if (r >= 6 * DROP_FROM && (r - 6 * DROP_FROM) % DROP_EVERY == 0) to_p = true;
            if (!to_p) queue[tail++] = slot_of[r];
            for (int w = 0; w < 3; w++) {
                int x = r - give[w];
                if (x >= 0 && x % 6 == 0 && x / 6 < kTiles && (tl[x / 6].flags & (F_FINE | F_P)) == (F_FINE | F_P)) {
                    tl[x / 6].p[w] = tl[coarse_of[tl[x / 6].unit]].p[w];
                    if (x / 6 < NOGIVE_FROM) queue[tail++] = tl[x / 6].p[w] >> 3;
                }
            }
        }
        const int s = queue[head++];
        slot_of[c] = s;
        tl[c / 6].chunk[c % 6] = s * 8 + ((uses[s] + 1) & 1) * 2 + (loads[s] & 1);
        if (c % 6 == 0 && c) tl[c / 6 - 1].chunk[6] = tl[c / 6].chunk[0];
        uses[s]++, loads[s]++;
    }
    for (int t = 0; t < kTiles; t++)
        if ((tl[t].flags & (F_FINE | F_P)) == (F_FINE | F_P)) memcpy(tl[t].p, tl[coarse_of[tl[t].unit]].p, 3);
}

typedef CUresult (*EncodeFn)(CUtensorMap*, CUtensorMapDataType, cuuint32_t, void*, const cuuint64_t*, const cuuint64_t*,
                             const cuuint32_t*, const cuuint32_t*, CUtensorMapInterleave, CUtensorMapSwizzle,
                             CUtensorMapL2promotion, CUtensorMapFloatOOBfill);

void encode_2d(EncodeFn enc, CUtensorMap* tm, const void* ptr, uint64_t rows, uint32_t box_rows, CUtensorMapL2promotion promo) {
    cuuint64_t dims[2] = {(cuuint64_t)kC, rows};
    cuuint64_t strides[1] = {(cuuint64_t)kC * 2};
    cuuint32_t box[2] = {64, box_rows};
    cuuint32_t es[2] = {1, 1};
    enc(tm, CU_TENSOR_MAP_DATA_TYPE_BFLOAT16, 2, const_cast<void*>(ptr), dims, strides, box, es, CU_TENSOR_MAP_INTERLEAVE_NONE,
        CU_TENSOR_MAP_SWIZZLE_128B, promo, CU_TENSOR_MAP_FLOAT_OOB_FILL_NONE);
}

}

extern "C" void kernel_launch(void* const* d_in, const int* in_sizes, int n_in, void* d_out, int out_size) {
    (void)in_sizes; (void)n_in; (void)out_size;
    static EncodeFn enc = nullptr;
    static Schedule sched;
    static int pace = 0;
    if (!enc) {
        void* fn = nullptr;
        cudaDriverEntryPointQueryResult qr;
        cudaGetDriverEntryPoint("cuTensorMapEncodeTiled", &fn, cudaEnableDefault, &qr);
        enc = (EncodeFn)fn;
        cudaFuncSetAttribute(fpn_lateral_kernel, cudaFuncAttributeMaxDynamicSharedMemorySize, kSmemBytes);
        cudaLaunchConfig_t cfg = {};
        cfg.gridDim = dim3(2);
        cfg.blockDim = dim3(512);
        cfg.dynamicSmemBytes = kSmemBytes;
        cudaLaunchAttribute at;
        at.id = cudaLaunchAttributeClusterDimension;
        at.val.clusterDim.x = 2; at.val.clusterDim.y = 1; at.val.clusterDim.z = 1;
        cfg.attrs = &at; cfg.numAttrs = 1;
        int ncl = 0;
        if (cudaOccupancyMaxActiveClusters(&ncl, fpn_lateral_kernel, &cfg) != cudaSuccess) { (void)cudaGetLastError(); ncl = 0; }
        pace = ncl >= kClusters ? PACE : 1 << 20;
        int pa[8] = {}, pb[8] = {};
        for (int i = 0, d = PAT_A >= 1000 ? 1000 : PAT_A >= 100 ? 100 : 10; d; i++, d /= 10) pa[i] = PAT_A / d % 10;
        for (int i = 0, d = PAT_B >= 1000 ? 1000 : PAT_B >= 100 ? 100 : 10; d; i++, d /= 10) pb[i] = PAT_B / d % 10;
        build_schedule(sched.tile[0], sched.pw[0], pa);
        build_schedule(sched.tile[1], sched.pw[1], pb);
    }
    CUtensorMap tm_fine, tm_coarse, tm_wlat, tm_wout, tm_out;
    encode_2d(enc, &tm_fine, d_in[0], kFinePix, 32, CU_TENSOR_MAP_L2_PROMOTION_L2_128B);
    {
        cuuint64_t dims[3] = {64, (cuuint64_t)kC, 6};
        cuuint64_t strides[2] = {768, 128};
        cuuint32_t box[3] = {64, 16, 6};
        cuuint32_t es[3] = {1, 1, 1};
        enc(&tm_wlat, CU_TENSOR_MAP_DATA_TYPE_BFLOAT16, 3, d_in[2], dims, strides, box, es, CU_TENSOR_MAP_INTERLEAVE_NONE,
            CU_TENSOR_MAP_SWIZZLE_128B, CU_TENSOR_MAP_L2_PROMOTION_L2_256B, CU_TENSOR_MAP_FLOAT_OOB_FILL_NONE);
    }
    encode_2d(enc, &tm_wout, d_in[3], kC, 192, CU_TENSOR_MAP_L2_PROMOTION_L2_256B);
    encode_2d(enc, &tm_out, d_out, kFinePix, 64, CU_TENSOR_MAP_L2_PROMOTION_NONE);
    {
        cuuint64_t dims[4] = {(cuuint64_t)kC, 2, 4, (cuuint64_t)kCoarsePix / 8};
        cuuint64_t strides[3] = {4 * 768, 768, 8 * 768};
        cuuint32_t box[4] = {64, 2, 4, 4};
        cuuint32_t es[4] = {1, 1, 1, 1};
        enc(&tm_coarse, CU_TENSOR_MAP_DATA_TYPE_BFLOAT16, 4, d_in[1], dims, strides, box, es, CU_TENSOR_MAP_INTERLEAVE_NONE,
            CU_TENSOR_MAP_SWIZZLE_128B, CU_TENSOR_MAP_L2_PROMOTION_L2_128B, CU_TENSOR_MAP_FLOAT_OOB_FILL_NONE);
    }
    fpn_lateral_kernel<<<2 * kClusters, 512, kSmemBytes>>>(tm_fine, tm_coarse, tm_wlat, tm_wout, tm_out, sched, (const char*)d_in[0], (const char*)d_in[1],
                                                          (const char*)d_in[2], (const char*)d_in[3], pace);
}
```

```cpp
#include <cuda_runtime.h>
#include <cuda_bf16.h>
#include <cuda.h>
#include <stdint.h>
#include <string.h>
#include <type_traits>
#include <stdlib.h>

#define PF_INIT 2
#define LD_EF 0
#define PACE 32
#define PACE_FROM 12
#define TOKEN_K 3
#define PAT_A 54
#define PAT_B 45
#define TAKE -2, 0, 2
#define GIVE -4, -2, 0
#define PW0 3
#define PW1 -1
#define PF0 1
#define PF_WAIT 2
#define NOGIVE_FROM 99
#define DROP_FROM 99
#define DROP_EVERY 4
#define LEAD_FROM 4
#define LEAD_MAX 4
#define LEAD_HOLD 10
#define LEAD_DECAY 3
#define W_FIRST 1
#define L_POS 0
#define PF_MODE 0
#define NSTG 6
#define PACER 1
#define SHAPE 1
#define NPAT 2
#define PF_SPLIT 1
#define NO_MMA 0
#define CURVE_REC(k, i) do {} while (0)

#define P2(k) do {} while (0)
namespace {

constexpr int kC = 384;
constexpr int kFinePix = 384 * 384;
constexpr int kCoarsePix = 192 * 192;
constexpr int kClusters = 64;
constexpr int kTiles = 45;
#define SLOTS 25
constexpr int kSlots = SLOTS;
constexpr int kChunk = 8192;
constexpr int kTileBytes = 6 * kChunk;
constexpr int kOffOut = kSlots * kChunk;
constexpr int kOffBar = kOffOut + 3 * kChunk;
constexpr int kSmemBytes = kOffBar + 1024;
constexpr int kSlotL = kSlots - 17;
constexpr int kSlotW = kSlots - 15;
constexpr int kBarFull = 0, kBarEmpty = 8 * kSlots, kBarW = 16 * kSlots, kBarL = kBarW + 24;
constexpr int kBarPiece = kBarL + 8, kBarReady = kBarPiece + 8, kBarGo = kBarReady + 8, kBarFree = kBarGo + 8, kBarStaged = kBarFree + 24;
constexpr int kBarSwap = kBarStaged + 24;
constexpr int kBarReady2 = kBarSwap + 56;
constexpr int kStarted = kBarSwap + 192, kAllowed = kStarted + 4;
constexpr int kPieces = 24;

enum : uint32_t { F_FINE = 1, F_P = 2, F_SHIFT = 4, F_SWAP = 8, F_READY = 16, F_SWAPH = 32, F_STAGED = 64, F_SW1 = 128 };
struct alignas(16) Tile {
    uint8_t chunk[7];
    uint8_t flags;
    uint8_t p[3];
    uint8_t pw;
    uint16_t pos;
    uint16_t wcnt;
};
constexpr int kGroup = kClusters / NPAT;
struct Schedule {
    Tile tile[NPAT][kTiles + 1];
    uint16_t pf[NPAT][kTiles + 1][2];
    alignas(8) uint8_t wslot[NPAT][2][3][8];
    uint8_t worder[24];
    int members, pgroup;
    int pace_from, pace_to, pf_k, pf_first, gate1, psleep, hold;
    int need[NPAT][kTiles + 1];
    uint16_t vt[NPAT][kTiles + 1];
};
static int envi(const char*, int d) { return d; }
static const char* envs(const char*, const char* d) { return d; }

__device__ uint4 g_wfrag[2][2][3][24][128];
__device__ uint32_t g_ready;
__device__ uint32_t g_done;
__device__ uint32_t g_progress[4][32];

__device__ __forceinline__ uint32_t smem_u32(const void* p) { return (uint32_t)__cvta_generic_to_shared(p); }

__device__ __forceinline__ void mbar_init(uint32_t bar, uint32_t count) {
    asm volatile("mbarrier.init.shared::cta.b64 [%0], %1;" ::"r"(bar), "r"(count) : "memory");
}
__device__ __forceinline__ void mbar_expect_tx(uint32_t bar, uint32_t bytes) {
    asm volatile("mbarrier.arrive.expect_tx.shared::cta.b64 _, [%0], %1;" ::"r"(bar), "r"(bytes) : "memory");
}
__device__ __forceinline__ void mbar_wait(uint32_t bar, uint32_t parity) {
    asm volatile(
        "{\n"
        ".reg .pred p;\n"
        ".reg .u32 n;\n"
        "mov.u32 n, 0;\n"
        "WAIT_LOOP:\n"
        "mbarrier.try_wait.parity.shared::cta.b64 p, [%0], %1;\n"
        "@p bra WAIT_DONE;\n"
        "add.u32 n, n, 1;\n"
        "setp.lt.u32 p, n, 0x400000;\n"
        "@p bra WAIT_LOOP;\n"
        "trap;\n"
        "WAIT_DONE:\n"
        "}\n" ::"r"(bar), "r"(parity) : "memory");
}
__device__ __forceinline__ void mbar_wait1(uint32_t bar, uint32_t parity) {
    uint32_t r;
    asm volatile("{\n.reg .pred p;\nmbarrier.try_wait.parity.shared::cta.b64 p, [%1], %2;\nselp.u32 %0, 1, 0, p;\n}\n" : "=r"(r) : "r"(bar), "r"(parity) : "memory");
    if (!r) mbar_wait(bar, parity);
}
__device__ __forceinline__ bool mbar_test(uint32_t bar, uint32_t parity) {
    uint32_t r;
    asm volatile("{\n.reg .pred p;\nmbarrier.test_wait.parity.shared::cta.b64 p, [%1], %2;\nselp.u32 %0, 1, 0, p;\n}\n" : "=r"(r) : "r"(bar), "r"(parity) : "memory");
    return r != 0;
}
__device__ __forceinline__ void mbar_arrive(uint32_t bar) {
    asm volatile("mbarrier.arrive.shared::cta.b64 _, [%0];" ::"r"(bar) : "memory");
}
template <int N>
__device__ __forceinline__ void mbar_arrive_cluster(uint32_t bar) {
    if (N == 1) asm volatile("mbarrier.arrive.shared::cluster.b64 _, [%0];" ::"r"(bar) : "memory");
    else asm volatile("mbarrier.arrive.shared::cluster.b64 _, [%0], %1;" ::"r"(bar), "n"(N) : "memory");
}
__device__ __forceinline__ void bulk_load(uint32_t dst, const void* src, uint32_t bar) {
    asm volatile("cp.async.bulk.shared::cluster.global.mbarrier::complete_tx::bytes [%0], [%1], %2, [%3];"
                 ::"r"(dst), "l"(src), "n"(kChunk), "r"(bar) : "memory");
}
__device__ __forceinline__ void tma_load_2d(uint32_t dst, const CUtensorMap* tm, int c0, int c1, uint32_t bar) {
    asm volatile("cp.async.bulk.tensor.2d.shared::cluster.global.mbarrier::complete_tx::bytes [%0], [%1, {%2, %3}], [%4];"
                 ::"r"(dst), "l"(tm), "r"(c0), "r"(c1), "r"(bar) : "memory");
}
__device__ __forceinline__ void tma_load_3d(uint32_t dst, const CUtensorMap* tm, int c1, uint32_t bar) {
    asm volatile("cp.async.bulk.tensor.3d.shared::cluster.global.mbarrier::complete_tx::bytes [%0], [%1, {%2, %3, %2}], [%4];"
                 ::"r"(dst), "l"(tm), "r"(0), "r"(c1), "r"(bar) : "memory");
}
__device__ __forceinline__ void tma_load_5d_mc(uint32_t dst, const CUtensorMap* tm, int c0, int c3, int c4, uint32_t bar) {
    asm volatile("cp.async.bulk.tensor.5d.shared::cluster.global.mbarrier::complete_tx::bytes.multicast::cluster [%0], [%1, {%2, %3, %3, %4, %5}], [%6], %7;"
                 ::"r"(dst), "l"(tm), "r"(c0), "r"(0), "r"(c3), "r"(c4), "r"(bar), "h"((uint16_t)3) : "memory");
}
__device__ __forceinline__ void tma_store_4d(const CUtensorMap* tm, uint32_t src, int c0, int c3) {
    asm volatile("cp.async.bulk.tensor.4d.global.shared::cta.bulk_group [%0, {%2, %3, %3, %4}], [%1];"
                 ::"l"(tm), "r"(src), "r"(c0), "r"(0), "r"(c3) : "memory");
}
__device__ __forceinline__ void prefetch_l2(const void* p) {
    asm volatile("prefetch.global.L2 [%0];" ::"l"(p) : "memory");
}
__device__ __forceinline__ void prefetch_tm(const CUtensorMap* tm) {
    asm volatile("prefetch.tensormap [%0];" ::"l"(tm) : "memory");
}
__device__ __forceinline__ uint32_t now_ns() {
    uint32_t t;
    asm volatile("mov.u32 %0, %globaltimer_lo;" : "=r"(t));
    return t;
}
__device__ __forceinline__ bool elect_one() {
    uint32_t p;
    asm volatile("{\n.reg .pred p;\nelect.sync _|p, 0xffffffff;\nselp.u32 %0, 1, 0, p;\n}\n" : "=r"(p));
    return p != 0;
}
__device__ __forceinline__ void wait_started(uint32_t bars, uint32_t t) {
    uint32_t v;
    for (uint32_t n = 0;; n++) {
        asm volatile("ld.volatile.shared.u32 %0, [%1];" : "=r"(v) : "r"(bars + kStarted) : "memory");
        if (v > t) break;
        if (n == 0x1000000) __trap();
        __nanosleep(40);
    }
}
#define CLUSTER_ARRIVE() asm volatile("barrier.cluster.arrive.relaxed.aligned;" ::: "memory")
#define CLUSTER_WAIT() asm volatile("barrier.cluster.wait.acquire.aligned;" ::: "memory")

#define WG_FENCE() asm volatile("wgmma.fence.sync.aligned;" ::: "memory")
#define WG_COMMIT() asm volatile("wgmma.commit_group.sync.aligned;" ::: "memory")
#define WG_WAIT(n) asm volatile("wgmma.wait_group.sync.aligned %0;" ::"n"(n) : "memory")

#define ACC32 "{%0,%1,%2,%3,%4,%5,%6,%7,%8,%9,%10,%11,%12,%13,%14,%15,%16,%17,%18,%19,%20,%21,%22,%23,%24,%25,%26,%27,%28,%29,%30,%31}"
#define ACC8(b) "+f"(d[b]), "+f"(d[b + 1]), "+f"(d[b + 2]), "+f"(d[b + 3]), "+f"(d[b + 4]), "+f"(d[b + 5]), "+f"(d[b + 6]), "+f"(d[b + 7])

#define DESC_HI "0x40000040"
template <int BOFF>
__device__ __forceinline__ void wgmma_rs(float (&d)[32], const uint32_t* a, uint32_t b_lo) {
    asm volatile("{\n.reg .b32 tb;\n.reg .b64 db;\nadd.u32 tb, %36, %37;\nmov.b64 db, {tb, " DESC_HI "};\n"
                 "wgmma.mma_async.sync.aligned.m64n64k16.f32.bf16.bf16 " ACC32 ", {%32,%33,%34,%35}, db, 1, 1, 1, 0;\n}\n"
                 : ACC8(0), ACC8(8), ACC8(16), ACC8(24)
                 : "r"(a[0]), "r"(a[1]), "r"(a[2]), "r"(a[3]), "r"(b_lo), "n"(BOFF));
}
__device__ __forceinline__ void wgmma_rs_first(float (&d)[32], const uint32_t* a, uint32_t b_lo, uint32_t accum) {
    asm volatile("{\n.reg .pred p;\n.reg .b64 db;\nsetp.ne.u32 p, %37, 0;\nmov.b64 db, {%36, " DESC_HI "};\n"
                 "wgmma.mma_async.sync.aligned.m64n64k16.f32.bf16.bf16 " ACC32 ", {%32,%33,%34,%35}, db, p, 1, 1, 0;\n}\n"
                 : ACC8(0), ACC8(8), ACC8(16), ACC8(24)
                 : "r"(a[0]), "r"(a[1]), "r"(a[2]), "r"(a[3]), "r"(b_lo), "r"(accum));
}
template <int ACCUM, int BOFF>
__device__ __forceinline__ void wgmma_rs16(float (&d)[32], const uint32_t* a, uint32_t b_lo) {
    asm volatile("{\n.reg .b32 tb;\n.reg .b64 db;\nadd.u32 tb, %12, %13;\nmov.b64 db, {tb, " DESC_HI "};\n"
                 "wgmma.mma_async.sync.aligned.m64n16k16.f32.bf16.bf16 {%0,%1,%2,%3,%4,%5,%6,%7}, {%8,%9,%10,%11}, db, %14, 1, 1, 0;\n}\n"
                 : ACC8(0)
                 : "r"(a[0]), "r"(a[1]), "r"(a[2]), "r"(a[3]), "r"(b_lo), "n"(BOFF), "n"(ACCUM));
}
template <int S>
__device__ __forceinline__ void piece_steps(float (&d)[32], const uint32_t (&w)[96], uint32_t b_lo) {
    if constexpr (S < 24) {
        wgmma_rs16<(S > 0), (S >> 2) * 128 + (S & 3) * 2>(d, &w[4 * S], b_lo);
        piece_steps<S + 1>(d, w, b_lo);
    }
}

__device__ __forceinline__ uint32_t pack_bf16(float lo, float hi) {
    uint32_t r;
    asm("cvt.rn.bf16x2.f32 %0, %1, %2;" : "=r"(r) : "f"(hi), "f"(lo));
    return r;
}

template <int C>
__device__ __forceinline__ void reload_w(uint32_t (&w)[96], const char* base, uint32_t tid16, uint32_t on) {
#define W4(i) "+r"(w[16 * C + 4 * i]), "+r"(w[16 * C + 4 * i + 1]), "+r"(w[16 * C + 4 * i + 2]), "+r"(w[16 * C + 4 * i + 3])
    asm volatile("{\n.reg .pred p;\n.reg .b64 a;\nsetp.ne.u32 p, %19, 0;\ncvt.u64.u32 a, %18;\nadd.u64 a, a, %16;\n"
                 "@p ld.global.cg.v4.u32 {%0,%1,%2,%3}, [a + %17];\n"
                 "@p ld.global.cg.v4.u32 {%4,%5,%6,%7}, [a + %17 + 2048];\n"
                 "@p ld.global.cg.v4.u32 {%8,%9,%10,%11}, [a + %17 + 4096];\n"
                 "@p ld.global.cg.v4.u32 {%12,%13,%14,%15}, [a + %17 + 6144];\n}\n"
                 : W4(0), W4(1), W4(2), W4(3)
                 : "l"(base), "n"(C * 8192), "r"(tid16), "r"(on) : "memory");
#undef W4
}

template <int C>
__device__ __forceinline__ uint32_t entry(uint2 e) { return C < 4 ? e.x >> (8 * C) : e.y >> (8 * (C - 4)); }

template <int C>
__device__ __forceinline__ bool issue_chunk(float (&acc)[32], const uint32_t (&w)[96], uint2 e, uint32_t bars, uint32_t b_lo0, bool ready) {
    if (!ready) mbar_wait(bars + kBarFull + (entry<C>(e) & 0xF8), entry<C>(e) & 1);
    const bool next = mbar_test(bars + kBarFull + (entry<C + 1>(e) & 0xF8), entry<C + 1>(e) & 1);
    const uint32_t b_lo = b_lo0 + (entry<C>(e) & 0xF8) * 64;
    if (!NO_MMA) {
        WG_FENCE();
        if (C == 0) wgmma_rs_first(acc, &w[0], b_lo, e.y & (F_FINE << 24));
        else wgmma_rs<0>(acc, &w[16 * C], b_lo);
        wgmma_rs<2>(acc, &w[16 * C + 4], b_lo);
        wgmma_rs<4>(acc, &w[16 * C + 8], b_lo);
        wgmma_rs<6>(acc, &w[16 * C + 12], b_lo);
        WG_COMMIT();
    }
    return next;
}
template <int C, int PENDING, int MODE>
__device__ __forceinline__ void retire_chunk(uint32_t (&w)[96], uint2 e, const uint8_t (*ws)[3][8], int wg, uint32_t sbase, uint32_t rel_bar, bool rel, const char* swap, uint32_t tid16) {
    if (!NO_MMA) WG_WAIT(PENDING);
    if (rel) mbar_arrive_cluster<1>(rel_bar + (entry<C>(e) & 0xF8));
    if (MODE == 1 || (MODE == 2 && C < 6 - NSTG)) reload_w<C>(w, swap, tid16, 1);
    if (MODE == 2 && C >= 6 - NSTG) {
        const uint32_t x = ws[e.y >> 31][wg][C];
        mbar_wait(sbase + kOffBar + kBarSwap + 64 * wg + 8 * C, e.y >> 31);
        const uint32_t a = sbase + (x & 0xF8) * 1024 + tid16;
#pragma unroll
        for (int q = 0; q < 4; q++)
            asm volatile("ld.shared.v4.u32 {%0,%1,%2,%3}, [%4];" : "=r"(w[16 * C + 4 * q]), "=r"(w[16 * C + 4 * q + 1]), "=r"(w[16 * C + 4 * q + 2]), "=r"(w[16 * C + 4 * q + 3])
                         : "r"(a + q * 2048) : "memory");
        asm volatile("bar.sync %0, 128;" ::"r"(4 + wg + ((w[16 * C] | w[16 * C + 4] | w[16 * C + 8] | w[16 * C + 12]) & x & 1)) : "memory");
        if (rel) mbar_arrive_cluster<3>(rel_bar + (x & 0xF8));
    }
}

__device__ __forceinline__ int fine_group(uint32_t pos, int ci) {
    const uint32_t q = (pos & 0xFFF) + ci;
    return SHAPE ? q + q / 12 * 12 : 2 * q + (q / 6 + ((pos >> 12) & 1)) * 12;
}
constexpr int kRankF = SHAPE ? 12 : 1, kRankC = SHAPE ? 2 : 1, kSeg = SHAPE ? 16 : 32;
template <int L0, int L1>
__device__ __forceinline__ void prefetch_tile(uint32_t pos, int ci, int rank, int lane, const char* fine, const char* coarse) {
    const bool f = pos & 0x8000;
    const uint32_t row = f ? (fine_group(pos, ci) + kRankF * rank) * 32 : ((pos + kRankC * rank) * kGroup + ci) * kSeg;
    const char* p = (f ? fine : coarse) + (size_t)row * 768 + lane * 128;
    const char* q = SHAPE && !f ? p + (kGroup - 1) * kSeg * 768 : p;
#pragma unroll
    for (int l = L0; l < L1; l++) prefetch_l2((l < 3 ? p : q) + l * 4096);
}

__global__ void __cluster_dims__(2, 1, 1) __launch_bounds__(512, 1)
fpn_lateral_kernel(const __grid_constant__ CUtensorMap tm_fine, const __grid_constant__ CUtensorMap tm_coarse,
                   const __grid_constant__ CUtensorMap tm_wlat, const __grid_constant__ CUtensorMap tm_wout,
                   const __grid_constant__ CUtensorMap tm_out, const __grid_constant__ Schedule sched,
                   const char* __restrict__ fine, const char* __restrict__ coarse,
                   const char* __restrict__ wlat, const char* __restrict__ wout) {
    extern __shared__ __align__(1024) unsigned char smem_raw[];
    if (threadIdx.x == 0) CURVE_REC(0, 0);
    const uint32_t sbase = smem_u32(smem_raw);
    const uint32_t bars = sbase + kOffBar;
    const int warp_id = __shfl_sync(0xffffffffu, (int)(threadIdx.x >> 5), 0);
    const int lane = threadIdx.x & 31;
    const int wg = warp_id >> 2;
    const int rank = blockIdx.x & 1;
    const int cid = blockIdx.x >> 1;
    const int pat = cid % NPAT, ci = cid / NPAT;
    const Tile* const tiles = sched.tile[pat];

    if (wg == 3) {
        asm volatile("setmaxnreg.dec.sync.aligned.u32 32;");
        const int j = warp_id & 3;
        const bool lead = elect_one();
        if (j == 3) {
            if (lead) {
                for (int i = 0; i < 4; i++) mbar_init(bars + kBarW + 8 * i, 1);
                asm volatile("fence.mbarrier_init.release.cluster;" ::: "memory");
            }
            __syncwarp();
            if (!W_FIRST) CLUSTER_ARRIVE();
            if (lead) {
                asm volatile("fence.proxy.async.shared::cta;" ::: "memory");
#pragma unroll 1
                for (int g = 0; g < 3; g++) {
                    mbar_expect_tx(bars + kBarW + 8 * g, kTileBytes);
                    for (int c = 0; c < 2; c++) tma_load_2d(sbase + (kSlotW + 6 * g + 3 * c) * kChunk, &tm_wout, rank * 192 + g * 64, c * 192, bars + kBarW + 8 * g);
                    if (g == L_POS && cid < kPieces) {
                        mbar_expect_tx(bars + kBarL, 6 * 2048);
                        tma_load_3d(sbase + kSlotL * kChunk, &tm_wlat, cid * 16, bars + kBarL);
                    }
                }
            }
            __syncwarp();
            if (W_FIRST) CLUSTER_ARRIVE();
            CLUSTER_WAIT();
            if (lead && cid < kPieces) {
                mbar_wait(bars + kBarPiece, 0);
                asm volatile("fence.acq_rel.gpu;" ::: "memory");
                asm volatile("red.relaxed.gpu.global.add.u32 [%0], 1;" ::"l"(&g_ready) : "memory");
                CURVE_REC(2, 61);
            }
            __syncwarp();
            if (sched.pf_first <= sched.pf_k) mbar_wait(bars + kBarW + 8 * PF_WAIT, 0);
#pragma unroll 1
            for (int k = sched.pf_first; k <= sched.pf_k; k++) prefetch_tile<0, 6>(tiles[k].pos, ci, rank, lane, fine, coarse);
            if (sched.hold) mbar_wait(bars + kBarReady, 0);
#pragma unroll 1
            for (int t = 0; t < kTiles; t++) {
                const uint32_t pf = *(const uint32_t*)sched.pf[pat][t], pw = tiles[t].pw;
                if (pf == 0xFFFFFFFF && pw == 0) continue;
                wait_started(bars, 2 * t);
                if (pf != 0xFFFFFFFF) {
                    if (pf >= 0xFFFF0000 && PF_SPLIT) {
                        prefetch_tile<0, 3>(pf & 0xFFFF, ci, rank, lane, fine, coarse);
                        wait_started(bars, 2 * t + 1);
                        prefetch_tile<3, 6>(pf & 0xFFFF, ci, rank, lane, fine, coarse);
                    } else {
                        prefetch_tile<0, 6>(pf & 0xFFFF, ci, rank, lane, fine, coarse);
                        if (PF_SPLIT) wait_started(bars, 2 * t + 1);
                        if (pf < 0xFFFF0000) prefetch_tile<0, 6>(pf >> 16, ci, rank, lane, fine, coarse);
                    }
                }
                if (pw) {
                    const char* p = (const char*)&g_wfrag[pw - 1][rank][0][0][0] + lane * 128;
#pragma unroll 4
                    for (int l = 0; l < 36; l++) prefetch_l2(p + l * 4096);
                }
            }
        } else if (j == 2) {
            CLUSTER_ARRIVE();
            for (uint32_t l = blockIdx.x * 32 + lane; l < 2 * 2304; l += gridDim.x * 32) prefetch_l2(l < 2304 ? wout + l * 128 : wlat + (l - 2304) * 128);
            if (lead) prefetch_tm(&tm_coarse);
#pragma unroll 1
            for (int t = 0; t < sched.pf_first || t <= PF0; t++) {
                if (t == PF0) {
                    if (lead) {
                        prefetch_tm(&tm_fine);
                        prefetch_tm(&tm_out);
                    }
                    __syncwarp();
                    CLUSTER_WAIT();
                    mbar_wait(bars + kBarW + 8 * PF_WAIT, 0);
                    if (t >= sched.pf_first) break;
                }
                prefetch_tile<0, 6>(tiles[t].pos, ci, rank, lane, fine, coarse);
            }
            if (lead) {
                uint32_t v, n = 0;
                for (;;) {
                    asm volatile("ld.acquire.gpu.global.u32 %0, [%1];" : "=r"(v) : "l"(&g_ready) : "memory");
                    if (v >= 2 * kPieces) break;
                    if (++n == 0x100000) __trap();
                    __nanosleep(50);
                }
                CURVE_REC(2, 62);
                mbar_arrive(bars + kBarReady);
                asm volatile("fence.proxy.async.global;" ::: "memory");
                mbar_arrive(bars + kBarReady2);
                if (atomicAdd(&g_done, 1) == gridDim.x - 1) {
                    g_ready = 0;
                    g_done = 0;
                }
                if (rank == 0 || sched.gate1) {
                    const uint16_t* vt = sched.vt[pat];
                    uint32_t* const ctr = g_progress[sched.pgroup * pat];
                    const int members = sched.members, last = sched.pace_to - 1;
                    asm volatile("ld.relaxed.gpu.global.u32 %0, [%1];" : "=r"(v) : "l"(ctr) : "memory");
                    const uint32_t base = v - v % (members * 1024);
                    int counted = rank == 0 ? sched.pace_from - 1 : last, allowed = sched.pace_from;
#pragma unroll 1
                    for (n = 0; n < 0x10000 && (allowed <= last || counted < last); n++) {
                        int started;
                        asm volatile("ld.volatile.shared.u32 %0, [%1];" : "=r"(started) : "r"(bars + kStarted) : "memory");
                        started = (started + 1) >> 1;
                        if (counted < last && counted < started) {
                            const int upto = min(started, last);
                            asm volatile("red.relaxed.gpu.global.add.u32 [%0], %1;" ::"l"(ctr), "r"(vt[upto] - vt[counted]) : "memory");
                            counted = upto;
                        }
                        if (allowed <= last && started + 1 >= allowed) {
                            asm volatile("ld.relaxed.gpu.global.u32 %0, [%1];" : "=r"(v) : "l"(ctr) : "memory");
                            while (allowed <= last && (int)(v - base) >= sched.need[pat][allowed]) allowed++;
                            asm volatile("st.volatile.shared.u32 [%0], %1;" ::"r"(bars + kAllowed), "r"(allowed > last ? kTiles : allowed) : "memory");
                        }
                        __nanosleep(sched.psleep);
                    }
                    asm volatile("st.volatile.shared.u32 [%0], %1;" ::"r"(bars + kAllowed), "r"(kTiles) : "memory");
                    if (counted < last) asm volatile("red.relaxed.gpu.global.add.u32 [%0], %1;" ::"l"(ctr), "r"(vt[last] - vt[counted]) : "memory");
                }
            }
        } else if (j == 1) {
            if (sbase & 1023) __trap();
            if (lead) {
                asm volatile("st.shared.u32 [%0], %1;" ::"r"(bars + kStarted), "r"(0) : "memory");
                asm volatile("st.shared.u32 [%0], %1;" ::"r"(bars + kAllowed), "r"(rank == 0 || sched.gate1 ? sched.pace_from : kTiles) : "memory");
                if (kSlots > 24) {
                    mbar_init(bars + kBarFull + 8 * 24, 1);
                    mbar_init(bars + kBarEmpty + 8 * 24, 6);
                }
                for (int i = 0; i < 9; i++) mbar_init(bars + kBarPiece + 8 * i, i == 0 ? 12 : i < 6 ? 1 : 4);
                asm volatile("fence.acq_rel.cta;" ::: "memory");
                asm volatile("fence.mbarrier_init.release.cluster;" ::: "memory");
            }
            __syncwarp();
            CLUSTER_ARRIVE();
            CLUSTER_WAIT();
            if (lead) {
                uint32_t k = 0;
#pragma unroll 1
                for (int t = 0; t < kTiles; t++) {
                    const uint32_t pos = tiles[t].pos;
                    if (!(pos & 0x8000)) continue;
                    const int row = fine_group(pos, ci);
#pragma unroll
                    for (int g = 0; g < 3; g++) {
                        mbar_wait1(bars + kBarStaged + 8 * g, k & 1);
                        if (g == 2) CURVE_REC(1, t);
                        asm volatile("fence.proxy.async.shared::cta;" ::: "memory");
                        tma_store_4d(&tm_out, sbase + kOffOut + g * kChunk, rank * 192 + g * 64, row);
                        asm volatile("cp.async.bulk.commit_group;" ::: "memory");
                        if (g > 0) {
                            asm volatile("cp.async.bulk.wait_group.read 1;" ::: "memory");
                            mbar_arrive(bars + kBarFree + 8 * g - 8);
                        }
                    }
                    asm volatile("cp.async.bulk.wait_group.read 0;" ::: "memory");
                    mbar_arrive(bars + kBarFree + 16);
                    CURVE_REC(3, t);
                    k++;
                }
            }
        } else {
            CLUSTER_ARRIVE();
            CLUSTER_WAIT();
            if (lead) {
                uint32_t dst0 = sbase + rank * 4096, bar0 = bars;
                asm volatile("" : "+r"(dst0), "+r"(bar0));
                uint32_t wk = 0, wi = 0;
                int allowed = 0;
#pragma unroll 1
                for (int t = 0; t < kTiles; t++) {
                    const uint4 e = *(const uint4*)&tiles[t];
                    const bool f = e.w & 0x8000;
                    const CUtensorMap* tm = f ? &tm_fine : &tm_coarse;
                    const int c3 = f ? 0 : ci * (kSeg / 8), c4 = f ? fine_group(e.w, ci) + kRankF * rank : (e.w & 0xFFF) + kRankC * rank;
                    for (uint32_t n = 0; t >= allowed; n++) {
                        asm volatile("ld.volatile.shared.u32 %0, [%1];" : "=r"(allowed) : "r"(bar0 + kAllowed) : "memory");
                        if (n == 0x4000000) __trap();
                        if (n) __nanosleep(20);
                    }
                    if (t) CURVE_REC(0, t);
#pragma unroll
                    for (int c = 0; c < 6; c++) {
                        if (c == 0 || (PF_SPLIT && c == 3)) asm volatile("st.volatile.shared.u32 [%0], %1;" ::"r"(bar0 + kStarted), "r"(2 * t + 1 + c / 3) : "memory");
                        const uint32_t x = c < 4 ? e.x >> (8 * c) : e.y >> (8 * (c - 4)), s8 = x & 0xF8;
                        mbar_wait1(bar0 + kBarEmpty + s8, (x >> 1) & 1);
                        mbar_expect_tx(bar0 + kBarFull + s8, kChunk);
                        tma_load_5d_mc(dst0 + s8 * 1024, tm, c * 64, c3, c4, bar0 + kBarFull + s8);
#pragma unroll 1
                        for (uint32_t n = (e.w >> (16 + 2 * c)) & 3; n; n--) {
                            if (wk == 0) mbar_wait(bar0 + kBarReady2, 0);
                            const uint32_t o = sched.worder[wk], y = (&sched.wslot[pat][wi][0][0])[o];
                            mbar_wait1(bar0 + kBarEmpty + (y & 0xF8), (y >> 1) & 1);
                            mbar_expect_tx(bar0 + kBarSwap + 8 * o, kChunk);
                            bulk_load(sbase + (y & 0xF8) * 1024, (const char*)&g_wfrag[0][rank][0][0][0] + (o - (o >> 3) * 2) * kChunk, bar0 + kBarSwap + 8 * o);
                            if (++wk == 3 * NSTG) wk = 0, wi++;
                        }
                    }
                }
            }
        }
        __syncwarp();
    } else {
        if (elect_one()) {
            for (int i = 2 * warp_id; i < 2 * warp_id + 2; i++) {
                mbar_init(bars + kBarSwap + 8 * i, 1);
                if (i >= kSlots) continue;
                mbar_init(bars + kBarFull + 8 * i, 1);
                mbar_init(bars + kBarEmpty + 8 * i, 6);
            }
            asm volatile("fence.mbarrier_init.release.cluster;" ::: "memory");
        }
        __syncwarp();
        CLUSTER_ARRIVE();
        asm volatile("setmaxnreg.inc.sync.aligned.u32 160;");
        const int tid = threadIdx.x & 127;
        const int warp = tid >> 5;
        const bool rel = tid < 2;
        uint32_t rel_bar;
        asm("mapa.shared::cluster.u32 %0, %1, %2;" : "=r"(rel_bar) : "r"(bars + kBarEmpty), "r"(tid & 1));
        const uint32_t b_lo0 = ((sbase & 0x3FFFF) >> 4) | 0x10000u;
        const uint32_t frag_off = ((lane >> 4) * 8 + (lane & 7)) * 128 + (((2 * warp + ((lane >> 3) & 1)) ^ (lane & 7)) << 4);
        uint32_t st_addr = sbase + kOffOut + wg * kChunk + frag_off, tid16 = tid * 16;
        asm volatile("" : "+r"(st_addr), "+r"(tid16));
        uint4* const wf = &g_wfrag[0][rank][wg][0][tid];
        constexpr int kSet = 2 * 3 * 24 * 128;

        float acc[32];
        uint32_t w[96], p[16];

        CLUSTER_WAIT();
        mbar_wait(bars + kBarW + 8 * wg, 0);
        const uint32_t w_addr = sbase + (kSlotW + 6 * wg) * kChunk + frag_off;
#pragma unroll
        for (int s = 0; s < 24; s++)
            asm volatile("ldmatrix.sync.aligned.m8n8.x4.trans.shared.b16 {%0,%1,%2,%3}, [%4];"
                         : "=r"(w[4 * s]), "=r"(w[4 * s + 1]), "=r"(w[4 * s + 2]), "=r"(w[4 * s + 3]) : "r"(w_addr + s * 2048) : "memory");
        if (cid < kPieces) {
            asm volatile("ldmatrix.sync.aligned.m8n8.x4.trans.shared.b16 {%0,%1,%2,%3}, [%4];"
                         : "=r"(p[0]), "=r"(p[1]), "=r"(p[2]), "=r"(p[3]) : "r"(w_addr + cid * 2048) : "memory");
            wf[cid * 128] = make_uint4(p[0], p[1], p[2], p[3]);
        }
        asm volatile("bar.sync %0, 128;" ::"r"(4 + wg) : "memory");
        if (tid < 12 && kSlotW + 6 * wg + (tid >> 1) < kSlots) mbar_arrive_cluster<3>(rel_bar + 8 * (kSlotW + 6 * wg + (tid >> 1)));
        if (threadIdx.x == 0) CURVE_REC(2, 59);
        if (cid < kPieces) {
            mbar_wait(bars + kBarL, 0);
            WG_FENCE();
            piece_steps<0>(acc, w, b_lo0 + kSlotL * 512);
            WG_COMMIT();
            WG_WAIT(0);
            wf[kSet + cid * 128] = make_uint4(pack_bf16(acc[0], acc[1]), pack_bf16(acc[2], acc[3]), pack_bf16(acc[4], acc[5]), pack_bf16(acc[6], acc[7]));
            __syncwarp();
            if (lane == 0) mbar_arrive(bars + kBarPiece);
        }
        if (tid < 4) mbar_arrive_cluster<1>(rel_bar + 8 * (kSlotL + (tid >> 1)));
        if (threadIdx.x == 256) CURVE_REC(2, 60);
#pragma unroll
        for (int i = 0; i < 16; i++) p[i] = 0;

        const int tok_in = 1 + wg, tok_out = wg == 2 ? 1 : wg + 2;
        if (TOKEN_K && wg == 2) asm volatile("bar.arrive 1, 256;" ::: "memory");
        uint32_t nstore = 1;
        bool rdy = false;
#pragma unroll 1
        for (int t = 0; t < kTiles; t++) {
            const uint2 e = *(const uint2*)&tiles[t];
            const uint32_t fl = e.y >> 24, pe = tiles[t].p[wg];
            const uint32_t p_addr = sbase + (pe & 0xF8) * 1024 + tid16;
            if ((~fl & (F_FINE | F_P)) == 0) {
#pragma unroll
                for (int q = 0; q < 4; q++)
                    asm volatile("ld.shared.v4.u32 {%0,%1,%2,%3}, [%4];" : "=r"(p[4 * q]), "=r"(p[4 * q + 1]), "=r"(p[4 * q + 2]), "=r"(p[4 * q + 3])
                                 : "r"(p_addr + q * 2048) : "memory");
            }
            if (!SHAPE && (fl & F_SHIFT)) {
#pragma unroll
                for (int i = 0; i < 8; i++) p[i] = p[8 + i];
            }
#pragma unroll
            for (int i = 0; i < 8; i++)
                asm volatile("shl.b32 %0, %4, 16;\nshl.b32 %1, %4, 16;\nand.b32 %2, %4, 0xffff0000;\nand.b32 %3, %4, 0xffff0000;"
                             : "=f"(acc[4 * i]), "=f"(acc[4 * i + 1]), "=f"(acc[4 * i + 2]), "=f"(acc[4 * i + 3]) : "r"(p[SHAPE ? i & 3 : i]));
            if (SHAPE) {
#pragma unroll
                for (int i = 0; i < 12; i++) p[i] = p[4 + i];
            }
            if (fl & F_READY) mbar_wait(bars + kBarReady, 0);
            const char* swap = (const char*)&g_wfrag[~fl & F_FINE][rank][wg][0][0];
            if (TOKEN_K) asm volatile("bar.sync %0, 256;" ::"r"(tok_in) : "memory");
            auto body = [&](auto mode) {
                constexpr int M = decltype(mode)::value;
                rdy = issue_chunk<0>(acc, w, e, bars, b_lo0, rdy);
                rdy = issue_chunk<1>(acc, w, e, bars, b_lo0, rdy);
                if (TOKEN_K == 2) asm volatile("bar.arrive %0, 256;" ::"r"(tok_out) : "memory");
                retire_chunk<0, 1, M>(w, e, sched.wslot[pat], wg, sbase, rel_bar, rel, swap, tid16);
                if (M == 0 && rel && (~fl & (F_FINE | F_P)) == 0) mbar_arrive_cluster<3>(rel_bar + (pe & 0xF8));
                rdy = issue_chunk<2>(acc, w, e, bars, b_lo0, rdy);
                if (TOKEN_K == 3) asm volatile("bar.arrive %0, 256;" ::"r"(tok_out) : "memory");
                retire_chunk<1, 1, M>(w, e, sched.wslot[pat], wg, sbase, rel_bar, rel, swap, tid16);
                rdy = issue_chunk<3>(acc, w, e, bars, b_lo0, rdy);
                retire_chunk<2, 1, M>(w, e, sched.wslot[pat], wg, sbase, rel_bar, rel, swap, tid16);
                rdy = issue_chunk<4>(acc, w, e, bars, b_lo0, rdy);
                retire_chunk<3, 1, M>(w, e, sched.wslot[pat], wg, sbase, rel_bar, rel, swap, tid16);
                rdy = issue_chunk<5>(acc, w, e, bars, b_lo0, rdy);
                retire_chunk<4, 1, M>(w, e, sched.wslot[pat], wg, sbase, rel_bar, rel, swap, tid16);
                if (fl & F_FINE) mbar_wait(bars + kBarFree + 8 * wg, nstore & 1);
                else if (M == 0) mbar_wait(bars + kBarEmpty + (pe & 0xF8), (pe >> 1) & 1);
                retire_chunk<5, 0, M>(w, e, sched.wslot[pat], wg, sbase, rel_bar, rel, swap, tid16);
            };
            if (!(fl & F_SWAP)) body(std::integral_constant<int, 0>());
            else if (fl & F_STAGED) body(std::integral_constant<int, 2>());
            else body(std::integral_constant<int, 1>());
            if (fl & F_FINE) {
                nstore++;
#pragma unroll
                for (int q = 0; q < 4; q++)
                    asm volatile("stmatrix.sync.aligned.m8n8.x4.trans.shared.b16 [%0], {%1,%2,%3,%4};" ::"r"(st_addr + q * 2048),
                                 "r"(pack_bf16(acc[8 * q], acc[8 * q + 1])), "r"(pack_bf16(acc[8 * q + 2], acc[8 * q + 3])),
                                 "r"(pack_bf16(acc[8 * q + 4], acc[8 * q + 5])), "r"(pack_bf16(acc[8 * q + 6], acc[8 * q + 7])) : "memory");
                __syncwarp();
                if (elect_one()) mbar_arrive(bars + kBarStaged + 8 * wg);
            } else {
#pragma unroll
                for (int q = 0; q < 4; q++) {
                    p[4 * q] = pack_bf16(acc[8 * q], acc[8 * q + 2]);
                    p[4 * q + 1] = pack_bf16(acc[8 * q + 1], acc[8 * q + 3]);
                    p[4 * q + 2] = pack_bf16(acc[8 * q + 4], acc[8 * q + 6]);
                    p[4 * q + 3] = pack_bf16(acc[8 * q + 5], acc[8 * q + 7]);
                    if (fl & F_P)
                        asm volatile("st.shared.v4.u32 [%0], {%1,%2,%3,%4};" ::"r"(p_addr + q * 2048),
                                     "r"(p[4 * q]), "r"(p[4 * q + 1]), "r"(p[4 * q + 2]), "r"(p[4 * q + 3]) : "memory");
                }
            }
        }
        if (TOKEN_K && wg == 0) asm volatile("bar.sync 1, 256;" ::: "memory");
    }
    CLUSTER_ARRIVE();
    CLUSTER_WAIT();
    if (threadIdx.x == 0) CURVE_REC(0, 63);
}

void build_schedule(int pat, Tile* tl, uint16_t (*pf)[2], uint8_t (*wslot)[3][8], uint8_t* worder, const int* gs, const char* leads, int pf_next) {
    const int take[3] = {TAKE}, give[3] = {GIVE};
    const int staged = envi("STAGED", 1), wadv = envi("WADV", 4), wrel = envi("WREL", 0);
    int coarse_of[16];
    int n = 0, nsw = 0, swt[2] = {};
    int units[kTiles];
    auto unit = [&](int t) { return units[t]; };
    for (int g = 0, i0 = 0; gs[g]; i0 += gs[g], g++) {
        for (int i = 1; i <= gs[g]; i++, n++) {
            units[n] = i0 + i % gs[g];
            tl[n].pos = (units[n] * NPAT + pat) * (SHAPE ? 4 : 2);
            tl[n].flags = i < gs[g] ? F_P : F_SWAP | F_SWAPH | (g == 0 ? F_READY : 0);
            coarse_of[unit(n)] = n;
            if (i == gs[g] && g > 0) tl[n + envi("PW1", PW1) + (tl[n + envi("PW1", PW1)].pw != 0)].pw = 2;
        }
        for (int i = 0; i < 4 * gs[g]; i++, n++) {
            units[n] = i0 + i / 4;
            tl[n].pos = 0x8000 + (SHAPE ? ((units[n] * NPAT + pat) * 4 + (i & 3)) * kGroup : ((units[n] * NPAT + pat) * 2 + (i & 3) / 2) * kGroup + (i & 1) * 0x1000);
            tl[n].flags = F_FINE | (i >= 4 && (i & 3) == 0 ? F_P : 0) | ((i & 3) == 2 ? F_SHIFT : 0);
            if (i == 4 * gs[g] - 1 && gs[g + 1]) {
                tl[n].flags |= staged ? F_SWAP | F_STAGED | (nsw ? F_SW1 : 0) : F_SWAP | F_SWAPH;
                if (staged) swt[nsw++] = n;
                if (envi("PW0", PW0) < 9) tl[n + envi("PW0", PW0)].pw = 1;
            }
        }
    }
    for (int t = 0, next = pf_next; t < kTiles; t++) {
        const int lead = leads[t] - '0';
        if (next <= t) next = t + 1;
        for (int i = 0; i < 2; i++)
            pf[t][i] = next <= t + lead && next < kTiles ? tl[next++].pos : 0xFFFF;
    }
    int nwo = 0;
    for (int need = -4; need < 6; need++)
        for (int g = 0; g < 3; g++) {
            const int c = need - give[g];
            if (c < 6 - NSTG || c > 5) continue;
            worder[nwo++] = g * 8 + c;
            for (int i = 0; i < nsw; i++) {
                const int j = 6 * swt[i] + need + 4 - wadv;
                tl[j / 6].wcnt += 1 << (2 * (j % 6));
            }
        }
    int uses[kSlots], loads[kSlots], queue[512], head = 0, tail = 0, slot_of[6 * kTiles];
    for (int s = 0; s < kSlots; s++) uses[s] = s >= kSlotL, loads[s] = 0;
    auto take_p = [&](int t, int w, int s) { tl[t].p[w] = s * 8 + ((uses[s] + 1) & 1) * 2; uses[s]++; };
    bool taken[kSlots] = {};
    for (int w = 0; w < 3; w++)
        if (take[w] < 0 && (tl[0].flags & F_P)) take_p(0, w, kSlotW + 6 * w + 2), taken[kSlotW + 6 * w + 2] = true;
    for (int s = 0; s < kSlotL; s++) queue[tail++] = s;
    for (int s = kSlotW; s < kSlots; s++) if (!taken[s]) queue[tail++] = s;
    for (int s = kSlotL; s < kSlotW; s++) queue[tail++] = s;
    int r = 0, wk = 0, wi = 0;
    auto get_slot = [&]() {
        for (; head == tail; r++) {
            bool to_p = false;
            for (int w = 0; w < 3; w++) {
                int x = r - take[w];
                if (x >= 0 && x % 6 == 0 && x / 6 < kTiles && (tl[x / 6].flags & (F_FINE | F_P)) == F_P) take_p(x / 6, w, slot_of[r]), to_p = true;
            }
            if (!to_p) queue[tail++] = slot_of[r];
            for (int w = 0; w < 3; w++) {
                int x = r - give[w];
                if (x >= 0 && x % 6 == 0 && x / 6 < kTiles && (tl[x / 6].flags & (F_FINE | F_P)) == (F_FINE | F_P)) {
                    tl[x / 6].p[w] = tl[coarse_of[unit(x / 6)]].p[w];
                    queue[tail++] = tl[x / 6].p[w] >> 3;
                }
                x -= wrel;
                if (x >= 0 && x / 6 < kTiles && (tl[x / 6].flags & F_STAGED) && x % 6 >= 6 - NSTG) queue[tail++] = wslot[tl[x / 6].flags >> 7][w][x % 6] >> 3;
            }
        }
        return queue[head++];
    };
    for (int c = 0; c < 6 * kTiles; c++) {
        int s = get_slot();
        slot_of[c] = s;
        tl[c / 6].chunk[c % 6] = s * 8 + ((uses[s] + 1) & 1) * 2 + (loads[s] & 1);
        if (c % 6 == 0 && c) tl[c / 6 - 1].chunk[6] = tl[c / 6].chunk[0];
        uses[s]++, loads[s]++;
        for (int k = (tl[c / 6].wcnt >> (2 * (c % 6))) & 3; k; k--) {
            s = get_slot();
            (&wslot[wi][0][0])[worder[wk]] = s * 8 + ((uses[s] + 1) & 1) * 2;
            uses[s]++;
            if (++wk == 3 * NSTG) wk = 0, wi++;
        }
    }
    for (int t = 0; t < kTiles; t++)
        if ((tl[t].flags & (F_FINE | F_P)) == (F_FINE | F_P)) memcpy(tl[t].p, tl[coarse_of[unit(t)]].p, 3);
}

typedef CUresult (*EncodeFn)(CUtensorMap*, CUtensorMapDataType, cuuint32_t, void*, const cuuint64_t*, const cuuint64_t*,
                             const cuuint32_t*, const cuuint32_t*, CUtensorMapInterleave, CUtensorMapSwizzle,
                             CUtensorMapL2promotion, CUtensorMapFloatOOBfill);

void encode_2d(EncodeFn enc, CUtensorMap* tm, const void* ptr, uint64_t rows, uint32_t box_rows, CUtensorMapL2promotion promo) {
    cuuint64_t dims[2] = {(cuuint64_t)kC, rows};
    cuuint64_t strides[1] = {(cuuint64_t)kC * 2};
    cuuint32_t box[2] = {64, box_rows};
    cuuint32_t es[2] = {1, 1};
    enc(tm, CU_TENSOR_MAP_DATA_TYPE_BFLOAT16, 2, const_cast<void*>(ptr), dims, strides, box, es, CU_TENSOR_MAP_INTERLEAVE_NONE,
        CU_TENSOR_MAP_SWIZZLE_128B, promo, CU_TENSOR_MAP_FLOAT_OOB_FILL_NONE);
}

}

extern "C" void kernel_launch(void* const* d_in, const int* in_sizes, int n_in, void* d_out, int out_size) {
    (void)in_sizes; (void)n_in; (void)out_size;
    static EncodeFn enc = nullptr;
    static Schedule sched;
    if (!enc) {
        void* fn = nullptr;
        cudaDriverEntryPointQueryResult qr;
        cudaGetDriverEntryPoint("cuTensorMapEncodeTiled", &fn, cudaEnableDefault, &qr);
        enc = (EncodeFn)fn;
        cudaFuncSetAttribute(fpn_lateral_kernel, cudaFuncAttributeMaxDynamicSharedMemorySize, kSmemBytes);
        if (envi("CARVE", 0)) cudaFuncSetAttribute(fpn_lateral_kernel, cudaFuncAttributePreferredSharedMemoryCarveout, envi("CARVE", 0));
        cudaLaunchConfig_t cfg = {};
        cfg.gridDim = dim3(2);
        cfg.blockDim = dim3(512);
        cfg.dynamicSmemBytes = kSmemBytes;
        cudaLaunchAttribute at;
        at.id = cudaLaunchAttributeClusterDimension;
        at.val.clusterDim.x = 2; at.val.clusterDim.y = 1; at.val.clusterDim.z = 1;
        cfg.attrs = &at; cfg.numAttrs = 1;
        int ncl = 0;
        if (cudaOccupancyMaxActiveClusters(&ncl, fpn_lateral_kernel, &cfg) != cudaSuccess) { (void)cudaGetLastError(); ncl = 0; }
        sched.pf_k = envi("PFK", 3), sched.pf_first = envi("PFFIRST", 4);
        const char* pn[4] = {"PATA", "PATB", "PATC", "PATD"};
        const char* ln[4] = {"LEADA", "LEADB", "LEADC", "LEADD"};
        const char* pd[4] = {"45", "45", "36", "63"};
        sched.pgroup = envi("PGROUP", 0), sched.members = sched.pgroup ? kGroup : kClusters;
        for (int q = 0; q < NPAT; q++) {
            int gs[8] = {};
            const char* sa = envs(pn[q], pd[q]);
            for (int i = 0; sa[i]; i++) gs[i] = sa[i] - '0';
            build_schedule(q, sched.tile[q], sched.pf[q], sched.wslot[q], sched.worder, gs, envs(ln[q], envs("LEAD", "111144444443322111111111111111111111111111111")), sched.pf_k + 1);
        }
        sched.hold = envi("HOLD", 0), sched.gate1 = envi("GATE1", 1), sched.psleep = envi("PSLEEP", 100);
        sched.pace_from = envi("PACE_FROM", 14), sched.pace_to = envi("PACE_TO", 45);
        const char* v5 = "555555555555555555555555555555555555555555555";
        const char* vts[4] = {envs("VTA", v5), envs("VTB", v5), envs("VTC", v5), envs("VTD", v5)};
        int total = 0;
        for (int q = 0; q < NPAT; q++) {
            int sum[kTiles + 1] = {};
            for (int t = sched.pace_from; t < sched.pace_to; t++) sum[t] = sum[t - 1] + vts[q][t] - '0';
            total = sum[sched.pace_to - 1];
            for (int t = sched.pace_from; t < sched.pace_to; t++) {
                sched.vt[q][t] = sum[t] * 1024 / total;
                int slack = envi("PSTART", 160) - envi("PRAMP", 6) * (t - sched.pace_from);
                if (slack < envi("PACE", 40)) slack = envi("PACE", 40);
                if (envs("SLK", nullptr)) slack = (envs("SLK", nullptr)[t] - '0') * 16;
                sched.need[q][t] = ncl >= kClusters ? sched.vt[q][t] * sched.members - slack * 5 * 1024 / total * sched.members / 64 : -1;
            }
        }
    }
    CUtensorMap tm_fine, tm_coarse, tm_wlat, tm_wout, tm_out;
    const cuuint32_t ones[5] = {1, 1, 1, 1, 1};
    {
        cuuint64_t dims[5] = {(cuuint64_t)kC, 2, 4, 4, (cuuint64_t)kFinePix / 32};
        cuuint64_t strides[4] = {768, 2 * 768, 8 * 768, 32 * 768};
        cuuint32_t box[5] = {64, 2, 4, 4, 1};
        enc(&tm_fine, CU_TENSOR_MAP_DATA_TYPE_BFLOAT16, 5, d_in[0], dims, strides, box, ones, CU_TENSOR_MAP_INTERLEAVE_NONE,
            CU_TENSOR_MAP_SWIZZLE_128B, CU_TENSOR_MAP_L2_PROMOTION_L2_128B, CU_TENSOR_MAP_FLOAT_OOB_FILL_NONE);
    }
    {
        cuuint64_t dims[3] = {64, (cuuint64_t)kC, 6};
        cuuint64_t strides[2] = {768, 128};
        cuuint32_t box[3] = {64, 16, 6};
        cuuint32_t es[3] = {1, 1, 1};
        enc(&tm_wlat, CU_TENSOR_MAP_DATA_TYPE_BFLOAT16, 3, d_in[2], dims, strides, box, es, CU_TENSOR_MAP_INTERLEAVE_NONE,
            CU_TENSOR_MAP_SWIZZLE_128B, CU_TENSOR_MAP_L2_PROMOTION_L2_256B, CU_TENSOR_MAP_FLOAT_OOB_FILL_NONE);
    }
    encode_2d(enc, &tm_wout, d_in[3], kC, 192, CU_TENSOR_MAP_L2_PROMOTION_L2_256B);
    {
        cuuint64_t dims[4] = {(cuuint64_t)kC, 32, 2, (cuuint64_t)kFinePix / 32 - kRankF};
        cuuint64_t strides[3] = {768, kRankF * 32 * 768, 32 * 768};
        cuuint32_t box[4] = {64, 32, 2, 1};
        enc(&tm_out, CU_TENSOR_MAP_DATA_TYPE_BFLOAT16, 4, d_out, dims, strides, box, ones, CU_TENSOR_MAP_INTERLEAVE_NONE,
            CU_TENSOR_MAP_SWIZZLE_128B, CU_TENSOR_MAP_L2_PROMOTION_NONE, CU_TENSOR_MAP_FLOAT_OOB_FILL_NONE);
    }
    {
        cuuint64_t dims[5] = {(cuuint64_t)kC, 2, 4, kGroup * kSeg / 8, (cuuint64_t)kCoarsePix / (kGroup * kSeg)};
        cuuint64_t strides[4] = {4 * 768, 768, 8 * 768, kGroup * kSeg * 768};
        cuuint32_t box[5] = {64, 2, 4, kSeg / 8, 32 / kSeg};
        enc(&tm_coarse, CU_TENSOR_MAP_DATA_TYPE_BFLOAT16, 5, d_in[1], dims, strides, box, ones, CU_TENSOR_MAP_INTERLEAVE_NONE,
            CU_TENSOR_MAP_SWIZZLE_128B, CU_TENSOR_MAP_L2_PROMOTION_L2_128B, CU_TENSOR_MAP_FLOAT_OOB_FILL_NONE);
    }
    fpn_lateral_kernel<<<2 * kClusters, 512, kSmemBytes>>>(tm_fine, tm_coarse, tm_wlat, tm_wout, tm_out, sched, (const char*)d_in[0], (const char*)d_in[1],
                                                          (const char*)d_in[2], (const char*)d_in[3]);
}
```

```cpp
#include <cuda_runtime.h>
#include <cuda_bf16.h>
#include <cuda.h>
#include <stdint.h>
#include <string.h>
#include <type_traits>
#include <stdlib.h>

#define TOKEN_K 3
#define TAKE -2, 0, 2
#define GIVE -4, -2, 0
#define L_POS 0
#define NSTG 6
#define EV 3
#define STPOL 0
#define NO_MMA 0
#define NPAT 1
#define SHAPE 1
#define OBUF 1
#define LD_EF 0
#define CURVE_REC(k, i) do {} while (0)

namespace {

constexpr int kC = 384;
constexpr int kFinePix = 384 * 384;
constexpr int kCoarsePix = 192 * 192;
constexpr int kClusters = 64;
constexpr int kTiles = 45;
#define SLOTS (28 - 3 * OBUF)
constexpr int kSlots = SLOTS;
constexpr int kChunk = 8192;
constexpr int kTileBytes = 6 * kChunk;
constexpr int kOffOut = kSlots * kChunk;
constexpr int kOffBar = kOffOut + 3 * OBUF * kChunk;
constexpr int kSmemBytes = kOffBar + 1024;
constexpr int kSlotL = kSlots + 3 * OBUF - 20;
constexpr int kSlotW = kSlots + 3 * OBUF - 18;
constexpr int kBarFull = 0, kBarEmpty = 8 * kSlots, kBarW = 16 * kSlots, kBarL = kBarW + 24;
constexpr int kBarPiece = kBarL + 8, kBarReady = kBarPiece + 8, kBarGo = kBarReady + 8, kBarFree = kBarGo + 8, kBarStaged = kBarFree + 24 * OBUF;
constexpr int kBarSwap = kBarStaged + 24 * OBUF;
constexpr int kBarReady2 = kBarSwap + 56;
constexpr int kStarted = kBarSwap + 192, kAllowed = kStarted + 4;
constexpr int kPieces = 24;

enum : uint32_t { F_FINE = 1, F_P = 2, F_SHIFT = 4, F_SWAP = 8, F_READY = 16, F_SWAPH = 32, F_STAGED = 64, F_SW1 = 128 };
struct alignas(16) Tile {
    uint8_t chunk[7];
    uint8_t flags;
    uint8_t p[3];
    uint8_t pw;
    uint16_t pos;
    uint16_t wcnt;
};
constexpr int kGroup = kClusters / NPAT;
struct Schedule {
    Tile tile[NPAT][kTiles + 1];
    uint16_t tgt[EV * kTiles + 2];
    alignas(8) uint8_t wslot[NPAT][2][3][8];
    uint8_t worder[24];
    uint8_t sef[48];
    int members, pgroup;
    int pace_from, pace_to, gate1, psleep, pf_from, pw_ev[2], pw_div, t_a, t_d, t_max, fsleep;
    int need[NPAT][kTiles + 1];
    uint16_t vt[NPAT][kTiles + 1];
};
static int envi(const char*, int d) { return d; }
static const char* envs(const char*, const char* d) { return d; }

__device__ uint4 g_wfrag[2][2][3][24][128];
__device__ uint32_t g_ready;
__device__ uint32_t g_done;
__device__ uint32_t g_progress[4][32];

__device__ __forceinline__ uint32_t smem_u32(const void* p) { return (uint32_t)__cvta_generic_to_shared(p); }

__device__ __forceinline__ void mbar_init(uint32_t bar, uint32_t count) {
    asm volatile("mbarrier.init.shared::cta.b64 [%0], %1;" ::"r"(bar), "r"(count) : "memory");
}
__device__ __forceinline__ void mbar_expect_tx(uint32_t bar, uint32_t bytes) {
    asm volatile("mbarrier.arrive.expect_tx.shared::cta.b64 _, [%0], %1;" ::"r"(bar), "r"(bytes) : "memory");
}
__device__ __forceinline__ void mbar_wait(uint32_t bar, uint32_t parity) {
    asm volatile(
        "{\n"
        ".reg .pred p;\n"
        ".reg .u32 n;\n"
        "mov.u32 n, 0;\n"
        "WAIT_LOOP:\n"
        "mbarrier.try_wait.parity.shared::cta.b64 p, [%0], %1;\n"
        "@p bra WAIT_DONE;\n"
        "add.u32 n, n, 1;\n"
        "setp.lt.u32 p, n, 0x400000;\n"
        "@p bra WAIT_LOOP;\n"
        "trap;\n"
        "WAIT_DONE:\n"
        "}\n" ::"r"(bar), "r"(parity) : "memory");
}
__device__ __forceinline__ void mbar_wait1(uint32_t bar, uint32_t parity) {
    uint32_t r;
    asm volatile("{\n.reg .pred p;\nmbarrier.try_wait.parity.shared::cta.b64 p, [%1], %2;\nselp.u32 %0, 1, 0, p;\n}\n" : "=r"(r) : "r"(bar), "r"(parity) : "memory");
    if (!r) mbar_wait(bar, parity);
}
__device__ __forceinline__ bool mbar_test(uint32_t bar, uint32_t parity) {
    uint32_t r;
    asm volatile("{\n.reg .pred p;\nmbarrier.test_wait.parity.shared::cta.b64 p, [%1], %2;\nselp.u32 %0, 1, 0, p;\n}\n" : "=r"(r) : "r"(bar), "r"(parity) : "memory");
    return r != 0;
}
__device__ __forceinline__ void mbar_arrive(uint32_t bar) {
    asm volatile("mbarrier.arrive.shared::cta.b64 _, [%0];" ::"r"(bar) : "memory");
}
template <int N>
__device__ __forceinline__ void mbar_arrive_cluster(uint32_t bar) {
    if (N == 1) asm volatile("mbarrier.arrive.shared::cluster.b64 _, [%0];" ::"r"(bar) : "memory");
    else asm volatile("mbarrier.arrive.shared::cluster.b64 _, [%0], %1;" ::"r"(bar), "n"(N) : "memory");
}
__device__ __forceinline__ void bulk_load(uint32_t dst, const void* src, uint32_t bar) {
    asm volatile("cp.async.bulk.shared::cluster.global.mbarrier::complete_tx::bytes [%0], [%1], %2, [%3];"
                 ::"r"(dst), "l"(src), "n"(kChunk), "r"(bar) : "memory");
}
__device__ __forceinline__ void tma_load_2d(uint32_t dst, const CUtensorMap* tm, int c0, int c1, uint32_t bar) {
    asm volatile("cp.async.bulk.tensor.2d.shared::cluster.global.mbarrier::complete_tx::bytes [%0], [%1, {%2, %3}], [%4];"
                 ::"r"(dst), "l"(tm), "r"(c0), "r"(c1), "r"(bar) : "memory");
}
__device__ __forceinline__ void tma_load_3d(uint32_t dst, const CUtensorMap* tm, int c1, uint32_t bar) {
    asm volatile("cp.async.bulk.tensor.3d.shared::cluster.global.mbarrier::complete_tx::bytes [%0], [%1, {%2, %3, %2}], [%4];"
                 ::"r"(dst), "l"(tm), "r"(0), "r"(c1), "r"(bar) : "memory");
}
__device__ __forceinline__ void tma_load_5d_mc(uint32_t dst, const CUtensorMap* tm, int c0, int c3, int c4, uint32_t bar, uint64_t pol) {
    asm volatile("cp.async.bulk.tensor.5d.shared::cluster.global.mbarrier::complete_tx::bytes.multicast::cluster [%0], [%1, {%2, %3, %3, %4, %5}], [%6], %7;"
                 ::"r"(dst), "l"(tm), "r"(c0), "r"(0), "r"(c3), "r"(c4), "r"(bar), "h"((uint16_t)3) : "memory");
}
__device__ __forceinline__ void tma_store_4d(const CUtensorMap* tm, uint32_t src, int c0, int c3, uint64_t pol) {
    if (STPOL) asm volatile("cp.async.bulk.tensor.4d.global.shared::cta.bulk_group.L2::cache_hint [%0, {%2, %3, %3, %4}], [%1], %5;"
                 ::"l"(tm), "r"(src), "r"(c0), "r"(0), "r"(c3), "l"(pol) : "memory");
    else asm volatile("cp.async.bulk.tensor.4d.global.shared::cta.bulk_group [%0, {%2, %3, %3, %4}], [%1];"
                 ::"l"(tm), "r"(src), "r"(c0), "r"(0), "r"(c3) : "memory");
}
__device__ __forceinline__ void prefetch_l2(const void* p) {
    asm volatile("prefetch.global.L2 [%0];" ::"l"(p) : "memory");
}
__device__ __forceinline__ void prefetch_tm(const CUtensorMap* tm) {
    asm volatile("prefetch.tensormap [%0];" ::"l"(tm) : "memory");
}
__device__ __forceinline__ uint32_t now_ns() {
    uint32_t t;
    asm volatile("mov.u32 %0, %globaltimer_lo;" : "=r"(t));
    return t;
}
__device__ __forceinline__ bool elect_one() {
    uint32_t p;
    asm volatile("{\n.reg .pred p;\nelect.sync _|p, 0xffffffff;\nselp.u32 %0, 1, 0, p;\n}\n" : "=r"(p));
    return p != 0;
}
#define CLUSTER_ARRIVE() asm volatile("barrier.cluster.arrive.relaxed.aligned;" ::: "memory")
#define CLUSTER_WAIT() asm volatile("barrier.cluster.wait.acquire.aligned;" ::: "memory")

#define WG_FENCE() asm volatile("wgmma.fence.sync.aligned;" ::: "memory")
#define WG_COMMIT() asm volatile("wgmma.commit_group.sync.aligned;" ::: "memory")
#define WG_WAIT(n) asm volatile("wgmma.wait_group.sync.aligned %0;" ::"n"(n) : "memory")

#define ACC32 "{%0,%1,%2,%3,%4,%5,%6,%7,%8,%9,%10,%11,%12,%13,%14,%15,%16,%17,%18,%19,%20,%21,%22,%23,%24,%25,%26,%27,%28,%29,%30,%31}"
#define ACC8(b) "+f"(d[b]), "+f"(d[b + 1]), "+f"(d[b + 2]), "+f"(d[b + 3]), "+f"(d[b + 4]), "+f"(d[b + 5]), "+f"(d[b + 6]), "+f"(d[b + 7])

#define DESC_HI "0x40000040"
template <int BOFF>
__device__ __forceinline__ void wgmma_rs(float (&d)[32], const uint32_t* a, uint32_t b_lo) {
    asm volatile("{\n.reg .b32 tb;\n.reg .b64 db;\nadd.u32 tb, %36, %37;\nmov.b64 db, {tb, " DESC_HI "};\n"
                 "wgmma.mma_async.sync.aligned.m64n64k16.f32.bf16.bf16 " ACC32 ", {%32,%33,%34,%35}, db, 1, 1, 1, 0;\n}\n"
                 : ACC8(0), ACC8(8), ACC8(16), ACC8(24)
                 : "r"(a[0]), "r"(a[1]), "r"(a[2]), "r"(a[3]), "r"(b_lo), "n"(BOFF));
}
__device__ __forceinline__ void wgmma_rs_first(float (&d)[32], const uint32_t* a, uint32_t b_lo, uint32_t accum) {
    asm volatile("{\n.reg .pred p;\n.reg .b64 db;\nsetp.ne.u32 p, %37, 0;\nmov.b64 db, {%36, " DESC_HI "};\n"
                 "wgmma.mma_async.sync.aligned.m64n64k16.f32.bf16.bf16 " ACC32 ", {%32,%33,%34,%35}, db, p, 1, 1, 0;\n}\n"
                 : ACC8(0), ACC8(8), ACC8(16), ACC8(24)
                 : "r"(a[0]), "r"(a[1]), "r"(a[2]), "r"(a[3]), "r"(b_lo), "r"(accum));
}
template <int ACCUM, int BOFF>
__device__ __forceinline__ void wgmma_rs16(float (&d)[32], const uint32_t* a, uint32_t b_lo) {
    asm volatile("{\n.reg .b32 tb;\n.reg .b64 db;\nadd.u32 tb, %12, %13;\nmov.b64 db, {tb, " DESC_HI "};\n"
                 "wgmma.mma_async.sync.aligned.m64n16k16.f32.bf16.bf16 {%0,%1,%2,%3,%4,%5,%6,%7}, {%8,%9,%10,%11}, db, %14, 1, 1, 0;\n}\n"
                 : ACC8(0)
                 : "r"(a[0]), "r"(a[1]), "r"(a[2]), "r"(a[3]), "r"(b_lo), "n"(BOFF), "n"(ACCUM));
}
template <int S>
__device__ __forceinline__ void piece_steps(float (&d)[32], const uint32_t (&w)[96], uint32_t b_lo) {
    if constexpr (S < 24) {
        wgmma_rs16<(S > 0), (S >> 2) * 128 + (S & 3) * 2>(d, &w[4 * S], b_lo);
        piece_steps<S + 1>(d, w, b_lo);
    }
}

__device__ __forceinline__ uint32_t pack_bf16(float lo, float hi) {
    uint32_t r;
    asm("cvt.rn.bf16x2.f32 %0, %1, %2;" : "=r"(r) : "f"(hi), "f"(lo));
    return r;
}

template <int C>
__device__ __forceinline__ void reload_w(uint32_t (&w)[96], const char* base, uint32_t tid16, uint32_t on) {
#define W4(i) "+r"(w[16 * C + 4 * i]), "+r"(w[16 * C + 4 * i + 1]), "+r"(w[16 * C + 4 * i + 2]), "+r"(w[16 * C + 4 * i + 3])
    asm volatile("{\n.reg .pred p;\n.reg .b64 a;\nsetp.ne.u32 p, %19, 0;\ncvt.u64.u32 a, %18;\nadd.u64 a, a, %16;\n"
                 "@p ld.global.cg.v4.u32 {%0,%1,%2,%3}, [a + %17];\n"
                 "@p ld.global.cg.v4.u32 {%4,%5,%6,%7}, [a + %17 + 2048];\n"
                 "@p ld.global.cg.v4.u32 {%8,%9,%10,%11}, [a + %17 + 4096];\n"
                 "@p ld.global.cg.v4.u32 {%12,%13,%14,%15}, [a + %17 + 6144];\n}\n"
                 : W4(0), W4(1), W4(2), W4(3)
                 : "l"(base), "n"(C * 8192), "r"(tid16), "r"(on) : "memory");
#undef W4
}

template <int C>
__device__ __forceinline__ uint32_t entry(uint2 e) { return C < 4 ? e.x >> (8 * C) : e.y >> (8 * (C - 4)); }

template <int C>
__device__ __forceinline__ bool issue_chunk(float (&acc)[32], const uint32_t (&w)[96], uint2 e, uint32_t bars, uint32_t b_lo0, bool ready) {
    if (!ready) mbar_wait(bars + kBarFull + (entry<C>(e) & 0xF8), entry<C>(e) & 1);
    const bool next = mbar_test(bars + kBarFull + (entry<C + 1>(e) & 0xF8), entry<C + 1>(e) & 1);
    const uint32_t b_lo = b_lo0 + (entry<C>(e) & 0xF8) * 64;
    if (!NO_MMA) {
        WG_FENCE();
        if (C == 0) wgmma_rs_first(acc, &w[0], b_lo, e.y & (F_FINE << 24));
        else wgmma_rs<0>(acc, &w[16 * C], b_lo);
        wgmma_rs<2>(acc, &w[16 * C + 4], b_lo);
        wgmma_rs<4>(acc, &w[16 * C + 8], b_lo);
        wgmma_rs<6>(acc, &w[16 * C + 12], b_lo);
        WG_COMMIT();
    }
    return next;
}
template <int C, int PENDING, int MODE>
__device__ __forceinline__ void retire_chunk(uint32_t (&w)[96], uint2 e, const uint8_t (*ws)[3][8], int wg, uint32_t sbase, uint32_t rel_bar, bool rel, const char* swap, uint32_t tid16) {
    if (!NO_MMA) WG_WAIT(PENDING);
    if (rel) mbar_arrive_cluster<1>(rel_bar + (entry<C>(e) & 0xF8));
    if (MODE == 1 || (MODE == 2 && C < 6 - NSTG)) reload_w<C>(w, swap, tid16, 1);
    if (MODE == 2 && C >= 6 - NSTG) {
        const uint32_t x = ws[e.y >> 31][wg][C];
        mbar_wait(sbase + kOffBar + kBarSwap + 64 * wg + 8 * C, e.y >> 31);
        const uint32_t a = sbase + (x & 0xF8) * 1024 + tid16;
#pragma unroll
        for (int q = 0; q < 4; q++)
            asm volatile("ld.shared.v4.u32 {%0,%1,%2,%3}, [%4];" : "=r"(w[16 * C + 4 * q]), "=r"(w[16 * C + 4 * q + 1]), "=r"(w[16 * C + 4 * q + 2]), "=r"(w[16 * C + 4 * q + 3])
                         : "r"(a + q * 2048) : "memory");
        asm volatile("bar.sync %0, 128;" ::"r"(4 + wg + ((w[16 * C] | w[16 * C + 4] | w[16 * C + 8] | w[16 * C + 12]) & x & 1)) : "memory");
        if (rel) mbar_arrive_cluster<3>(rel_bar + (x & 0xF8));
    }
}

__device__ __forceinline__ int fine_group(uint32_t pos, int ci) {
    const uint32_t q = (pos & 0xFFF) + ci;
    return SHAPE ? q + q / 12 * 12 : 2 * q + (q / 6 + ((pos >> 12) & 1)) * 12;
}
constexpr int kRankF = SHAPE ? 12 : 1, kRankC = SHAPE ? 2 : 1, kSeg = SHAPE ? 16 : 32;
template <int L0, int L1>
__device__ __forceinline__ void prefetch_tile(uint32_t pos, int ci, int rank, int lane, const char* fine, const char* coarse) {
    const bool f = pos & 0x8000;
    const uint32_t row = f ? (fine_group(pos, ci) + kRankF * rank) * 32 : (((pos & 0xFFF) + kRankC * rank) * kGroup + ci) * kSeg;
    const char* p = (f ? fine : coarse) + (size_t)row * 768 + lane * 128;
    const char* q = SHAPE && !f ? p + (kGroup - 1) * kSeg * 768 : p;
#pragma unroll
    for (int l = L0; l < L1; l++) prefetch_l2((l < 3 ? p : q) + l * 4096);
}

__global__ void __cluster_dims__(2, 1, 1) __launch_bounds__(512, 1)
fpn_lateral_kernel(const __grid_constant__ CUtensorMap tm_fine, const __grid_constant__ CUtensorMap tm_coarse,
                   const __grid_constant__ CUtensorMap tm_wlat, const __grid_constant__ CUtensorMap tm_wout,
                   const __grid_constant__ CUtensorMap tm_out, const __grid_constant__ Schedule sched,
                   const char* __restrict__ fine, const char* __restrict__ coarse,
                   const char* __restrict__ wlat, const char* __restrict__ wout) {
    extern __shared__ __align__(1024) unsigned char smem_raw[];
    if (threadIdx.x == 0) CURVE_REC(0, 0);
    const uint32_t sbase = smem_u32(smem_raw);
    const uint32_t bars = sbase + kOffBar;
    const int warp_id = __shfl_sync(0xffffffffu, (int)(threadIdx.x >> 5), 0);
    const int lane = threadIdx.x & 31;
    const int wg = warp_id >> 2;
    const int rank = blockIdx.x & 1;
    const int cid = blockIdx.x >> 1;
    const int pat = cid % NPAT, ci = cid / NPAT;
    const Tile* const tiles = sched.tile[pat];

    if (wg == 3) {
        asm volatile("setmaxnreg.dec.sync.aligned.u32 32;");
        const int j = warp_id & 3;
        const bool lead = elect_one();
        if (j == 3) {
            uint32_t c0;
            asm volatile("mov.u32 %0, %clock;" : "=r"(c0));
            if (lead) {
                for (int i = 0; i < 4; i++) mbar_init(bars + kBarW + 8 * i, 1);
                asm volatile("fence.mbarrier_init.release.cluster;" ::: "memory");
            }
            __syncwarp();
            if (lead) {
                asm volatile("fence.proxy.async.shared::cta;" ::: "memory");
#pragma unroll 1
                for (int g = 0; g < 3; g++) {
                    mbar_expect_tx(bars + kBarW + 8 * g, kTileBytes);
                    for (int c = 0; c < 2; c++) tma_load_2d(sbase + (kSlotW + 6 * g + 3 * c) * kChunk, &tm_wout, rank * 192 + g * 64, c * 192, bars + kBarW + 8 * g);
                    if (g == L_POS && cid < kPieces) {
                        mbar_expect_tx(bars + kBarL, 6 * 2048);
                        tma_load_3d(sbase + kSlotL * kChunk, &tm_wlat, cid * 16, bars + kBarL);
                    }
                }
            }
            __syncwarp();
            CLUSTER_ARRIVE();
            CLUSTER_WAIT();
            uint32_t cur = sched.pf_from, u = 0, pw = sched.pw_ev[0] == 1;
            const char* p = nullptr;
#pragma unroll 1
            for (uint32_t n = 0; cur < 6 * kTiles; n++) {
                uint32_t v;
                asm volatile("ld.volatile.shared.u32 %0, [%1];" : "=r"(v) : "r"(bars + kStarted) : "memory");
                uint32_t tgt = sched.tgt[v];
                if (cur < sched.t_max) {
                    uint32_t c;
                    asm volatile("mov.u32 %0, %clock;" : "=r"(c));
                    if ((int)(c - c0) >= (int)(sched.t_a + cur * sched.t_d)) tgt = max(tgt, cur + 1);
                }
#pragma unroll 1
                for (; cur < tgt; cur++) {
                    if (u == 0) {
                        const uint32_t pos = tiles[cur / 6].pos;
                        const bool f = pos & 0x8000;
                        const uint32_t row = f ? (fine_group(pos, ci) + kRankF * rank) * 32 + lane : ((pos + kRankC * rank + (lane >> 4)) * kGroup + ci) * kSeg + (lane & 15);
                        p = (f ? fine : coarse) + (size_t)row * 768;
                    }
                    prefetch_l2(p);
                    p += 128;
                    u = u == 5 ? 0 : u + 1;
                }
                if (pw < 2 && v >= sched.pw_ev[pw]) {
                    const char* q = (const char*)&g_wfrag[pw][rank][0][0][0] + lane * 128;
#pragma unroll 1
                    for (int l = ci % sched.pw_div; l < 36; l += sched.pw_div) prefetch_l2(q + l * 4096);
                    pw++;
                }
                if (n == 0x1000000) __trap();
                __nanosleep(sched.fsleep);
            }
        } else if (j == 2) {
            CLUSTER_ARRIVE();
            for (uint32_t l = blockIdx.x * 32 + lane; l < 2 * 2304; l += gridDim.x * 32) prefetch_l2(l < 2304 ? wout + l * 128 : wlat + (l - 2304) * 128);
            if (lead) prefetch_tm(&tm_coarse);
            prefetch_tile<0, 6>(tiles[0].pos, ci, rank, lane, fine, coarse);
            if (lead) {
                prefetch_tm(&tm_fine);
                prefetch_tm(&tm_out);
            }
            __syncwarp();
            CLUSTER_WAIT();
            if (lead) {
                if (cid < kPieces) {
                    mbar_wait(bars + kBarPiece, 0);
                    asm volatile("fence.acq_rel.gpu;" ::: "memory");
                    asm volatile("red.relaxed.gpu.global.add.u32 [%0], 1;" ::"l"(&g_ready) : "memory");
                    CURVE_REC(2, 61);
                }
                uint32_t v, n = 0;
                for (;;) {
                    asm volatile("ld.acquire.gpu.global.u32 %0, [%1];" : "=r"(v) : "l"(&g_ready) : "memory");
                    if (v >= 2 * kPieces) break;
                    if (++n == 0x100000) __trap();
                    __nanosleep(50);
                }
                CURVE_REC(2, 62);
                mbar_arrive(bars + kBarReady);
                asm volatile("fence.proxy.async.global;" ::: "memory");
                mbar_arrive(bars + kBarReady2);
                if (atomicAdd(&g_done, 1) == gridDim.x - 1) {
                    g_ready = 0;
                    g_done = 0;
                }
                if (rank == 0 || sched.gate1) {
                    const uint16_t* vt = sched.vt[pat];
                    uint32_t* const ctr = g_progress[sched.pgroup * pat];
                    const int members = sched.members, last = sched.pace_to - 1;
                    asm volatile("ld.relaxed.gpu.global.u32 %0, [%1];" : "=r"(v) : "l"(ctr) : "memory");
                    const uint32_t base = v - v % (members * 1024);
                    int counted = rank == 0 ? sched.pace_from - 1 : last, allowed = sched.pace_from;
#pragma unroll 1
                    for (n = 0; n < 0x10000 && (allowed <= last || counted < last); n++) {
                        int started;
                        asm volatile("ld.volatile.shared.u32 %0, [%1];" : "=r"(started) : "r"(bars + kStarted) : "memory");
                        started = (started + EV - 1) / EV;
                        if (counted < last && counted < started) {
                            const int upto = min(started, last);
                            asm volatile("red.relaxed.gpu.global.add.u32 [%0], %1;" ::"l"(ctr), "r"(vt[upto] - vt[counted]) : "memory");
                            counted = upto;
                        }
                        if (allowed <= last && started + 1 >= allowed) {
                            asm volatile("ld.relaxed.gpu.global.u32 %0, [%1];" : "=r"(v) : "l"(ctr) : "memory");
                            while (allowed <= last && (int)(v - base) >= sched.need[pat][allowed]) allowed++;
                            asm volatile("st.volatile.shared.u32 [%0], %1;" ::"r"(bars + kAllowed), "r"(allowed > last ? kTiles : allowed) : "memory");
                        }
                        __nanosleep(sched.psleep);
                    }
                    asm volatile("st.volatile.shared.u32 [%0], %1;" ::"r"(bars + kAllowed), "r"(kTiles) : "memory");
                    if (counted < last) asm volatile("red.relaxed.gpu.global.add.u32 [%0], %1;" ::"l"(ctr), "r"(vt[last] - vt[counted]) : "memory");
                }
            }
        } else if (j == 1) {
            if (sbase & 1023) __trap();
            if (lead) {
                asm volatile("st.shared.u32 [%0], %1;" ::"r"(bars + kStarted), "r"(0) : "memory");
                asm volatile("st.shared.u32 [%0], %1;" ::"r"(bars + kAllowed), "r"(rank == 0 || sched.gate1 ? sched.pace_from : kTiles) : "memory");
                if (kSlots > 24) {
                    mbar_init(bars + kBarFull + 8 * 24, 1);
                    mbar_init(bars + kBarEmpty + 8 * 24, 6);
                }
                for (int i = 0; i < 3 + 6 * OBUF; i++) mbar_init(bars + kBarPiece + 8 * i, i == 0 ? 12 : i < 3 + 3 * OBUF ? 1 : 4);
                asm volatile("fence.acq_rel.cta;" ::: "memory");
                asm volatile("fence.mbarrier_init.release.cluster;" ::: "memory");
            }
            __syncwarp();
            CLUSTER_ARRIVE();
            CLUSTER_WAIT();
            if (lead) {
                uint32_t k = 0;
                uint64_t pol_first, pol_normal;
                asm volatile("createpolicy.fractional.L2::evict_first.b64 %0, 1.0;" : "=l"(pol_first));
                asm volatile("createpolicy.fractional.L2::evict_normal.b64 %0, 1.0;" : "=l"(pol_normal));
#pragma unroll 1
                for (int t = 0; t < kTiles; t++) {
                    const uint32_t pos = tiles[t].pos, ef = sched.sef[t] >> (3 * rank);
                    if (!(pos & 0x8000)) continue;
                    const int row = fine_group(pos, ci);
#pragma unroll
                    for (int g = 0; g < 3; g++) {
                        mbar_wait1(bars + kBarStaged + 8 * g, k & 1);
                        if (g == 2) CURVE_REC(1, t);
                        asm volatile("fence.proxy.async.shared::cta;" ::: "memory");
                        tma_store_4d(&tm_out, sbase + kOffOut + g * kChunk, rank * 192 + g * 64, row, ef >> g & 1 ? pol_first : pol_normal);
                        asm volatile("cp.async.bulk.commit_group;" ::: "memory");
                        if (g > 0) {
                            asm volatile("cp.async.bulk.wait_group.read 1;" ::: "memory");
                            mbar_arrive(bars + kBarFree + 8 * g - 8);
                        }
                    }
                    asm volatile("cp.async.bulk.wait_group.read 0;" ::: "memory");
                    mbar_arrive(bars + kBarFree + 16);
                    CURVE_REC(3, t);
                    k++;
                }
                asm volatile("cp.async.bulk.wait_group.read 0;" ::: "memory");
            }
        } else {
            CLUSTER_ARRIVE();
            CLUSTER_WAIT();
            if (lead) {
                uint32_t dst0 = sbase + rank * 4096, bar0 = bars;
                asm volatile("" : "+r"(dst0), "+r"(bar0));
                uint32_t wk = 0, wi = 0;
                int allowed = 0;
                uint64_t pol_first, pol_normal;
                asm volatile("createpolicy.fractional.L2::evict_first.b64 %0, 1.0;" : "=l"(pol_first));
                asm volatile("createpolicy.fractional.L2::evict_normal.b64 %0, 1.0;" : "=l"(pol_normal));
#pragma unroll 1
                for (int t = 0; t < kTiles; t++) {
                    const uint4 e = *(const uint4*)&tiles[t];
                    const bool f = e.w & 0x8000;
                    const uint64_t pol = e.w & 0x4000 ? pol_first : pol_normal;
                    const CUtensorMap* tm = f ? &tm_fine : &tm_coarse;
                    const int c3 = f ? 0 : ci * (kSeg / 8), c4 = f ? fine_group(e.w, ci) + kRankF * rank : (e.w & 0xFFF) + kRankC * rank;
                    for (uint32_t n = 0; t >= allowed; n++) {
                        asm volatile("ld.volatile.shared.u32 %0, [%1];" : "=r"(allowed) : "r"(bar0 + kAllowed) : "memory");
                        if (n == 0x4000000) __trap();
                        if (n) __nanosleep(20);
                    }
                    if (t) CURVE_REC(0, t);
#pragma unroll
                    for (int c = 0; c < 6; c++) {
                        if (c % (6 / EV) == 0) asm volatile("st.volatile.shared.u32 [%0], %1;" ::"r"(bar0 + kStarted), "r"(EV * t + 1 + c / (6 / EV)) : "memory");
                        const uint32_t x = c < 4 ? e.x >> (8 * c) : e.y >> (8 * (c - 4)), s8 = x & 0xF8;
                        mbar_wait1(bar0 + kBarEmpty + s8, (x >> 1) & 1);
                        mbar_expect_tx(bar0 + kBarFull + s8, kChunk);
                        tma_load_5d_mc(dst0 + s8 * 1024, tm, c * 64, c3, c4, bar0 + kBarFull + s8, pol);
#pragma unroll 1
                        for (uint32_t n = (e.w >> (16 + 2 * c)) & 3; n; n--) {
                            if (wk == 0) mbar_wait(bar0 + kBarReady2, 0);
                            const uint32_t o = sched.worder[wk], y = (&sched.wslot[pat][wi][0][0])[o];
                            mbar_wait1(bar0 + kBarEmpty + (y & 0xF8), (y >> 1) & 1);
                            mbar_expect_tx(bar0 + kBarSwap + 8 * o, kChunk);
                            bulk_load(sbase + (y & 0xF8) * 1024, (const char*)&g_wfrag[0][rank][0][0][0] + (o - (o >> 3) * 2) * kChunk, bar0 + kBarSwap + 8 * o);
                            if (++wk == 3 * NSTG) wk = 0, wi++;
                        }
                    }
                }
            }
        }
        __syncwarp();
    } else {
        if (elect_one()) {
            for (int i = 2 * warp_id; i < 2 * warp_id + 2; i++) {
                mbar_init(bars + kBarSwap + 8 * i, 1);
                if (i >= kSlots) continue;
                mbar_init(bars + kBarFull + 8 * i, 1);
                mbar_init(bars + kBarEmpty + 8 * i, 6);
            }
            asm volatile("fence.mbarrier_init.release.cluster;" ::: "memory");
        }
        __syncwarp();
        CLUSTER_ARRIVE();
        asm volatile("setmaxnreg.inc.sync.aligned.u32 160;");
        const int tid = threadIdx.x & 127;
        const int warp = tid >> 5;
        const bool rel = tid < 2;
        uint32_t rel_bar;
        asm("mapa.shared::cluster.u32 %0, %1, %2;" : "=r"(rel_bar) : "r"(bars + kBarEmpty), "r"(tid & 1));
        const uint32_t b_lo0 = ((sbase & 0x3FFFF) >> 4) | 0x10000u;
        const uint32_t frag_off = ((lane >> 4) * 8 + (lane & 7)) * 128 + (((2 * warp + ((lane >> 3) & 1)) ^ (lane & 7)) << 4);
        uint32_t st_addr = sbase + kOffOut + OBUF * wg * kChunk + frag_off, tid16 = tid * 16;
        asm volatile("" : "+r"(st_addr), "+r"(tid16));
        uint4* const wf = &g_wfrag[0][rank][wg][0][tid];
        constexpr int kSet = 2 * 3 * 24 * 128;

        float acc[32];
        uint32_t w[96], p[16];

        CLUSTER_WAIT();
        mbar_wait(bars + kBarW + 8 * wg, 0);
        const uint32_t w_addr = sbase + (kSlotW + 6 * wg) * kChunk + frag_off;
#pragma unroll
        for (int s = 0; s < 24; s++)
            asm volatile("ldmatrix.sync.aligned.m8n8.x4.trans.shared.b16 {%0,%1,%2,%3}, [%4];"
                         : "=r"(w[4 * s]), "=r"(w[4 * s + 1]), "=r"(w[4 * s + 2]), "=r"(w[4 * s + 3]) : "r"(w_addr + s * 2048) : "memory");
        if (cid < kPieces) {
            asm volatile("ldmatrix.sync.aligned.m8n8.x4.trans.shared.b16 {%0,%1,%2,%3}, [%4];"
                         : "=r"(p[0]), "=r"(p[1]), "=r"(p[2]), "=r"(p[3]) : "r"(w_addr + cid * 2048) : "memory");
            wf[cid * 128] = make_uint4(p[0], p[1], p[2], p[3]);
        }
        asm volatile("bar.sync %0, 128;" ::"r"(4 + wg) : "memory");
        if (tid < 12 && kSlotW + 6 * wg + (tid >> 1) < kSlots) mbar_arrive_cluster<3>(rel_bar + 8 * (kSlotW + 6 * wg + (tid >> 1)));
        if (threadIdx.x == 0) CURVE_REC(2, 59);
        if (cid < kPieces) {
            mbar_wait(bars + kBarL, 0);
            WG_FENCE();
            piece_steps<0>(acc, w, b_lo0 + kSlotL * 512);
            WG_COMMIT();
            WG_WAIT(0);
            wf[kSet + cid * 128] = make_uint4(pack_bf16(acc[0], acc[1]), pack_bf16(acc[2], acc[3]), pack_bf16(acc[4], acc[5]), pack_bf16(acc[6], acc[7]));
            __syncwarp();
            if (lane == 0) mbar_arrive(bars + kBarPiece);
        }
        if (tid < 4) mbar_arrive_cluster<1>(rel_bar + 8 * (kSlotL + (tid >> 1)));
        if (threadIdx.x == 256) CURVE_REC(2, 60);
#pragma unroll
        for (int i = 0; i < 16; i++) p[i] = 0;

        const int tok_in = 1 + wg, tok_out = wg == 2 ? 1 : wg + 2;
        if (TOKEN_K && wg == 2) asm volatile("bar.arrive 1, 256;" ::: "memory");
        uint32_t nstore = OBUF;
        bool rdy = false;
#pragma unroll 1
        for (int t = 0; t < kTiles; t++) {
            const uint2 e = *(const uint2*)&tiles[t];
            const uint32_t fl = e.y >> 24, pe = tiles[t].p[wg];
            const uint32_t p_addr = sbase + (pe & 0xF8) * 1024 + tid16;
            if ((~fl & (F_FINE | F_P)) == 0) {
#pragma unroll
                for (int q = 0; q < 4; q++)
                    asm volatile("ld.shared.v4.u32 {%0,%1,%2,%3}, [%4];" : "=r"(p[4 * q]), "=r"(p[4 * q + 1]), "=r"(p[4 * q + 2]), "=r"(p[4 * q + 3])
                                 : "r"(p_addr + q * 2048) : "memory");
            }
            if (!SHAPE && (fl & F_SHIFT)) {
#pragma unroll
                for (int i = 0; i < 8; i++) p[i] = p[8 + i];
            }
#pragma unroll
            for (int i = 0; i < 8; i++)
                asm volatile("shl.b32 %0, %4, 16;\nshl.b32 %1, %4, 16;\nand.b32 %2, %4, 0xffff0000;\nand.b32 %3, %4, 0xffff0000;"
                             : "=f"(acc[4 * i]), "=f"(acc[4 * i + 1]), "=f"(acc[4 * i + 2]), "=f"(acc[4 * i + 3]) : "r"(p[SHAPE ? i & 3 : i]));
            if (SHAPE) {
#pragma unroll
                for (int i = 0; i < 12; i++) p[i] = p[4 + i];
            }
            if (fl & F_READY) mbar_wait(bars + kBarReady, 0);
            const char* swap = (const char*)&g_wfrag[~fl & F_FINE][rank][wg][0][0];
            if (TOKEN_K) asm volatile("bar.sync %0, 256;" ::"r"(tok_in) : "memory");
            auto body = [&](auto mode) {
                constexpr int M = decltype(mode)::value;
                rdy = issue_chunk<0>(acc, w, e, bars, b_lo0, rdy);
                rdy = issue_chunk<1>(acc, w, e, bars, b_lo0, rdy);
                if (TOKEN_K == 2) asm volatile("bar.arrive %0, 256;" ::"r"(tok_out) : "memory");
                retire_chunk<0, 1, M>(w, e, sched.wslot[pat], wg, sbase, rel_bar, rel, swap, tid16);
                if (M == 0 && rel && (~fl & (F_FINE | F_P)) == 0) mbar_arrive_cluster<3>(rel_bar + (pe & 0xF8));
                rdy = issue_chunk<2>(acc, w, e, bars, b_lo0, rdy);
                if (TOKEN_K == 3) asm volatile("bar.arrive %0, 256;" ::"r"(tok_out) : "memory");
                retire_chunk<1, 1, M>(w, e, sched.wslot[pat], wg, sbase, rel_bar, rel, swap, tid16);
                rdy = issue_chunk<3>(acc, w, e, bars, b_lo0, rdy);
                retire_chunk<2, 1, M>(w, e, sched.wslot[pat], wg, sbase, rel_bar, rel, swap, tid16);
                rdy = issue_chunk<4>(acc, w, e, bars, b_lo0, rdy);
                retire_chunk<3, 1, M>(w, e, sched.wslot[pat], wg, sbase, rel_bar, rel, swap, tid16);
                rdy = issue_chunk<5>(acc, w, e, bars, b_lo0, rdy);
                retire_chunk<4, 1, M>(w, e, sched.wslot[pat], wg, sbase, rel_bar, rel, swap, tid16);
                if (fl & F_FINE) mbar_wait(bars + kBarFree + 8 * OBUF * wg + 8 * (nstore & (OBUF - 1)), (nstore >> (OBUF - 1)) & 1);
                else if (M == 0) mbar_wait(bars + kBarEmpty + (pe & 0xF8), (pe >> 1) & 1);
                retire_chunk<5, 0, M>(w, e, sched.wslot[pat], wg, sbase, rel_bar, rel, swap, tid16);
            };
            if (!(fl & F_SWAP)) body(std::integral_constant<int, 0>());
            else if (fl & F_STAGED) body(std::integral_constant<int, 2>());
            else body(std::integral_constant<int, 1>());
            if (fl & F_FINE) {
                const uint32_t ob = nstore & (OBUF - 1);
                nstore++;
#pragma unroll
                for (int q = 0; q < 4; q++)
                    asm volatile("stmatrix.sync.aligned.m8n8.x4.trans.shared.b16 [%0], {%1,%2,%3,%4};" ::"r"(st_addr + ob * kChunk + q * 2048),
                                 "r"(pack_bf16(acc[8 * q], acc[8 * q + 1])), "r"(pack_bf16(acc[8 * q + 2], acc[8 * q + 3])),
                                 "r"(pack_bf16(acc[8 * q + 4], acc[8 * q + 5])), "r"(pack_bf16(acc[8 * q + 6], acc[8 * q + 7])) : "memory");
                __syncwarp();
                if (elect_one()) mbar_arrive(bars + kBarStaged + 8 * OBUF * wg + 8 * ob);
            } else {
#pragma unroll
                for (int q = 0; q < 4; q++) {
                    p[4 * q] = pack_bf16(acc[8 * q], acc[8 * q + 2]);
                    p[4 * q + 1] = pack_bf16(acc[8 * q + 1], acc[8 * q + 3]);
                    p[4 * q + 2] = pack_bf16(acc[8 * q + 4], acc[8 * q + 6]);
                    p[4 * q + 3] = pack_bf16(acc[8 * q + 5], acc[8 * q + 7]);
                    if (fl & F_P)
                        asm volatile("st.shared.v4.u32 [%0], {%1,%2,%3,%4};" ::"r"(p_addr + q * 2048),
                                     "r"(p[4 * q]), "r"(p[4 * q + 1]), "r"(p[4 * q + 2]), "r"(p[4 * q + 3]) : "memory");
                }
            }
        }
        if (TOKEN_K && wg == 0) asm volatile("bar.sync 1, 256;" ::: "memory");
    }
    CLUSTER_ARRIVE();
    CLUSTER_WAIT();
    if (threadIdx.x == 0) CURVE_REC(0, 63);
}

void build_schedule(int pat, Tile* tl, uint8_t (*wslot)[3][8], uint8_t* worder, const int* gs) {
    const int take[3] = {TAKE}, give[3] = {GIVE};
    const int staged = envi("STAGED", 1), wadv = envi("WADV", 4), wrel = envi("WREL", 0);
    int coarse_of[16];
    int n = 0, nsw = 0, swt[2] = {};
    int units[kTiles];
    auto unit = [&](int t) { return units[t]; };
    for (int g = 0, i0 = 0; gs[g]; i0 += gs[g], g++) {
        for (int i = 1; i <= gs[g]; i++, n++) {
            units[n] = i0 + i % gs[g];
            tl[n].pos = (units[n] * NPAT + pat) * (SHAPE ? 4 : 2);
            tl[n].flags = i < gs[g] ? F_P : F_SWAP | F_SWAPH | (g == 0 ? F_READY : 0);
            coarse_of[unit(n)] = n;
        }
        for (int i = 0; i < 4 * gs[g]; i++, n++) {
            units[n] = i0 + i / 4;
            tl[n].pos = 0x8000 + (SHAPE ? ((units[n] * NPAT + pat) * 4 + (i & 3)) * kGroup : ((units[n] * NPAT + pat) * 2 + (i & 3) / 2) * kGroup + (i & 1) * 0x1000);
            tl[n].flags = F_FINE | (i >= 4 && (i & 3) == 0 ? F_P : 0) | ((i & 3) == 2 ? F_SHIFT : 0);
            if (i == 4 * gs[g] - 1 && gs[g + 1]) {
                tl[n].flags |= staged ? F_SWAP | F_STAGED | (nsw ? F_SW1 : 0) : F_SWAP | F_SWAPH;
                if (staged) swt[nsw++] = n;
            }
        }
    }
    int nwo = 0;
    for (int need = -4; need < 6; need++)
        for (int g = 0; g < 3; g++) {
            const int c = need - give[g];
            if (c < 6 - NSTG || c > 5) continue;
            worder[nwo++] = g * 8 + c;
            for (int i = 0; i < nsw; i++) {
                const int j = 6 * swt[i] + need + 4 - wadv;
                tl[j / 6].wcnt += 1 << (2 * (j % 6));
            }
        }
    int uses[kSlots], loads[kSlots], queue[512], head = 0, tail = 0, slot_of[6 * kTiles];
    for (int s = 0; s < kSlots; s++) uses[s] = s >= kSlotL, loads[s] = 0;
    auto take_p = [&](int t, int w, int s) { tl[t].p[w] = s * 8 + ((uses[s] + 1) & 1) * 2; uses[s]++; };
    bool taken[kSlots] = {};
    for (int w = 0; w < 3; w++)
        if (take[w] < 0 && (tl[0].flags & F_P)) take_p(0, w, kSlotW + 6 * w + 2), taken[kSlotW + 6 * w + 2] = true;
    for (int s = 0; s < kSlotL; s++) queue[tail++] = s;
    for (int s = kSlotW; s < kSlots; s++) if (!taken[s]) queue[tail++] = s;
    for (int s = kSlotL; s < kSlotW; s++) queue[tail++] = s;
    int r = 0, wk = 0, wi = 0;
    auto get_slot = [&]() {
        for (; head == tail; r++) {
            bool to_p = false;
            for (int w = 0; w < 3; w++) {
                int x = r - take[w];
                if (x >= 0 && x % 6 == 0 && x / 6 < kTiles && (tl[x / 6].flags & (F_FINE | F_P)) == F_P) take_p(x / 6, w, slot_of[r]), to_p = true;
            }
            if (!to_p) queue[tail++] = slot_of[r];
            for (int w = 0; w < 3; w++) {
                int x = r - give[w];
                if (x >= 0 && x % 6 == 0 && x / 6 < kTiles && (tl[x / 6].flags & (F_FINE | F_P)) == (F_FINE | F_P)) {
                    tl[x / 6].p[w] = tl[coarse_of[unit(x / 6)]].p[w];
                    queue[tail++] = tl[x / 6].p[w] >> 3;
                }
                x -= wrel;
                if (x >= 0 && x / 6 < kTiles && (tl[x / 6].flags & F_STAGED) && x % 6 >= 6 - NSTG) queue[tail++] = wslot[tl[x / 6].flags >> 7][w][x % 6] >> 3;
            }
        }
        return queue[head++];
    };
    for (int c = 0; c < 6 * kTiles; c++) {
        int s = get_slot();
        slot_of[c] = s;
        tl[c / 6].chunk[c % 6] = s * 8 + ((uses[s] + 1) & 1) * 2 + (loads[s] & 1);
        if (c % 6 == 0 && c) tl[c / 6 - 1].chunk[6] = tl[c / 6].chunk[0];
        uses[s]++, loads[s]++;
        for (int k = (tl[c / 6].wcnt >> (2 * (c % 6))) & 3; k; k--) {
            s = get_slot();
            (&wslot[wi][0][0])[worder[wk]] = s * 8 + ((uses[s] + 1) & 1) * 2;
            uses[s]++;
            if (++wk == 3 * NSTG) wk = 0, wi++;
        }
    }
    for (int t = 0; t < kTiles; t++)
        if ((tl[t].flags & (F_FINE | F_P)) == (F_FINE | F_P)) memcpy(tl[t].p, tl[coarse_of[unit(t)]].p, 3);
}

typedef CUresult (*EncodeFn)(CUtensorMap*, CUtensorMapDataType, cuuint32_t, void*, const cuuint64_t*, const cuuint64_t*,
                             const cuuint32_t*, const cuuint32_t*, CUtensorMapInterleave, CUtensorMapSwizzle,
                             CUtensorMapL2promotion, CUtensorMapFloatOOBfill);

void encode_2d(EncodeFn enc, CUtensorMap* tm, const void* ptr, uint64_t rows, uint32_t box_rows, CUtensorMapL2promotion promo) {
    cuuint64_t dims[2] = {(cuuint64_t)kC, rows};
    cuuint64_t strides[1] = {(cuuint64_t)kC * 2};
    cuuint32_t box[2] = {64, box_rows};
    cuuint32_t es[2] = {1, 1};
    enc(tm, CU_TENSOR_MAP_DATA_TYPE_BFLOAT16, 2, const_cast<void*>(ptr), dims, strides, box, es, CU_TENSOR_MAP_INTERLEAVE_NONE,
        CU_TENSOR_MAP_SWIZZLE_128B, promo, CU_TENSOR_MAP_FLOAT_OOB_FILL_NONE);
}

}

extern "C" void kernel_launch(void* const* d_in, const int* in_sizes, int n_in, void* d_out, int out_size) {
    (void)in_sizes; (void)n_in; (void)out_size;
    static EncodeFn enc = nullptr;
    static Schedule sched;
    if (!enc) {
        void* fn = nullptr;
        cudaDriverEntryPointQueryResult qr;
        cudaGetDriverEntryPoint("cuTensorMapEncodeTiled", &fn, cudaEnableDefault, &qr);
        enc = (EncodeFn)fn;
        cudaFuncSetAttribute(fpn_lateral_kernel, cudaFuncAttributeMaxDynamicSharedMemorySize, kSmemBytes);
        if (envi("CARVE", 0)) cudaFuncSetAttribute(fpn_lateral_kernel, cudaFuncAttributePreferredSharedMemoryCarveout, envi("CARVE", 0));
        cudaLaunchConfig_t cfg = {};
        cfg.gridDim = dim3(2);
        cfg.blockDim = dim3(512);
        cfg.dynamicSmemBytes = kSmemBytes;
        cudaLaunchAttribute at;
        at.id = cudaLaunchAttributeClusterDimension;
        at.val.clusterDim.x = 2; at.val.clusterDim.y = 1; at.val.clusterDim.z = 1;
        cfg.attrs = &at; cfg.numAttrs = 1;
        int ncl = 0;
        if (cudaOccupancyMaxActiveClusters(&ncl, fpn_lateral_kernel, &cfg) != cudaSuccess) { (void)cudaGetLastError(); ncl = 0; }
        const char* pn[4] = {"PATA", "PATB", "PATC", "PATD"};
        const char* pd[4] = {"45", "45", "36", "63"};
        sched.pgroup = envi("PGROUP", 0), sched.members = sched.pgroup ? kGroup : kClusters;
        for (int q = 0; q < NPAT; q++) {
            int gs[8] = {};
            const char* sa = envs(pn[q], pd[q]);
            for (int i = 0; sa[i]; i++) gs[i] = sa[i] - '0';
            build_schedule(q, sched.tile[q], sched.wslot[q], sched.worder, gs);
        }
        {
            const uint8_t masks[7] = {0, 1, 9, 0x15, 0x1B, 0x1F, 0x3F};
            const char* sef = envs("SEF", "000000000000000000000000000000000000000000000");
            for (int t = 0; t < kTiles; t++) sched.sef[t] = masks[sef[t] - '0'];
            const char* lead = envs("LEAD", "000066ciooooiicc666666666666666666666666666666");
            auto digit = [](char ch) { return ch > '9' ? ch - 'a' + 10 : ch - '0'; };
            sched.pf_from = envi("PFFROM", 30);
            int pos = sched.pf_from;
            sched.tgt[0] = pos;
            for (int e = 0; e < EV * kTiles; e++) {
                const int t = e / EV, f = e % EV + 1;
                const int x = 6 * t + f * (6 / EV) + (digit(lead[t]) * (EV - f) + digit(lead[t + 1]) * f) / EV;
                if (pos < x) pos = x;
                if (pos > 6 * kTiles) pos = 6 * kTiles;
                sched.tgt[e + 1] = pos;
            }
            sched.pw_ev[0] = envi("PW0", 0) * EV / 6 + 1, sched.pw_ev[1] = envi("PW1", 141) * EV / 6 + 1, sched.pw_div = envi("PWDIV", 4);
            sched.t_a = envi("TA", 0), sched.t_d = envi("TD", 290), sched.t_max = envi("TMAX", 0), sched.fsleep = envi("FSLEEP", 40);
        }
        sched.gate1 = envi("GATE1", 1), sched.psleep = envi("PSLEEP", 100);
        sched.pace_from = envi("PACE_FROM", 14), sched.pace_to = envi("PACE_TO", 45);
        const char* v5 = "555555555555555555555555555555555555555555555";
        const char* vts[4] = {envs("VTA", v5), envs("VTB", v5), envs("VTC", v5), envs("VTD", v5)};
        int total = 0;
        for (int q = 0; q < NPAT; q++) {
            int sum[kTiles + 1] = {};
            for (int t = sched.pace_from; t < sched.pace_to; t++) sum[t] = sum[t - 1] + vts[q][t] - '0';
            total = sum[sched.pace_to - 1];
            for (int t = sched.pace_from; t < sched.pace_to; t++) {
                sched.vt[q][t] = sum[t] * 1024 / total;
                int slack = envi("PSTART", 160) - envi("PRAMP", 6) * (t - sched.pace_from);
                if (slack < envi("PACE", 40)) slack = envi("PACE", 40);
                if (envs("SLK", nullptr)) slack = (envs("SLK", nullptr)[t] - '0') * 16;
                sched.need[q][t] = ncl >= kClusters ? sched.vt[q][t] * sched.members - slack * 5 * 1024 / total * sched.members / 64 : -1;
            }
        }
    }
    CUtensorMap tm_fine, tm_coarse, tm_wlat, tm_wout, tm_out;
    const cuuint32_t ones[5] = {1, 1, 1, 1, 1};
    {
        cuuint64_t dims[5] = {(cuuint64_t)kC, 2, 4, 4, (cuuint64_t)kFinePix / 32};
        cuuint64_t strides[4] = {768, 2 * 768, 8 * 768, 32 * 768};
        cuuint32_t box[5] = {64, 2, 4, 4, 1};
        enc(&tm_fine, CU_TENSOR_MAP_DATA_TYPE_BFLOAT16, 5, d_in[0], dims, strides, box, ones, CU_TENSOR_MAP_INTERLEAVE_NONE,
            CU_TENSOR_MAP_SWIZZLE_128B, CU_TENSOR_MAP_L2_PROMOTION_L2_128B, CU_TENSOR_MAP_FLOAT_OOB_FILL_NONE);
    }
    {
        cuuint64_t dims[3] = {64, (cuuint64_t)kC, 6};
        cuuint64_t strides[2] = {768, 128};
        cuuint32_t box[3] = {64, 16, 6};
        cuuint32_t es[3] = {1, 1, 1};
        enc(&tm_wlat, CU_TENSOR_MAP_DATA_TYPE_BFLOAT16, 3, d_in[2], dims, strides, box, es, CU_TENSOR_MAP_INTERLEAVE_NONE,
            CU_TENSOR_MAP_SWIZZLE_128B, CU_TENSOR_MAP_L2_PROMOTION_L2_256B, CU_TENSOR_MAP_FLOAT_OOB_FILL_NONE);
    }
    encode_2d(enc, &tm_wout, d_in[3], kC, 192, CU_TENSOR_MAP_L2_PROMOTION_L2_256B);
    {
        cuuint64_t dims[4] = {(cuuint64_t)kC, 32, 2, (cuuint64_t)kFinePix / 32 - kRankF};
        cuuint64_t strides[3] = {768, kRankF * 32 * 768, 32 * 768};
        cuuint32_t box[4] = {64, 32, 2, 1};
        enc(&tm_out, CU_TENSOR_MAP_DATA_TYPE_BFLOAT16, 4, d_out, dims, strides, box, ones, CU_TENSOR_MAP_INTERLEAVE_NONE,
            CU_TENSOR_MAP_SWIZZLE_128B, CU_TENSOR_MAP_L2_PROMOTION_NONE, CU_TENSOR_MAP_FLOAT_OOB_FILL_NONE);
    }
    {
        cuuint64_t dims[5] = {(cuuint64_t)kC, 2, 4, kGroup * kSeg / 8, (cuuint64_t)kCoarsePix / (kGroup * kSeg)};
        cuuint64_t strides[4] = {4 * 768, 768, 8 * 768, kGroup * kSeg * 768};
        cuuint32_t box[5] = {64, 2, 4, kSeg / 8, 32 / kSeg};
        enc(&tm_coarse, CU_TENSOR_MAP_DATA_TYPE_BFLOAT16, 5, d_in[1], dims, strides, box, ones, CU_TENSOR_MAP_INTERLEAVE_NONE,
            CU_TENSOR_MAP_SWIZZLE_128B, CU_TENSOR_MAP_L2_PROMOTION_L2_128B, CU_TENSOR_MAP_FLOAT_OOB_FILL_NONE);
    }
    fpn_lateral_kernel<<<2 * kClusters, 512, kSmemBytes>>>(tm_fine, tm_coarse, tm_wlat, tm_wout, tm_out, sched, (const char*)d_in[0], (const char*)d_in[1],
                                                          (const char*)d_in[2], (const char*)d_in[3]);
}
```

```cpp
#include <cuda_runtime.h>
#include <cuda_bf16.h>
#include <cuda.h>
#include <stdint.h>
#include <string.h>
#include <type_traits>
#include <stdlib.h>

#define TOKEN_K 3
#define TAKE -2, 0, 2
#define GIVE -4, -2, 0
#define L_POS 0
#define NSTG 6
#define EV 3
#define STPOL 0
#define NO_MMA 0
#define EARLY 1
#define EARLY_T 0
#define W_PRE 0
#define TOPPF 1
#define TLBW 1
#define W_MIX 0x1E
#define WR 1
#define CHAINS 1
#define ROT 0
#define PUBTMA 1
#define DEFER 2
#define INLOOP 1
#define WSPLIT 1
#define TPF_N 0
#define TPF_A 400
#define TPF_D 300
#define NPAT 1
#define SHAPE 1
#define OBUF 1
#define LD_EF 0
#define CURVE_REC(k, i) do {} while (0)

#define CREC0(c) do {} while (0)
namespace {

constexpr int kC = 384;
constexpr int kFinePix = 384 * 384;
constexpr int kCoarsePix = 192 * 192;
constexpr int kClusters = 64;
constexpr int kTiles = 45;
#define SLOTS (28 - 3 * OBUF)
constexpr int kSlots = SLOTS;
constexpr int kChunk = 8192;
constexpr int kTileBytes = 6 * kChunk;
constexpr int kOffOut = kSlots * kChunk;
constexpr int kOffBar = kOffOut + 3 * OBUF * kChunk;
constexpr int kSmemBytes = kOffBar + 1024;
constexpr int kSlotL = kSlots + 3 * OBUF - 20;
constexpr int kSlotW = kSlots + 3 * OBUF - 18;
constexpr int kBarFull = 0, kBarEmpty = 8 * kSlots, kBarW = 16 * kSlots, kBarL = kBarW + 24;
constexpr int kBarPiece = kBarL + 8, kBarReady = kBarPiece + 8, kBarGo = kBarReady + 8, kBarFree = kBarGo + 8, kBarStaged = kBarFree + 24 * OBUF;
constexpr int kBarSwap = kBarStaged + 24 * OBUF;
constexpr int kBarReady2 = kBarSwap + 56;
constexpr int kStarted = kBarSwap + 192, kAllowed = kStarted + 4;
constexpr int kBarW2 = WSPLIT ? kStarted + 8 : kBarW;
constexpr int kPos0 = 4;
constexpr int kPieces = 24;

enum : uint32_t { F_FINE = 1, F_P = 2, F_Q1 = 4, F_SWAP = 8, F_READY = 16, F_Q2 = 32, F_STAGED = 64, F_SW1 = 128 };
struct alignas(16) Tile {
    uint8_t chunk[7];
    uint8_t flags;
    uint8_t p[3];
    uint8_t pw;
    uint16_t pos;
    uint16_t wcnt;
};
constexpr int kGroup = kClusters / NPAT;
struct Schedule {
    Tile tile[NPAT][kTiles + 1];
    uint16_t tgt[EV * kTiles + 2];
    alignas(8) uint8_t wslot[NPAT][2][3][8];
    uint8_t worder[24];
    uint8_t sef[48];
    int members, pgroup;
    int pace_from, pace_to, gate1, psleep, pf_from, pw_ev[2], pw_div, t_a, t_d, t_max, fsleep;
    int need[NPAT][kTiles + 1];
    uint16_t vt[NPAT][kTiles + 1];
};
static int envi(const char*, int d) { return d; }
static const char* envs(const char*, const char* d) { return d; }

struct Scratch {
    uint4 wfrag[2][2][3][24][128];
    uint32_t ready, pad0[31];
    uint32_t done, pad1[31];
    uint32_t progress[4][32];
};
__device__ Scratch g_scratch;
#define g_wfrag scr->wfrag
#define g_ready scr->ready
#define g_done scr->done
#define g_progress scr->progress

__device__ __forceinline__ uint32_t smem_u32(const void* p) { return (uint32_t)__cvta_generic_to_shared(p); }

__device__ __forceinline__ void mbar_init(uint32_t bar, uint32_t count) {
    asm volatile("mbarrier.init.shared::cta.b64 [%0], %1;" ::"r"(bar), "r"(count) : "memory");
}
__device__ __forceinline__ void mbar_expect_tx(uint32_t bar, uint32_t bytes) {
    asm volatile("mbarrier.arrive.expect_tx.shared::cta.b64 _, [%0], %1;" ::"r"(bar), "r"(bytes) : "memory");
}
__device__ __forceinline__ void mbar_wait(uint32_t bar, uint32_t parity) {
    asm volatile(
        "{\n"
        ".reg .pred p;\n"
        ".reg .u32 n;\n"
        "mov.u32 n, 0;\n"
        "WAIT_LOOP:\n"
        "mbarrier.try_wait.parity.shared::cta.b64 p, [%0], %1;\n"
        "@p bra WAIT_DONE;\n"
        "add.u32 n, n, 1;\n"
        "setp.lt.u32 p, n, 0x400000;\n"
        "@p bra WAIT_LOOP;\n"
        "trap;\n"
        "WAIT_DONE:\n"
        "}\n" ::"r"(bar), "r"(parity) : "memory");
}
__device__ __forceinline__ void mbar_wait1(uint32_t bar, uint32_t parity) {
    uint32_t r;
    asm volatile("{\n.reg .pred p;\nmbarrier.try_wait.parity.shared::cta.b64 p, [%1], %2;\nselp.u32 %0, 1, 0, p;\n}\n" : "=r"(r) : "r"(bar), "r"(parity) : "memory");
    if (!r) mbar_wait(bar, parity);
}
__device__ __forceinline__ bool mbar_test(uint32_t bar, uint32_t parity) {
    uint32_t r;
    asm volatile("{\n.reg .pred p;\nmbarrier.test_wait.parity.shared::cta.b64 p, [%1], %2;\nselp.u32 %0, 1, 0, p;\n}\n" : "=r"(r) : "r"(bar), "r"(parity) : "memory");
    return r != 0;
}
__device__ __forceinline__ void mbar_arrive(uint32_t bar) {
    asm volatile("mbarrier.arrive.shared::cta.b64 _, [%0];" ::"r"(bar) : "memory");
}
template <int N>
__device__ __forceinline__ void mbar_arrive_cluster(uint32_t bar) {
    if (N == 1) asm volatile("mbarrier.arrive.shared::cluster.b64 _, [%0];" ::"r"(bar) : "memory");
    else asm volatile("mbarrier.arrive.shared::cluster.b64 _, [%0], %1;" ::"r"(bar), "n"(N) : "memory");
}
__device__ __forceinline__ void bulk_load(uint32_t dst, const void* src, uint32_t bar) {
    asm volatile("cp.async.bulk.shared::cluster.global.mbarrier::complete_tx::bytes [%0], [%1], %2, [%3];"
                 ::"r"(dst), "l"(src), "n"(kChunk), "r"(bar) : "memory");
}
__device__ __forceinline__ void tma_load_2d(uint32_t dst, const CUtensorMap* tm, int c0, int c1, uint32_t bar) {
    asm volatile("cp.async.bulk.tensor.2d.shared::cluster.global.mbarrier::complete_tx::bytes [%0], [%1, {%2, %3}], [%4];"
                 ::"r"(dst), "l"(tm), "r"(c0), "r"(c1), "r"(bar) : "memory");
}
__device__ __forceinline__ void tma_load_3d(uint32_t dst, const CUtensorMap* tm, int c1, uint32_t bar) {
    asm volatile("cp.async.bulk.tensor.3d.shared::cluster.global.mbarrier::complete_tx::bytes [%0], [%1, {%2, %3, %2}], [%4];"
                 ::"r"(dst), "l"(tm), "r"(0), "r"(c1), "r"(bar) : "memory");
}
__device__ __forceinline__ void tma_load_5d_mc(uint32_t dst, const CUtensorMap* tm, int c0, int c3, int c4, uint32_t bar, uint64_t pol) {
    asm volatile("cp.async.bulk.tensor.5d.shared::cluster.global.mbarrier::complete_tx::bytes.multicast::cluster [%0], [%1, {%2, %3, %3, %4, %5}], [%6], %7;"
                 ::"r"(dst), "l"(tm), "r"(c0), "r"(0), "r"(c3), "r"(c4), "r"(bar), "h"((uint16_t)3) : "memory");
}
__device__ __forceinline__ void tma_store_4d(const CUtensorMap* tm, uint32_t src, int c0, int c3, uint64_t pol) {
    if (STPOL) asm volatile("cp.async.bulk.tensor.4d.global.shared::cta.bulk_group.L2::cache_hint [%0, {%2, %3, %3, %4}], [%1], %5;"
                 ::"l"(tm), "r"(src), "r"(c0), "r"(0), "r"(c3), "l"(pol) : "memory");
    else asm volatile("cp.async.bulk.tensor.4d.global.shared::cta.bulk_group [%0, {%2, %3, %3, %4}], [%1];"
                 ::"l"(tm), "r"(src), "r"(c0), "r"(0), "r"(c3) : "memory");
}
__device__ __forceinline__ void prefetch_l2(const void* p) {
    asm volatile("prefetch.global.L2 [%0];" ::"l"(p) : "memory");
}
__device__ __forceinline__ void prefetch_tm(const CUtensorMap* tm) {
    asm volatile("prefetch.tensormap [%0];" ::"l"(tm) : "memory");
}
__device__ __forceinline__ uint32_t now_ns() {
    uint32_t t;
    asm volatile("mov.u32 %0, %globaltimer_lo;" : "=r"(t));
    return t;
}
__device__ __forceinline__ bool elect_one() {
    uint32_t p;
    asm volatile("{\n.reg .pred p;\nelect.sync _|p, 0xffffffff;\nselp.u32 %0, 1, 0, p;\n}\n" : "=r"(p));
    return p != 0;
}
#define CLUSTER_ARRIVE() asm volatile("barrier.cluster.arrive.relaxed.aligned;" ::: "memory")
#define CLUSTER_WAIT() asm volatile("barrier.cluster.wait.acquire.aligned;" ::: "memory")

#define WG_FENCE() asm volatile("wgmma.fence.sync.aligned;" ::: "memory")
#define WG_COMMIT() asm volatile("wgmma.commit_group.sync.aligned;" ::: "memory")
#define WG_WAIT(n) asm volatile("wgmma.wait_group.sync.aligned %0;" ::"n"(n) : "memory")

#define ACC32 "{%0,%1,%2,%3,%4,%5,%6,%7,%8,%9,%10,%11,%12,%13,%14,%15,%16,%17,%18,%19,%20,%21,%22,%23,%24,%25,%26,%27,%28,%29,%30,%31}"
#define ACC8(b) "+f"(d[b]), "+f"(d[b + 1]), "+f"(d[b + 2]), "+f"(d[b + 3]), "+f"(d[b + 4]), "+f"(d[b + 5]), "+f"(d[b + 6]), "+f"(d[b + 7])

#define DESC_HI "0x40000040"
template <int BOFF>
__device__ __forceinline__ void wgmma_rs(float (&d)[32], const uint32_t* a, uint32_t b_lo) {
    asm volatile("{\n.reg .b32 tb;\n.reg .b64 db;\nadd.u32 tb, %36, %37;\nmov.b64 db, {tb, " DESC_HI "};\n"
                 "wgmma.mma_async.sync.aligned.m64n64k16.f32.bf16.bf16 " ACC32 ", {%32,%33,%34,%35}, db, 1, 1, 1, 0;\n}\n"
                 : ACC8(0), ACC8(8), ACC8(16), ACC8(24)
                 : "r"(a[0]), "r"(a[1]), "r"(a[2]), "r"(a[3]), "r"(b_lo), "n"(BOFF));
}
__device__ __forceinline__ void wgmma_rs_first(float (&d)[32], const uint32_t* a, uint32_t b_lo, uint32_t accum) {
    asm volatile("{\n.reg .pred p;\n.reg .b64 db;\nsetp.ne.u32 p, %37, 0;\nmov.b64 db, {%36, " DESC_HI "};\n"
                 "wgmma.mma_async.sync.aligned.m64n64k16.f32.bf16.bf16 " ACC32 ", {%32,%33,%34,%35}, db, p, 1, 1, 0;\n}\n"
                 : ACC8(0), ACC8(8), ACC8(16), ACC8(24)
                 : "r"(a[0]), "r"(a[1]), "r"(a[2]), "r"(a[3]), "r"(b_lo), "r"(accum));
}
template <int ACCUM, int BOFF, int D>
__device__ __forceinline__ void wgmma_rs16(float (&d)[32], const uint32_t* a, uint32_t b_lo) {
    asm volatile("{\n.reg .b32 tb;\n.reg .b64 db;\nadd.u32 tb, %12, %13;\nmov.b64 db, {tb, " DESC_HI "};\n"
                 "wgmma.mma_async.sync.aligned.m64n16k16.f32.bf16.bf16 {%0,%1,%2,%3,%4,%5,%6,%7}, {%8,%9,%10,%11}, db, %14, 1, 1, 0;\n}\n"
                 : ACC8(D)
                 : "r"(a[0]), "r"(a[1]), "r"(a[2]), "r"(a[3]), "r"(b_lo), "n"(BOFF), "n"(ACCUM));
}
template <int S>
__device__ __forceinline__ void piece_steps(float (&d)[32], const uint32_t (&w)[96], uint32_t b_lo) {
    if constexpr (S < 24) {
        wgmma_rs16<(S >= CHAINS), (S >> 2) * 128 + (S & 3) * 2, S % CHAINS * 8>(d, &w[4 * S], b_lo);
        piece_steps<S + 1>(d, w, b_lo);
    }
}

__device__ __forceinline__ uint32_t pack_bf16(float lo, float hi) {
    uint32_t r;
    asm("cvt.rn.bf16x2.f32 %0, %1, %2;" : "=r"(r) : "f"(hi), "f"(lo));
    return r;
}

template <int C>
__device__ __forceinline__ void reload_w(uint32_t (&w)[96], const char* base, uint32_t tid16, uint32_t on) {
#define W4(i) "+r"(w[16 * C + 4 * i]), "+r"(w[16 * C + 4 * i + 1]), "+r"(w[16 * C + 4 * i + 2]), "+r"(w[16 * C + 4 * i + 3])
    asm volatile("{\n.reg .pred p;\n.reg .b64 a;\nsetp.ne.u32 p, %19, 0;\ncvt.u64.u32 a, %18;\nadd.u64 a, a, %16;\n"
                 "@p ld.global.cg.v4.u32 {%0,%1,%2,%3}, [a + %17];\n"
                 "@p ld.global.cg.v4.u32 {%4,%5,%6,%7}, [a + %17 + 2048];\n"
                 "@p ld.global.cg.v4.u32 {%8,%9,%10,%11}, [a + %17 + 4096];\n"
                 "@p ld.global.cg.v4.u32 {%12,%13,%14,%15}, [a + %17 + 6144];\n}\n"
                 : W4(0), W4(1), W4(2), W4(3)
                 : "l"(base), "n"(C * 8192), "r"(tid16), "r"(on) : "memory");
#undef W4
}

template <int C>
__device__ __forceinline__ uint32_t entry(uint2 e) { return C < 4 ? e.x >> (8 * C) : e.y >> (8 * (C - 4)); }

template <int C>
__device__ __forceinline__ bool issue_chunk(float (&acc)[32], const uint32_t (&w)[96], uint2 e, uint32_t bars, uint32_t b_lo0, bool ready) {
    if (!ready) mbar_wait(bars + kBarFull + (entry<C>(e) & 0xF8), entry<C>(e) & 1);
    const bool next = C < 5 && mbar_test(bars + kBarFull + (entry<C + 1>(e) & 0xF8), entry<C + 1>(e) & 1);
    const uint32_t b_lo = b_lo0 + (entry<C>(e) & 0xF8) * 64;
    if (!NO_MMA) {
        WG_FENCE();
        if (C == 0) wgmma_rs_first(acc, &w[0], b_lo, e.y & (F_FINE << 24));
        else wgmma_rs<0>(acc, &w[16 * C], b_lo);
        wgmma_rs<2>(acc, &w[16 * C + 4], b_lo);
        wgmma_rs<4>(acc, &w[16 * C + 8], b_lo);
        wgmma_rs<6>(acc, &w[16 * C + 12], b_lo);
        WG_COMMIT();
    }
    return next;
}
template <int C, int PENDING, int MODE>
__device__ __forceinline__ void retire_chunk(uint32_t (&w)[96], uint2 e, const uint8_t (*ws)[3][8], int wg, uint32_t sbase, uint32_t rel_bar, bool rel, const char* swap, uint32_t tid16) {
    if (!NO_MMA) WG_WAIT(PENDING);
    if (rel) mbar_arrive_cluster<1>(rel_bar + (entry<C>(e) & 0xF8));
    if (MODE == 1 && C < 6 - DEFER) reload_w<C>(w, swap, tid16, 1);
    if (MODE == 2 && C >= 6 - NSTG) {
        const uint32_t x = ws[e.y >> 31][wg][C];
        mbar_wait(sbase + kOffBar + kBarSwap + 64 * wg + 8 * C, e.y >> 31);
        const uint32_t a = sbase + (x & 0xF8) * 1024 + tid16;
#pragma unroll
        for (int q = 0; q < 4; q++)
            asm volatile("ld.shared.v4.u32 {%0,%1,%2,%3}, [%4];" : "=r"(w[16 * C + 4 * q]), "=r"(w[16 * C + 4 * q + 1]), "=r"(w[16 * C + 4 * q + 2]), "=r"(w[16 * C + 4 * q + 3])
                         : "r"(a + q * 2048) : "memory");
        asm volatile("bar.sync %0, 128;" ::"r"(4 + wg + ((w[16 * C] | w[16 * C + 4] | w[16 * C + 8] | w[16 * C + 12]) & x & 1)) : "memory");
        if (rel) mbar_arrive_cluster<3>(rel_bar + (x & 0xF8));
    }
}

__device__ __forceinline__ int pub_slot(int g) { return g == 0 ? kSlotL + 1 : g == 1 ? kSlotW + 11 : kSlotW + 14; }
__device__ __forceinline__ int fine_group(uint32_t pos, int ci) {
    const uint32_t q = (pos & 0xFFF) + ci;
    return SHAPE ? q + q / 12 * 12 : 2 * q + (q / 6 + ((pos >> 12) & 1)) * 12;
}
constexpr int kRankF = SHAPE ? 12 : 1, kRankC = SHAPE ? 2 : 1, kSeg = SHAPE ? 16 : 32;
template <int L0, int L1>
__device__ __forceinline__ void prefetch_tile(uint32_t pos, int ci, int rank, int lane, const char* fine, const char* coarse) {
    const bool f = pos & 0x8000;
    const uint32_t row = f ? (fine_group(pos, ci) + kRankF * rank) * 32 : (((pos & 0xFFF) + kRankC * rank) * kGroup + ci) * kSeg;
    const char* p = (f ? fine : coarse) + (size_t)row * 768 + lane * 128;
    const char* q = SHAPE && !f ? p + (kGroup - 1) * kSeg * 768 : p;
#pragma unroll
    for (int l = L0; l < L1; l++) prefetch_l2((l < 3 ? p : q) + l * 4096);
}

__global__ void __cluster_dims__(2, 1, 1) __launch_bounds__(512, 1)
fpn_lateral_kernel(Scratch* const scr, const char* __restrict__ fine, const char* __restrict__ coarse,
                   const char* __restrict__ wlat, const char* __restrict__ wout,
                   const __grid_constant__ CUtensorMap tm_fine, const __grid_constant__ CUtensorMap tm_coarse,
                   const __grid_constant__ CUtensorMap tm_wlat, const __grid_constant__ CUtensorMap tm_wout,
                   const __grid_constant__ CUtensorMap tm_out, const __grid_constant__ Schedule sched) {
    extern __shared__ __align__(1024) unsigned char smem_raw[];
    if (threadIdx.x == 0) CURVE_REC(0, 0);
    uint32_t t_start;
    asm volatile("mov.u32 %0, %clock;" : "=r"(t_start));
    const uint32_t sbase = smem_u32(smem_raw);
    const uint32_t bars = sbase + kOffBar;
    const int rot = !ROT ? 0 : blockIdx.x < 4 * kPieces ? blockIdx.x & 2 : 1;
    const int npc = !ROT ? (blockIdx.x < 2 * kPieces ? 3 : 0) : blockIdx.x < 4 * kPieces ? 2 - (rot >> 1) : 0;
    const int pj = blockIdx.x >> (1 + ROT);
    auto slice = [&](int g) { return g + rot >= 3 ? g + rot - 3 : g + rot; };
    if (threadIdx.x == EARLY_T) {
        mbar_init(bars + kBarW, 1);
        if (WSPLIT) mbar_init(bars + kBarW2, 1);
        mbar_init(bars + kBarL, 1);
        asm volatile("fence.proxy.async.shared::cta;" ::: "memory");
        mbar_expect_tx(bars + kBarW, kTileBytes >> WSPLIT);
        if (WSPLIT) mbar_expect_tx(bars + kBarW2, kTileBytes >> WSPLIT);
        for (int c = 0; c < 2; c++) tma_load_2d(sbase + (kSlotW + 3 * c) * kChunk, &tm_wout, (blockIdx.x & 1) * 192 + rot * 64, c * 192, bars + (c ? kBarW2 : kBarW));
        prefetch_tm(&tm_coarse);
        if (npc) {
            mbar_expect_tx(bars + kBarL, 6 * 2048);
            tma_load_3d(sbase + kSlotL * kChunk, &tm_wlat, pj * 16, bars + kBarL);
        }
        asm volatile("fence.mbarrier_init.release.cluster;" ::: "memory");
        CURVE_REC(1, 47);
    }
    {
        constexpr int kWw = (36 * WR + 31) / 32;
        const uint32_t t = threadIdx.x - 32, b = blockIdx.x, c = (t >> 5) - kWw, l = ((b >> 1) % (64 / WR)) * (36 * WR) + t;
        const uint32_t row = ((kPos0 + kRankC * (b & 1) + ((t >> 4) & 1)) * kGroup + (b >> 1)) * kSeg + (t & 15);
        const char* p = t >= 32 * kWw ? coarse + row * 768 + c * 128 : (b & 1 ? wlat : wout) + l * 128;
        if (t < 36 * WR || c < TOPPF) prefetch_l2(p);
    }
    const int warp_id = __shfl_sync(0xffffffffu, (int)(threadIdx.x >> 5), 0);
    const int lane = threadIdx.x & 31;
    const int wg = warp_id >> 2;
    const int rank = blockIdx.x & 1;
    const int cid = blockIdx.x >> 1;
    const int pat = cid % NPAT, ci = cid / NPAT;
    const Tile* const tiles = sched.tile[pat];

    if (wg == 3) {
        asm volatile("setmaxnreg.dec.sync.aligned.u32 32;");
        const int j = warp_id & 3;
        const bool lead = elect_one();
        if (j == 3) {
            uint32_t c0;
            asm volatile("mov.u32 %0, %clock;" : "=r"(c0));
            if (lead) CURVE_REC(1, 46);
            if (lead) {
                mbar_init(bars + kBarW + 8, 1);
                mbar_init(bars + kBarW + 16, 1);
                if (WSPLIT) mbar_init(bars + kBarW2 + 8, 1), mbar_init(bars + kBarW2 + 16, 1);
                asm volatile("fence.mbarrier_init.release.cluster;" ::: "memory");
                asm volatile("fence.proxy.async.shared::cta;" ::: "memory");
            }
            __syncwarp();
            CLUSTER_ARRIVE();
            if (lead) {
                for (int g = 1; g < 3; g++) {
                    mbar_expect_tx(bars + kBarW + 8 * g, kTileBytes >> WSPLIT);
                    if (WSPLIT) mbar_expect_tx(bars + kBarW2 + 8 * g, kTileBytes >> WSPLIT);
                }
                for (int g = 2; g < 2 + W_PRE; g++) tma_load_2d(sbase + (kSlotW + 3 * g) * kChunk, &tm_wout, rank * 192 + slice(g >> 1) * 64, (g & 1) * 192, bars + (g & 1 ? kBarW2 : kBarW) + 8 * (g >> 1));
            }
            __syncwarp();
            CLUSTER_WAIT();
            if (lead) {
                int g = 2 + W_PRE;
#pragma unroll 1
                for (int c = 0; c < 6; c++) {
                    mbar_expect_tx(bars + kBarFull + 8 * c, kChunk);
                    tma_load_5d_mc(sbase + rank * 4096 + c * kChunk, &tm_coarse, c * 64, ci * (kSeg / 8), kPos0 + kRankC * rank, bars + kBarFull + 8 * c, 0);
                    CURVE_REC(1, 52 + c);
                    if ((W_MIX >> c & 1) && g < 6) {
                        tma_load_2d(sbase + (kSlotW + 3 * g) * kChunk, &tm_wout, rank * 192 + slice(g >> 1) * 64, (g & 1) * 192, bars + (g & 1 ? kBarW2 : kBarW) + 8 * (g >> 1));
                        g++;
                    }
                }
#pragma unroll 1
                for (; g < 6; g++) {
                    tma_load_2d(sbase + (kSlotW + 3 * g) * kChunk, &tm_wout, rank * 192 + slice(g >> 1) * 64, (g & 1) * 192, bars + (g & 1 ? kBarW2 : kBarW) + 8 * (g >> 1));
                    CURVE_REC(1, 47 + (g >> 1));
                }
            }
            __syncwarp();
            uint32_t cur = sched.pf_from, u = 0, pw = sched.pw_ev[0] == 1;
            const char* p = nullptr;
#pragma unroll 1
            for (uint32_t n = 0; cur < 6 * kTiles; n++) {
                uint32_t v;
                asm volatile("ld.volatile.shared.u32 %0, [%1];" : "=r"(v) : "r"(bars + kStarted) : "memory");
                uint32_t tgt = sched.tgt[v];
                if (cur < sched.t_max) {
                    uint32_t c;
                    asm volatile("mov.u32 %0, %clock;" : "=r"(c));
                    if ((int)(c - c0) >= (int)(sched.t_a + cur * sched.t_d)) tgt = max(tgt, cur + 1);
                }
#pragma unroll 1
                for (; cur < tgt; cur++) {
                    if (u == 0) {
                        const uint32_t pos = tiles[cur / 6].pos;
                        const bool f = pos & 0x8000;
                        const uint32_t row = f ? (fine_group(pos, ci) + kRankF * rank) * 32 + lane : ((pos + kRankC * rank + (lane >> 4)) * kGroup + ci) * kSeg + (lane & 15);
                        p = (f ? fine : coarse) + (size_t)row * 768;
                    }
                    prefetch_l2(p);
                    p += 128;
                    u = u == 5 ? 0 : u + 1;
                }
                if (pw < 2 && v >= sched.pw_ev[pw]) {
                    const char* q = (const char*)&g_wfrag[pw][rank][0][0][0] + lane * 128;
#pragma unroll 1
                    for (int l = ci % sched.pw_div; l < 36; l += sched.pw_div) prefetch_l2(q + l * 4096);
                    pw++;
                }
                if (n == 0x1000000) __trap();
                __nanosleep(sched.fsleep);
            }
        } else if (j == 2) {
            if (lead) CURVE_REC(1, 58);
            CLUSTER_ARRIVE();
            if (lead) {
                uint32_t v;
                asm volatile("ld.relaxed.gpu.global.u32 %0, [%1];" : "=r"(v) : "l"(&g_ready) : "memory");
            }
            if (lead) {
                CURVE_REC(1, 59);
                prefetch_tm(&tm_fine);
                prefetch_tm(&tm_out);
            }
            __syncwarp();
            CLUSTER_WAIT();
            if (lead) {
                if (npc) {
                    mbar_wait(bars + kBarPiece, 0);
                    asm volatile("fence.proxy.async.shared::cta;" ::: "memory");
                    for (int i = 0; i < 2 * npc; i++)
                        asm volatile("cp.async.bulk.global.shared::cta.bulk_group [%0], [%1], 2048;"
                                     ::"l"(&g_wfrag[i & 1][rank][slice(i >> 1)][pj][0]), "r"(sbase + pub_slot(i >> 1) * kChunk + 4096 + (i & 1) * 2048) : "memory");
                    asm volatile("cp.async.bulk.commit_group;" ::: "memory");
                    asm volatile("cp.async.bulk.wait_group.read 0;" ::: "memory");
                    for (int i = 0; i < 2 * npc; i++) {
                        uint32_t b;
                        asm("mapa.shared::cluster.u32 %0, %1, %2;" : "=r"(b) : "r"(bars + kBarEmpty + 8 * pub_slot(i >> 1)), "r"(i & 1));
                        asm volatile("mbarrier.arrive.shared::cluster.b64 _, [%0], %1;" ::"r"(b), "r"(i < 2 ? 1 : 3) : "memory");
                    }
                    asm volatile("cp.async.bulk.wait_group 0;" ::: "memory");
                    asm volatile("red.relaxed.gpu.global.add.u32 [%0], 1;" ::"l"(&g_ready) : "memory");
                    CURVE_REC(2, 61);
                }
                uint32_t v, n = 0;
                for (;;) {
                    asm volatile("ld.acquire.gpu.global.u32 %0, [%1];" : "=r"(v) : "l"(&g_ready) : "memory");
                    if (v >= (2 * kPieces << ROT)) break;
                    if (++n == 0x100000) __trap();
                    __nanosleep(50);
                }
                CURVE_REC(2, 62);
                mbar_arrive(bars + kBarReady);
                asm volatile("fence.proxy.async.global;" ::: "memory");
                mbar_arrive(bars + kBarReady2);
                if (atomicAdd(&g_done, 1) == gridDim.x - 1) {
                    g_ready = 0;
                    g_done = 0;
                }
                asm volatile("st.volatile.shared.u32 [%0], %1;" ::"r"(bars + kAllowed), "r"(rank == 0 || sched.gate1 ? sched.pace_from : kTiles) : "memory");
                if (rank == 0 || sched.gate1) {
                    const uint16_t* vt = sched.vt[pat];
                    uint32_t* const ctr = g_progress[sched.pgroup * pat];
                    const int members = sched.members, last = sched.pace_to - 1;
                    asm volatile("ld.relaxed.gpu.global.u32 %0, [%1];" : "=r"(v) : "l"(ctr) : "memory");
                    const uint32_t base = v - v % (members * 1024);
                    int counted = rank == 0 ? sched.pace_from - 1 : last, allowed = sched.pace_from;
#pragma unroll 1
                    for (n = 0; n < 0x10000 && (allowed <= last || counted < last); n++) {
                        int started;
                        asm volatile("ld.volatile.shared.u32 %0, [%1];" : "=r"(started) : "r"(bars + kStarted) : "memory");
                        started = (started + EV - 1) / EV;
                        if (counted < last && counted < started) {
                            const int upto = min(started, last);
                            asm volatile("red.relaxed.gpu.global.add.u32 [%0], %1;" ::"l"(ctr), "r"(vt[upto] - vt[counted]) : "memory");
                            counted = upto;
                        }
                        if (allowed <= last && started + 1 >= allowed) {
                            asm volatile("ld.relaxed.gpu.global.u32 %0, [%1];" : "=r"(v) : "l"(ctr) : "memory");
                            while (allowed <= last && (int)(v - base) >= sched.need[pat][allowed]) allowed++;
                            asm volatile("st.volatile.shared.u32 [%0], %1;" ::"r"(bars + kAllowed), "r"(allowed > last ? kTiles : allowed) : "memory");
                        }
                        __nanosleep(sched.psleep);
                    }
                    asm volatile("st.volatile.shared.u32 [%0], %1;" ::"r"(bars + kAllowed), "r"(kTiles) : "memory");
                    if (counted < last) asm volatile("red.relaxed.gpu.global.add.u32 [%0], %1;" ::"l"(ctr), "r"(vt[last] - vt[counted]) : "memory");
                }
            }
        } else if (j == 1) {
            if (lead) CURVE_REC(3, 51);
            if (sbase & 1023) __trap();
            if (lead) {
                asm volatile("st.shared.u32 [%0], %1;" ::"r"(bars + kStarted), "r"(0) : "memory");
                asm volatile("st.shared.u32 [%0], %1;" ::"r"(bars + kAllowed), "r"(8) : "memory");
                if (kSlots > 24) {
                    mbar_init(bars + kBarFull + 8 * 24, 1);
                    mbar_init(bars + kBarEmpty + 8 * 24, 6);
                }
                for (int i = 0; i < 3 + 6 * OBUF; i++) mbar_init(bars + kBarPiece + 8 * i, i == 0 ? max(4 * npc, 1) : i < 3 + 3 * OBUF ? 1 : 4);
                asm volatile("fence.acq_rel.cta;" ::: "memory");
                asm volatile("fence.mbarrier_init.release.cluster;" ::: "memory");
                CURVE_REC(3, 52);
            }
            __syncwarp();
            CLUSTER_ARRIVE();
            CLUSTER_WAIT();
            if (lead) {
                uint32_t k = 0;
                uint64_t pol_first, pol_normal;
                asm volatile("createpolicy.fractional.L2::evict_first.b64 %0, 1.0;" : "=l"(pol_first));
                asm volatile("createpolicy.fractional.L2::evict_normal.b64 %0, 1.0;" : "=l"(pol_normal));
#pragma unroll 1
                for (int t = 0; t < kTiles; t++) {
                    const uint32_t pos = tiles[t].pos, ef = sched.sef[t] >> (3 * rank);
                    if (!(pos & 0x8000)) continue;
                    const int row = fine_group(pos, ci);
#pragma unroll
                    for (int g = 0; g < 3; g++) {
                        mbar_wait1(bars + kBarStaged + 8 * g, k & 1);
                        if (g == 2) CURVE_REC(1, t);
                        asm volatile("fence.proxy.async.shared::cta;" ::: "memory");
                        tma_store_4d(&tm_out, sbase + kOffOut + g * kChunk, rank * 192 + slice(g) * 64, row, ef >> g & 1 ? pol_first : pol_normal);
                        asm volatile("cp.async.bulk.commit_group;" ::: "memory");
                        if (g > 0) {
                            asm volatile("cp.async.bulk.wait_group.read 1;" ::: "memory");
                            mbar_arrive(bars + kBarFree + 8 * g - 8);
                        }
                    }
                    asm volatile("cp.async.bulk.wait_group.read 0;" ::: "memory");
                    mbar_arrive(bars + kBarFree + 16);
                    CURVE_REC(3, t);
                    k++;
                }
                asm volatile("cp.async.bulk.wait_group.read 0;" ::: "memory");
            }
        } else {
            if (lead) CURVE_REC(1, 50);
            CLUSTER_ARRIVE();
            uint4 e = *(const uint4*)&tiles[1];
            asm volatile("" : "+r"(e.x), "+r"(e.y), "+r"(e.w));
            CLUSTER_WAIT();
            if (lead) CURVE_REC(1, 51);
            if (lead) {
                uint32_t dst0 = sbase + rank * 4096, bar0 = bars;
                asm volatile("" : "+r"(dst0), "+r"(bar0));
                uint32_t wk = 0, wi = 0;
                int allowed = 0;
                uint64_t pol_first, pol_normal;
                asm volatile("createpolicy.fractional.L2::evict_first.b64 %0, 1.0;" : "=l"(pol_first));
                asm volatile("createpolicy.fractional.L2::evict_normal.b64 %0, 1.0;" : "=l"(pol_normal));
#pragma unroll 1
                for (int t = EARLY ? 1 : 0; t < kTiles; t++) {
                    if (t > 1) e = *(const uint4*)&tiles[t];
                    const bool f = e.w & 0x8000;
                    const uint64_t pol = e.w & 0x4000 ? pol_first : pol_normal;
                    const CUtensorMap* tm = f ? &tm_fine : &tm_coarse;
                    const int c3 = f ? 0 : ci * (kSeg / 8), c4 = f ? fine_group(e.w, ci) + kRankF * rank : (e.w & 0xFFF) + kRankC * rank;
                    for (uint32_t n = 0; t >= allowed; n++) {
                        asm volatile("ld.volatile.shared.u32 %0, [%1];" : "=r"(allowed) : "r"(bar0 + kAllowed) : "memory");
                        if (n == 0x4000000) __trap();
                        if (n) __nanosleep(20);
                    }
                    if (t) CURVE_REC(0, t);
#pragma unroll
                    for (int c = 0; c < 6; c++) {
                        if (c % (6 / EV) == 0) asm volatile("st.volatile.shared.u32 [%0], %1;" ::"r"(bar0 + kStarted), "r"(EV * t + 1 + c / (6 / EV)) : "memory");
                        const uint32_t x = c < 4 ? e.x >> (8 * c) : e.y >> (8 * (c - 4)), s8 = x & 0xF8;
                        mbar_wait1(bar0 + kBarEmpty + s8, (x >> 1) & 1);
                        mbar_expect_tx(bar0 + kBarFull + s8, kChunk);
                        tma_load_5d_mc(dst0 + s8 * 1024, tm, c * 64, c3, c4, bar0 + kBarFull + s8, pol);
#pragma unroll 1
                        for (uint32_t n = (e.w >> (16 + 2 * c)) & 3; n; n--) {
                            if (wk == 0) mbar_wait(bar0 + kBarReady2, 0);
                            const uint32_t o = sched.worder[wk], y = (&sched.wslot[pat][wi][0][0])[o];
                            mbar_wait1(bar0 + kBarEmpty + (y & 0xF8), (y >> 1) & 1);
                            mbar_expect_tx(bar0 + kBarSwap + 8 * o, kChunk);
                            bulk_load(sbase + (y & 0xF8) * 1024, (const char*)&g_wfrag[0][rank][0][0][0] + (6 * slice(o >> 3) + (o & 7)) * kChunk, bar0 + kBarSwap + 8 * o);
                            if (++wk == 3 * NSTG) wk = 0, wi++;
                        }
                    }
                }
            }
        }
        __syncwarp();
    } else {
        if (elect_one()) {
            for (int i = 2 * warp_id; i < 2 * warp_id + 2; i++) {
                mbar_init(bars + kBarSwap + 8 * i, 1);
                if (i >= kSlots) continue;
                mbar_init(bars + kBarFull + 8 * i, 1);
                mbar_init(bars + kBarEmpty + 8 * i, 6);
            }
            asm volatile("fence.mbarrier_init.release.cluster;" ::: "memory");
        }
        __syncwarp();
        CLUSTER_ARRIVE();
        asm volatile("setmaxnreg.inc.sync.aligned.u32 160;");
        const int tid = threadIdx.x & 127;
        const int warp = tid >> 5;
        const bool rel = tid < 2;
        uint32_t rel_bar;
        asm("mapa.shared::cluster.u32 %0, %1, %2;" : "=r"(rel_bar) : "r"(bars + kBarEmpty), "r"(tid & 1));
        const uint32_t b_lo0 = ((sbase & 0x3FFFF) >> 4) | 0x10000u;
        const uint32_t frag_off = ((lane >> 4) * 8 + (lane & 7)) * 128 + (((2 * warp + ((lane >> 3) & 1)) ^ (lane & 7)) << 4);
        uint32_t st_addr = sbase + kOffOut + OBUF * wg * kChunk + frag_off, tid16 = tid * 16;
        asm volatile("" : "+r"(st_addr), "+r"(tid16));
        uint4* const wf = &g_wfrag[0][rank][slice(wg)][pj][tid];
        constexpr int kSet = 2 * 3 * 24 * 128;

        float acc[32];
        uint32_t w[96], p[16];

        auto load_w = [&]() {
        mbar_wait(bars + kBarW + 8 * wg, 0);
        if (tid == 0) CURVE_REC(3, 48 + wg);
        const uint32_t w_addr = sbase + (kSlotW + 6 * wg) * kChunk + frag_off;
#pragma unroll
        for (int s = 0; s < 24; s++) {
            if (WSPLIT && s == 12) mbar_wait(bars + kBarW2 + 8 * wg, 0);
            asm volatile("ldmatrix.sync.aligned.m8n8.x4.trans.shared.b16 {%0,%1,%2,%3}, [%4];"
                         : "=r"(w[4 * s]), "=r"(w[4 * s + 1]), "=r"(w[4 * s + 2]), "=r"(w[4 * s + 3]) : "r"(w_addr + s * 2048) : "memory");
        }
        if (wg < npc) {
            asm volatile("ldmatrix.sync.aligned.m8n8.x4.trans.shared.b16 {%0,%1,%2,%3}, [%4];"
                         : "=r"(p[0]), "=r"(p[1]), "=r"(p[2]), "=r"(p[3]) : "r"(w_addr + pj * 2048) : "memory");
            if (!PUBTMA) wf[0] = make_uint4(p[0], p[1], p[2], p[3]);
        }
        asm volatile("bar.sync %0, 128;" ::"r"(4 + wg) : "memory");
        {
            const uint32_t m = (wg == 2 ? 0x3F : 0xFFF) & ~(PUBTMA && wg && wg < npc ? 3u << 2 * (pub_slot(wg) - kSlotW - 6 * wg) : 0u);
            asm volatile("{\n.reg .pred p;\nsetp.ne.u32 p, %1, 0;\n@p mbarrier.arrive.shared::cluster.b64 _, [%0], 3;\n}\n"
                         ::"r"(rel_bar + 8 * (kSlotW + 6 * wg + (tid >> 1))), "r"(tid < 12 ? m >> tid & 1 : 0) : "memory");
        }
        if (threadIdx.x == 0) CURVE_REC(2, 59);
        if (wg < npc) {
            mbar_wait(bars + kBarL, 0);
            if (threadIdx.x == 0) CURVE_REC(3, 61);
            WG_FENCE();
            piece_steps<0>(acc, w, b_lo0 + kSlotL * 512);
            WG_COMMIT();
            WG_WAIT(0);
#pragma unroll
            for (int i = 0; i < 8; i++) {
                asm volatile("" : "+f"(acc[i]), "+f"(acc[8 + i]), "+f"(acc[16 + i]), "+f"(acc[24 + i]));
                if (CHAINS == 2) acc[i] += acc[8 + i];
                if (CHAINS == 4) acc[i] = (acc[i] + acc[8 + i]) + (acc[16 + i] + acc[24 + i]);
            }
            const uint32_t a = sbase + pub_slot(wg) * kChunk + 4096 + tid16;
            asm volatile("st.shared.v4.u32 [%0], {%1,%2,%3,%4};" ::"r"(a), "r"(p[0]), "r"(p[1]), "r"(p[2]), "r"(p[3]) : "memory");
            asm volatile("st.shared.v4.u32 [%0], {%1,%2,%3,%4};" ::"r"(a + 2048), "r"(pack_bf16(acc[0], acc[1])), "r"(pack_bf16(acc[2], acc[3])),
                         "r"(pack_bf16(acc[4], acc[5])), "r"(pack_bf16(acc[6], acc[7])) : "memory");
            __syncwarp();
            if (threadIdx.x == 0) CURVE_REC(3, 62);
            if (lane == 0) mbar_arrive(bars + kBarPiece);
        }
        if (tid < (PUBTMA && wg == 0 && npc ? 2 : 4)) mbar_arrive_cluster<1>(rel_bar + 8 * (kSlotL + (tid >> 1)));
        if (threadIdx.x == 256) CURVE_REC(2, 60);
        };
        if (tid == 0) CURVE_REC(3, 46);
        CLUSTER_WAIT();
        if (tid == 0) CURVE_REC(3, 47);
#pragma unroll
        for (int i = 0; i < 16; i++) p[i] = 0;

        const int tok_in = 1 + wg, tok_out = wg == 2 ? 1 : wg + 2;
#pragma unroll 1
        for (int t = 0; t < kTiles; t++) {
            const uint2 e = *(const uint2*)&tiles[t];
            const uint32_t fl = e.y >> 24, pe = tiles[t].p[wg];
            const uint32_t p_addr = sbase + (pe & 0xF8) * 1024 + tid16;
            if ((~fl & (F_FINE | F_P)) == 0) {
#pragma unroll
                for (int q = 0; q < 4; q++)
                    asm volatile("ld.shared.v4.u32 {%0,%1,%2,%3}, [%4];" : "=r"(p[4 * q]), "=r"(p[4 * q + 1]), "=r"(p[4 * q + 2]), "=r"(p[4 * q + 3])
                                 : "r"(p_addr + q * 2048) : "memory");
            }
            const char* swap = (const char*)&g_wfrag[1][rank][slice(wg)][0][0];
            auto init = [&](auto quarter) {
                constexpr int Q = decltype(quarter)::value;
#pragma unroll
                for (int i = 0; i < 8; i++)
                    asm volatile("shl.b32 %0, %4, 16;\nshl.b32 %1, %4, 16;\nand.b32 %2, %4, 0xffff0000;\nand.b32 %3, %4, 0xffff0000;"
                                 : "=f"(acc[4 * i]), "=f"(acc[4 * i + 1]), "=f"(acc[4 * i + 2]), "=f"(acc[4 * i + 3]) : "r"(p[4 * Q + (i & 3)]));
            };
            if (fl & F_FINE) {
                if (fl & F_Q2) {
                    if (fl & F_Q1) init(std::integral_constant<int, 3>());
                    else init(std::integral_constant<int, 2>());
                } else {
                    if (fl & F_Q1) init(std::integral_constant<int, 1>());
                    else {
                        if (DEFER >= 3) reload_w<3>(w, swap, tid16, ~fl & F_P);
                        if (DEFER >= 2) reload_w<4>(w, swap, tid16, ~fl & F_P);
                        if (DEFER >= 1) reload_w<5>(w, swap, tid16, ~fl & F_P);
                        init(std::integral_constant<int, 0>());
                    }
                }
            }
            if (fl & F_READY) {
                if (INLOOP && t == 0) load_w();
                else mbar_wait(bars + kBarReady, 0);
            }
            mbar_wait(bars + kBarFull + (e.x & 0xF8), e.x & 1);
            asm volatile("{\n.reg .pred p;\nsetp.eq.u32 p, %1, 0;\n@p bar.sync %0, 256;\n}\n" ::"r"(tok_in), "r"(pe & 1) : "memory");
            auto body = [&](auto mode) {
                constexpr int M = decltype(mode)::value;
                if (M == 1 && DEFER) asm volatile("{\n.reg .pred p;\nsetp.ne.u32 p, %0, 0;\n@p trap;\n}\n" ::"r"(w[95] & e.x & 4));
                bool rdy = issue_chunk<0>(acc, w, e, bars, b_lo0, true);
                CREC0(0);
                rdy = issue_chunk<1>(acc, w, e, bars, b_lo0, rdy);
                CREC0(1);
                if (TOKEN_K == 2) asm volatile("{\n.reg .pred p;\nsetp.eq.u32 p, %1, 0;\n@p bar.arrive %0, 256;\n}\n" ::"r"(tok_out), "r"(pe & 4) : "memory");
                retire_chunk<0, 1, M>(w, e, sched.wslot[pat], wg, sbase, rel_bar, rel, swap, tid16);
                if (M == 0 && rel && (~fl & (F_FINE | F_P)) == 0) mbar_arrive_cluster<3>(rel_bar + (pe & 0xF8));
                rdy = issue_chunk<2>(acc, w, e, bars, b_lo0, rdy);
                CREC0(2);
                if (TOKEN_K == 3) asm volatile("{\n.reg .pred p;\nsetp.eq.u32 p, %1, 0;\n@p bar.arrive %0, 256;\n}\n" ::"r"(tok_out), "r"(pe & 4) : "memory");
                retire_chunk<1, 1, M>(w, e, sched.wslot[pat], wg, sbase, rel_bar, rel, swap, tid16);
                rdy = issue_chunk<3>(acc, w, e, bars, b_lo0, rdy);
                CREC0(3);
                retire_chunk<2, 1, M>(w, e, sched.wslot[pat], wg, sbase, rel_bar, rel, swap, tid16);
                rdy = issue_chunk<4>(acc, w, e, bars, b_lo0, rdy);
                CREC0(4);
                retire_chunk<3, 1, M>(w, e, sched.wslot[pat], wg, sbase, rel_bar, rel, swap, tid16);
                rdy = issue_chunk<5>(acc, w, e, bars, b_lo0, rdy);
                CREC0(5);
                retire_chunk<4, 1, M>(w, e, sched.wslot[pat], wg, sbase, rel_bar, rel, swap, tid16);
                if (M != 1) mbar_wait(bars + (fl & F_FINE ? kBarFree + 8 * wg : kBarEmpty + (pe & 0xF8)), (pe >> 1) & 1);
                retire_chunk<5, 0, M>(w, e, sched.wslot[pat], wg, sbase, rel_bar, rel, swap, tid16);
            };
            if (!(fl & F_SWAP)) body(std::integral_constant<int, 0>());
            else if (fl & F_STAGED) body(std::integral_constant<int, 2>());
            else body(std::integral_constant<int, 1>());
            if (fl & F_FINE) {
#pragma unroll
                for (int q = 0; q < 4; q++)
                    asm volatile("stmatrix.sync.aligned.m8n8.x4.trans.shared.b16 [%0], {%1,%2,%3,%4};" ::"r"(st_addr + q * 2048),
                                 "r"(pack_bf16(acc[8 * q], acc[8 * q + 1])), "r"(pack_bf16(acc[8 * q + 2], acc[8 * q + 3])),
                                 "r"(pack_bf16(acc[8 * q + 4], acc[8 * q + 5])), "r"(pack_bf16(acc[8 * q + 6], acc[8 * q + 7])) : "memory");
                __syncwarp();
                asm volatile("{\n.reg .pred p;\nelect.sync _|p, 0xffffffff;\n@p mbarrier.arrive.shared::cta.b64 _, [%0];\n}\n" ::"r"(bars + kBarStaged + 8 * wg) : "memory");
            } else {
#pragma unroll
                for (int q = 0; q < 4; q++) {
                    p[4 * q] = pack_bf16(acc[8 * q], acc[8 * q + 2]);
                    p[4 * q + 1] = pack_bf16(acc[8 * q + 1], acc[8 * q + 3]);
                    p[4 * q + 2] = pack_bf16(acc[8 * q + 4], acc[8 * q + 6]);
                    p[4 * q + 3] = pack_bf16(acc[8 * q + 5], acc[8 * q + 7]);
                    if (fl & F_P)
                        asm volatile("st.shared.v4.u32 [%0], {%1,%2,%3,%4};" ::"r"(p_addr + q * 2048),
                                     "r"(p[4 * q]), "r"(p[4 * q + 1]), "r"(p[4 * q + 2]), "r"(p[4 * q + 3]) : "memory");
                }
            }
        }
    }
    CLUSTER_ARRIVE();
    CLUSTER_WAIT();
    if (threadIdx.x == 0) CURVE_REC(0, 63);
}

void build_schedule(int pat, Tile* tl, uint8_t (*wslot)[3][8], uint8_t* worder, const int* gs) {
    const int take[3] = {TAKE}, give[3] = {GIVE};
    const int staged = envi("STAGED", 1), wadv = envi("WADV", 4), wrel = envi("WREL", 0);
    int coarse_of[16];
    int n = 0, nsw = 0, swt[2] = {};
    int units[kTiles];
    auto unit = [&](int t) { return units[t]; };
    for (int g = 0, i0 = 0; gs[g]; i0 += gs[g], g++) {
        for (int i = 1; i <= gs[g]; i++, n++) {
            units[n] = i0 + i % gs[g];
            tl[n].pos = (units[n] * NPAT + pat) * (SHAPE ? 4 : 2);
            tl[n].flags = i < gs[g] ? F_P : F_SWAP | (g == 0 ? F_READY : 0);
            coarse_of[unit(n)] = n;
        }
        for (int i = 0; i < 4 * gs[g]; i++, n++) {
            units[n] = i0 + i / 4;
            tl[n].pos = 0x8000 + (SHAPE ? ((units[n] * NPAT + pat) * 4 + (i & 3)) * kGroup : ((units[n] * NPAT + pat) * 2 + (i & 3) / 2) * kGroup + (i & 1) * 0x1000);
            tl[n].flags = F_FINE | (i >= 4 && (i & 3) == 0 ? F_P : 0) | (i & 1 ? F_Q1 : 0) | (i & 2 ? F_Q2 : 0);
            if (i == 4 * gs[g] - 1 && gs[g + 1]) {
                tl[n].flags |= staged ? F_SWAP | F_STAGED | (nsw ? F_SW1 : 0) : F_SWAP;
                if (staged) swt[nsw++] = n;
            }
        }
    }
    int nwo = 0;
    for (int need = -4; need < 6; need++)
        for (int g = 0; g < 3; g++) {
            const int c = need - give[g];
            if (c < 6 - NSTG || c > 5) continue;
            worder[nwo++] = g * 8 + c;
            for (int i = 0; i < nsw; i++) {
                const int j = 6 * swt[i] + need + 4 - wadv;
                tl[j / 6].wcnt += 1 << (2 * (j % 6));
            }
        }
    int uses[kSlots], loads[kSlots], queue[512], head = 0, tail = 0, slot_of[6 * kTiles];
    for (int s = 0; s < kSlots; s++) uses[s] = s >= kSlotL, loads[s] = 0;
    auto take_p = [&](int t, int w, int s) { tl[t].p[w] = s * 8 + ((uses[s] + 1) & 1) * 2; uses[s]++; };
    bool taken[kSlots] = {};
    for (int w = 0; w < 3; w++)
        if (take[w] < 0 && (tl[0].flags & F_P)) take_p(0, w, kSlotW + 6 * w + 2), taken[kSlotW + 6 * w + 2] = true;
    for (int s = 0; s < kSlotL; s++) queue[tail++] = s;
    for (int s = kSlotW; s < kSlots; s++) if (!taken[s]) queue[tail++] = s;
    for (int s = kSlotL; s < kSlotW; s++) queue[tail++] = s;
    int r = 0, wk = 0, wi = 0;
    auto get_slot = [&]() {
        for (; head == tail; r++) {
            bool to_p = false;
            for (int w = 0; w < 3; w++) {
                int x = r - take[w];
                if (x >= 0 && x % 6 == 0 && x / 6 < kTiles && (tl[x / 6].flags & (F_FINE | F_P)) == F_P) take_p(x / 6, w, slot_of[r]), to_p = true;
            }
            if (!to_p) queue[tail++] = slot_of[r];
            for (int w = 0; w < 3; w++) {
                int x = r - give[w];
                if (x >= 0 && x % 6 == 0 && x / 6 < kTiles && (tl[x / 6].flags & (F_FINE | F_P)) == (F_FINE | F_P)) {
                    tl[x / 6].p[w] = tl[coarse_of[unit(x / 6)]].p[w];
                    queue[tail++] = tl[x / 6].p[w] >> 3;
                }
                x -= wrel;
                if (x >= 0 && x / 6 < kTiles && (tl[x / 6].flags & F_STAGED) && x % 6 >= 6 - NSTG) queue[tail++] = wslot[tl[x / 6].flags >> 7][w][x % 6] >> 3;
            }
        }
        return queue[head++];
    };
    for (int c = 0; c < 6 * kTiles; c++) {
        int s = get_slot();
        slot_of[c] = s;
        tl[c / 6].chunk[c % 6] = s * 8 + ((uses[s] + 1) & 1) * 2 + (loads[s] & 1);
        if (c % 6 == 0 && c) tl[c / 6 - 1].chunk[6] = tl[c / 6].chunk[0];
        uses[s]++, loads[s]++;
        for (int k = (tl[c / 6].wcnt >> (2 * (c % 6))) & 3; k; k--) {
            s = get_slot();
            (&wslot[wi][0][0])[worder[wk]] = s * 8 + ((uses[s] + 1) & 1) * 2;
            uses[s]++;
            if (++wk == 3 * NSTG) wk = 0, wi++;
        }
    }
    for (int t = 0; t < kTiles; t++)
        if ((tl[t].flags & (F_FINE | F_P)) == (F_FINE | F_P)) memcpy(tl[t].p, tl[coarse_of[unit(t)]].p, 3);
    for (int t = 0, k = 1; t < kTiles; t++)
        if (tl[t].flags & F_FINE) {
            for (int w = 0; w < 3; w++) tl[t].p[w] = (tl[t].p[w] & 0xF8) | (k & 1) * 2;
            k++;
        }
    if (INLOOP) tl[0].flags |= F_READY;
    const char* free_run = envs("NOTOK", "7100000000000000000000000000000000000000000001");
    for (int t = 0; t <= kTiles; t++)
        for (int w = 0; w < 3; w++)
            if ((free_run[t] - '0') >> w & 1) {
                tl[t].p[w] |= 1;
                if (w) tl[t].p[w - 1] |= 4;
                else if (t) tl[t - 1].p[2] |= 4;
            }
}

typedef CUresult (*EncodeFn)(CUtensorMap*, CUtensorMapDataType, cuuint32_t, void*, const cuuint64_t*, const cuuint64_t*,
                             const cuuint32_t*, const cuuint32_t*, CUtensorMapInterleave, CUtensorMapSwizzle,
                             CUtensorMapL2promotion, CUtensorMapFloatOOBfill);

void encode_2d(EncodeFn enc, CUtensorMap* tm, const void* ptr, uint64_t rows, uint32_t box_rows, CUtensorMapL2promotion promo) {
    cuuint64_t dims[2] = {(cuuint64_t)kC, rows};
    cuuint64_t strides[1] = {(cuuint64_t)kC * 2};
    cuuint32_t box[2] = {64, box_rows};
    cuuint32_t es[2] = {1, 1};
    enc(tm, CU_TENSOR_MAP_DATA_TYPE_BFLOAT16, 2, const_cast<void*>(ptr), dims, strides, box, es, CU_TENSOR_MAP_INTERLEAVE_NONE,
        CU_TENSOR_MAP_SWIZZLE_128B, promo, CU_TENSOR_MAP_FLOAT_OOB_FILL_NONE);
}

}

extern "C" void kernel_launch(void* const* d_in, const int* in_sizes, int n_in, void* d_out, int out_size) {
    (void)in_sizes; (void)n_in; (void)out_size;
    static EncodeFn enc = nullptr;
    static Schedule sched;
    static Scratch* scr;
    if (!enc) {
        cudaGetSymbolAddress((void**)&scr, g_scratch);
        void* fn = nullptr;
        cudaDriverEntryPointQueryResult qr;
        cudaGetDriverEntryPoint("cuTensorMapEncodeTiled", &fn, cudaEnableDefault, &qr);
        enc = (EncodeFn)fn;
        cudaFuncSetAttribute(fpn_lateral_kernel, cudaFuncAttributeMaxDynamicSharedMemorySize, kSmemBytes);
        if (envi("CARVE", 0)) cudaFuncSetAttribute(fpn_lateral_kernel, cudaFuncAttributePreferredSharedMemoryCarveout, envi("CARVE", 0));
        cudaLaunchConfig_t cfg = {};
        cfg.gridDim = dim3(2);
        cfg.blockDim = dim3(512);
        cfg.dynamicSmemBytes = kSmemBytes;
        cudaLaunchAttribute at;
        at.id = cudaLaunchAttributeClusterDimension;
        at.val.clusterDim.x = 2; at.val.clusterDim.y = 1; at.val.clusterDim.z = 1;
        cfg.attrs = &at; cfg.numAttrs = 1;
        int ncl = 0;
        if (cudaOccupancyMaxActiveClusters(&ncl, fpn_lateral_kernel, &cfg) != cudaSuccess) { (void)cudaGetLastError(); ncl = 0; }
        const char* pn[4] = {"PATA", "PATB", "PATC", "PATD"};
        const char* pd[4] = {"45", "45", "36", "63"};
        sched.pgroup = envi("PGROUP", 0), sched.members = sched.pgroup ? kGroup : kClusters;
        for (int q = 0; q < NPAT; q++) {
            int gs[8] = {};
            const char* sa = envs(pn[q], pd[q]);
            for (int i = 0; sa[i]; i++) gs[i] = sa[i] - '0';
            build_schedule(q, sched.tile[q], sched.wslot[q], sched.worder, gs);
        }
        {
            const uint8_t masks[7] = {0, 1, 9, 0x15, 0x1B, 0x1F, 0x3F};
            const char* sef = envs("SEF", "000000000000000000000000000000000000000000000");
            for (int t = 0; t < kTiles; t++) sched.sef[t] = masks[sef[t] - '0'];
            const char* lead = envs("LEAD", "00006cioooooiicc666666666666666666666666666666");
            auto digit = [](char ch) { return ch > '9' ? ch - 'a' + 10 : ch - '0'; };
            sched.pf_from = envi("PFFROM", 30);
            int pos = sched.pf_from;
            sched.tgt[0] = pos;
            for (int e = 0; e < EV * kTiles; e++) {
                const int t = e / EV, f = e % EV + 1;
                const int x = 6 * t + f * (6 / EV) + (digit(lead[t]) * (EV - f) + digit(lead[t + 1]) * f) / EV;
                if (pos < x) pos = x;
                if (pos > 6 * kTiles) pos = 6 * kTiles;
                sched.tgt[e + 1] = pos;
            }
            sched.pw_ev[0] = envi("PW0", 0) * EV / 6 + 1, sched.pw_ev[1] = envi("PW1", 141) * EV / 6 + 1, sched.pw_div = envi("PWDIV", 4);
            sched.t_a = envi("TA", 0), sched.t_d = envi("TD", 290), sched.t_max = envi("TMAX", 0), sched.fsleep = envi("FSLEEP", 40);
        }
        sched.gate1 = envi("GATE1", 1), sched.psleep = envi("PSLEEP", 100);
        sched.pace_from = envi("PACE_FROM", 14), sched.pace_to = envi("PACE_TO", 45);
        const char* v5 = "555555555555555555555555555555555555555555555";
        const char* vts[4] = {envs("VTA", v5), envs("VTB", v5), envs("VTC", v5), envs("VTD", v5)};
        int total = 0;
        for (int q = 0; q < NPAT; q++) {
            int sum[kTiles + 1] = {};
            for (int t = sched.pace_from; t < sched.pace_to; t++) sum[t] = sum[t - 1] + vts[q][t] - '0';
            total = sum[sched.pace_to - 1];
            for (int t = sched.pace_from; t < sched.pace_to; t++) {
                sched.vt[q][t] = sum[t] * 1024 / total;
                int slack = envi("PSTART", 160) - envi("PRAMP", 6) * (t - sched.pace_from);
                if (slack < envi("PACE", 40)) slack = envi("PACE", 40);
                if (envs("SLK", nullptr)) slack = (envs("SLK", nullptr)[t] - '0') * 16;
                sched.need[q][t] = ncl >= kClusters ? sched.vt[q][t] * sched.members - slack * 5 * 1024 / total * sched.members / 64 : -1;
            }
        }
    }
    CUtensorMap tm_fine, tm_coarse, tm_wlat, tm_wout, tm_out;
    const cuuint32_t ones[5] = {1, 1, 1, 1, 1};
    {
        cuuint64_t dims[5] = {(cuuint64_t)kC, 2, 4, 4, (cuuint64_t)kFinePix / 32};
        cuuint64_t strides[4] = {768, 2 * 768, 8 * 768, 32 * 768};
        cuuint32_t box[5] = {64, 2, 4, 4, 1};
        enc(&tm_fine, CU_TENSOR_MAP_DATA_TYPE_BFLOAT16, 5, d_in[0], dims, strides, box, ones, CU_TENSOR_MAP_INTERLEAVE_NONE,
            CU_TENSOR_MAP_SWIZZLE_128B, CU_TENSOR_MAP_L2_PROMOTION_L2_128B, CU_TENSOR_MAP_FLOAT_OOB_FILL_NONE);
    }
    {
        cuuint64_t dims[3] = {64, (cuuint64_t)kC, 6};
        cuuint64_t strides[2] = {768, 128};
        cuuint32_t box[3] = {64, 16, 6};
        cuuint32_t es[3] = {1, 1, 1};
        enc(&tm_wlat, CU_TENSOR_MAP_DATA_TYPE_BFLOAT16, 3, d_in[2], dims, strides, box, es, CU_TENSOR_MAP_INTERLEAVE_NONE,
            CU_TENSOR_MAP_SWIZZLE_128B, CU_TENSOR_MAP_L2_PROMOTION_L2_256B, CU_TENSOR_MAP_FLOAT_OOB_FILL_NONE);
    }
    encode_2d(enc, &tm_wout, d_in[3], kC, 192, CU_TENSOR_MAP_L2_PROMOTION_L2_256B);
    {
        cuuint64_t dims[4] = {(cuuint64_t)kC, 32, 2, (cuuint64_t)kFinePix / 32 - kRankF};
        cuuint64_t strides[3] = {768, kRankF * 32 * 768, 32 * 768};
        cuuint32_t box[4] = {64, 32, 2, 1};
        enc(&tm_out, CU_TENSOR_MAP_DATA_TYPE_BFLOAT16, 4, d_out, dims, strides, box, ones, CU_TENSOR_MAP_INTERLEAVE_NONE,
            CU_TENSOR_MAP_SWIZZLE_128B, CU_TENSOR_MAP_L2_PROMOTION_NONE, CU_TENSOR_MAP_FLOAT_OOB_FILL_NONE);
    }
    {
        cuuint64_t dims[5] = {(cuuint64_t)kC, 2, 4, kGroup * kSeg / 8, (cuuint64_t)kCoarsePix / (kGroup * kSeg)};
        cuuint64_t strides[4] = {4 * 768, 768, 8 * 768, kGroup * kSeg * 768};
        cuuint32_t box[5] = {64, 2, 4, kSeg / 8, 32 / kSeg};
        enc(&tm_coarse, CU_TENSOR_MAP_DATA_TYPE_BFLOAT16, 5, d_in[1], dims, strides, box, ones, CU_TENSOR_MAP_INTERLEAVE_NONE,
            CU_TENSOR_MAP_SWIZZLE_128B, CU_TENSOR_MAP_L2_PROMOTION_L2_128B, CU_TENSOR_MAP_FLOAT_OOB_FILL_NONE);
    }
    fpn_lateral_kernel<<<2 * kClusters, 512, kSmemBytes>>>(scr, (const char*)d_in[0], (const char*)d_in[1], (const char*)d_in[2], (const char*)d_in[3],
                                                          tm_fine, tm_coarse, tm_wlat, tm_wout, tm_out, sched);
}
```

```cpp
#include <cuda_runtime.h>
#include <cuda_bf16.h>
#include <cuda.h>
#include <stdint.h>
#include <string.h>
#include <type_traits>
#include <stdlib.h>

#define TOKEN_K 3
#define TAKE -2, 0, 2
#define GIVE -4, -2, 0
#define L_POS 0
#define NSTG 6
#define EV 3
#define STPOL 0
#define NO_MMA 0
#define EARLY 1
#define EARLY_T 0
#define W_PRE 0
#define TOPPF 1
#define TLBW 1
#define W_MIX 0x1E
#define WR 1
#define CHAINS 1
#define ROT 0
#define PUBTMA 1
#define DEFER 2
#define INLOOP 1
#define WSPLIT 1
#define TPF_N 0
#define TPF_A 400
#define TPF_D 300
#define NPAT 1
#define SHAPE 1
#define OBUF 1
#define LD_EF 0
#define CURVE_REC(k, i) do {} while (0)

#define CREC0(c) do {} while (0)
namespace {

constexpr int kC = 384;
constexpr int kFinePix = 384 * 384;
constexpr int kCoarsePix = 192 * 192;
constexpr int kClusters = 64;
constexpr int kTiles = 45;
#define SLOTS (28 - 3 * OBUF)
constexpr int kSlots = SLOTS;
constexpr int kChunk = 8192;
constexpr int kTileBytes = 6 * kChunk;
constexpr int kOffOut = kSlots * kChunk;
constexpr int kOffBar = kOffOut + 3 * OBUF * kChunk;
constexpr int kSmemBytes = kOffBar + 1024;
constexpr int kSlotL = kSlots + 3 * OBUF - 20;
constexpr int kSlotW = kSlots + 3 * OBUF - 18;
constexpr int kBarFull = 0, kBarEmpty = 8 * kSlots, kBarW = 16 * kSlots, kBarL = kBarW + 24;
constexpr int kBarPiece = kBarL + 8, kBarReady = kBarPiece + 8, kBarGo = kBarReady + 8, kBarFree = kBarGo + 8, kBarStaged = kBarFree + 24 * OBUF;
constexpr int kBarSwap = kBarStaged + 24 * OBUF;
constexpr int kBarReady2 = kBarSwap + 56;
constexpr int kStarted = kBarSwap + 192, kAllowed = kStarted + 4;
constexpr int kBarW2 = WSPLIT ? kStarted + 8 : kBarW;
constexpr int kPos0 = 4;
constexpr int kPieces = 24;

enum : uint32_t { F_FINE = 1, F_P = 2, F_Q1 = 4, F_SWAP = 8, F_READY = 16, F_Q2 = 32, F_STAGED = 64, F_SW1 = 128 };
struct alignas(16) Tile {
    uint8_t chunk[7];
    uint8_t flags;
    uint8_t p[3];
    uint8_t pw;
    uint16_t pos;
    uint16_t wcnt;
};
constexpr int kGroup = kClusters / NPAT;
struct Schedule {
    Tile tile[NPAT][kTiles + 1];
    uint16_t tgt[EV * kTiles + 2];
    alignas(8) uint8_t wslot[NPAT][2][3][8];
    uint8_t worder[24];
    uint8_t sef[48];
    int members, pgroup, gslack;
    int pace_from, pace_to, gate1, psleep, pf_from, pw_ev[2], pw_div, t_a, t_d, t_max, fsleep;
    int need[NPAT][kTiles + 1];
    uint16_t vt[NPAT][kTiles + 1];
};
static int envi(const char*, int d) { return d; }
static const char* envs(const char*, const char* d) { return d; }

struct Scratch {
    uint4 wfrag[2][2][3][24][128];
    uint32_t ready, pad0[31];
    uint32_t done, pad1[31];
    uint32_t progress[4][32];
};
__device__ Scratch g_scratch;
#define g_wfrag scr->wfrag
#define g_ready scr->ready
#define g_done scr->done
#define g_progress scr->progress

__device__ __forceinline__ uint32_t smem_u32(const void* p) { return (uint32_t)__cvta_generic_to_shared(p); }

__device__ __forceinline__ void mbar_init(uint32_t bar, uint32_t count) {
    asm volatile("mbarrier.init.shared::cta.b64 [%0], %1;" ::"r"(bar), "r"(count) : "memory");
}
__device__ __forceinline__ void mbar_expect_tx(uint32_t bar, uint32_t bytes) {
    asm volatile("mbarrier.arrive.expect_tx.shared::cta.b64 _, [%0], %1;" ::"r"(bar), "r"(bytes) : "memory");
}
__device__ __forceinline__ void mbar_wait(uint32_t bar, uint32_t parity) {
    asm volatile(
        "{\n"
        ".reg .pred p;\n"
        ".reg .u32 n;\n"
        "mov.u32 n, 0;\n"
        "WAIT_LOOP:\n"
        "mbarrier.try_wait.parity.shared::cta.b64 p, [%0], %1;\n"
        "@p bra WAIT_DONE;\n"
        "add.u32 n, n, 1;\n"
        "setp.lt.u32 p, n, 0x400000;\n"
        "@p bra WAIT_LOOP;\n"
        "trap;\n"
        "WAIT_DONE:\n"
        "}\n" ::"r"(bar), "r"(parity) : "memory");
}
__device__ __forceinline__ void mbar_wait1(uint32_t bar, uint32_t parity) {
    uint32_t r;
    asm volatile("{\n.reg .pred p;\nmbarrier.try_wait.parity.shared::cta.b64 p, [%1], %2;\nselp.u32 %0, 1, 0, p;\n}\n" : "=r"(r) : "r"(bar), "r"(parity) : "memory");
    if (!r) mbar_wait(bar, parity);
}
__device__ __forceinline__ bool mbar_test(uint32_t bar, uint32_t parity) {
    uint32_t r;
    asm volatile("{\n.reg .pred p;\nmbarrier.test_wait.parity.shared::cta.b64 p, [%1], %2;\nselp.u32 %0, 1, 0, p;\n}\n" : "=r"(r) : "r"(bar), "r"(parity) : "memory");
    return r != 0;
}
__device__ __forceinline__ void mbar_arrive(uint32_t bar) {
    asm volatile("mbarrier.arrive.shared::cta.b64 _, [%0];" ::"r"(bar) : "memory");
}
template <int N>
__device__ __forceinline__ void mbar_arrive_cluster(uint32_t bar) {
    if (N == 1) asm volatile("mbarrier.arrive.shared::cluster.b64 _, [%0];" ::"r"(bar) : "memory");
    else asm volatile("mbarrier.arrive.shared::cluster.b64 _, [%0], %1;" ::"r"(bar), "n"(N) : "memory");
}
__device__ __forceinline__ void bulk_load(uint32_t dst, const void* src, uint32_t bar) {
    asm volatile("cp.async.bulk.shared::cluster.global.mbarrier::complete_tx::bytes [%0], [%1], %2, [%3];"
                 ::"r"(dst), "l"(src), "n"(kChunk), "r"(bar) : "memory");
}
__device__ __forceinline__ void tma_load_2d(uint32_t dst, const CUtensorMap* tm, int c0, int c1, uint32_t bar) {
    asm volatile("cp.async.bulk.tensor.2d.shared::cluster.global.mbarrier::complete_tx::bytes [%0], [%1, {%2, %3}], [%4];"
                 ::"r"(dst), "l"(tm), "r"(c0), "r"(c1), "r"(bar) : "memory");
}
__device__ __forceinline__ void tma_load_3d(uint32_t dst, const CUtensorMap* tm, int c1, uint32_t bar) {
    asm volatile("cp.async.bulk.tensor.3d.shared::cluster.global.mbarrier::complete_tx::bytes [%0], [%1, {%2, %3, %2}], [%4];"
                 ::"r"(dst), "l"(tm), "r"(0), "r"(c1), "r"(bar) : "memory");
}
__device__ __forceinline__ void tma_load_5d_mc(uint32_t dst, const CUtensorMap* tm, int c0, int c3, int c4, uint32_t bar, uint64_t pol) {
    asm volatile("cp.async.bulk.tensor.5d.shared::cluster.global.mbarrier::complete_tx::bytes.multicast::cluster [%0], [%1, {%2, %3, %3, %4, %5}], [%6], %7;"
                 ::"r"(dst), "l"(tm), "r"(c0), "r"(0), "r"(c3), "r"(c4), "r"(bar), "h"((uint16_t)3) : "memory");
}
__device__ __forceinline__ void tma_store_4d(const CUtensorMap* tm, uint32_t src, int c0, int c3, uint64_t pol) {
    if (STPOL) asm volatile("cp.async.bulk.tensor.4d.global.shared::cta.bulk_group.L2::cache_hint [%0, {%2, %3, %3, %4}], [%1], %5;"
                 ::"l"(tm), "r"(src), "r"(c0), "r"(0), "r"(c3), "l"(pol) : "memory");
    else asm volatile("cp.async.bulk.tensor.4d.global.shared::cta.bulk_group [%0, {%2, %3, %3, %4}], [%1];"
                 ::"l"(tm), "r"(src), "r"(c0), "r"(0), "r"(c3) : "memory");
}
__device__ __forceinline__ void prefetch_l2(const void* p) {
    asm volatile("prefetch.global.L2 [%0];" ::"l"(p) : "memory");
}
__device__ __forceinline__ void prefetch_tm(const CUtensorMap* tm) {
    asm volatile("prefetch.tensormap [%0];" ::"l"(tm) : "memory");
}
__device__ __forceinline__ uint32_t now_ns() {
    uint32_t t;
    asm volatile("mov.u32 %0, %globaltimer_lo;" : "=r"(t));
    return t;
}
__device__ __forceinline__ bool elect_one() {
    uint32_t p;
    asm volatile("{\n.reg .pred p;\nelect.sync _|p, 0xffffffff;\nselp.u32 %0, 1, 0, p;\n}\n" : "=r"(p));
    return p != 0;
}
#define CLUSTER_ARRIVE() asm volatile("barrier.cluster.arrive.relaxed.aligned;" ::: "memory")
#define CLUSTER_WAIT() asm volatile("barrier.cluster.wait.acquire.aligned;" ::: "memory")

#define WG_FENCE() asm volatile("wgmma.fence.sync.aligned;" ::: "memory")
#define WG_COMMIT() asm volatile("wgmma.commit_group.sync.aligned;" ::: "memory")
#define WG_WAIT(n) asm volatile("wgmma.wait_group.sync.aligned %0;" ::"n"(n) : "memory")

#define ACC32 "{%0,%1,%2,%3,%4,%5,%6,%7,%8,%9,%10,%11,%12,%13,%14,%15,%16,%17,%18,%19,%20,%21,%22,%23,%24,%25,%26,%27,%28,%29,%30,%31}"
#define ACC8(b) "+f"(d[b]), "+f"(d[b + 1]), "+f"(d[b + 2]), "+f"(d[b + 3]), "+f"(d[b + 4]), "+f"(d[b + 5]), "+f"(d[b + 6]), "+f"(d[b + 7])

#define DESC_HI "0x40000040"
template <int BOFF>
__device__ __forceinline__ void wgmma_rs(float (&d)[32], const uint32_t* a, uint32_t b_lo) {
    asm volatile("{\n.reg .b32 tb;\n.reg .b64 db;\nadd.u32 tb, %36, %37;\nmov.b64 db, {tb, " DESC_HI "};\n"
                 "wgmma.mma_async.sync.aligned.m64n64k16.f32.bf16.bf16 " ACC32 ", {%32,%33,%34,%35}, db, 1, 1, 1, 0;\n}\n"
                 : ACC8(0), ACC8(8), ACC8(16), ACC8(24)
                 : "r"(a[0]), "r"(a[1]), "r"(a[2]), "r"(a[3]), "r"(b_lo), "n"(BOFF));
}
__device__ __forceinline__ void wgmma_rs_first(float (&d)[32], const uint32_t* a, uint32_t b_lo, uint32_t accum) {
    asm volatile("{\n.reg .pred p;\n.reg .b64 db;\nsetp.ne.u32 p, %37, 0;\nmov.b64 db, {%36, " DESC_HI "};\n"
                 "wgmma.mma_async.sync.aligned.m64n64k16.f32.bf16.bf16 " ACC32 ", {%32,%33,%34,%35}, db, p, 1, 1, 0;\n}\n"
                 : ACC8(0), ACC8(8), ACC8(16), ACC8(24)
                 : "r"(a[0]), "r"(a[1]), "r"(a[2]), "r"(a[3]), "r"(b_lo), "r"(accum));
}
template <int ACCUM, int BOFF, int D>
__device__ __forceinline__ void wgmma_rs16(float (&d)[32], const uint32_t* a, uint32_t b_lo) {
    asm volatile("{\n.reg .b32 tb;\n.reg .b64 db;\nadd.u32 tb, %12, %13;\nmov.b64 db, {tb, " DESC_HI "};\n"
                 "wgmma.mma_async.sync.aligned.m64n16k16.f32.bf16.bf16 {%0,%1,%2,%3,%4,%5,%6,%7}, {%8,%9,%10,%11}, db, %14, 1, 1, 0;\n}\n"
                 : ACC8(D)
                 : "r"(a[0]), "r"(a[1]), "r"(a[2]), "r"(a[3]), "r"(b_lo), "n"(BOFF), "n"(ACCUM));
}
template <int S>
__device__ __forceinline__ void piece_steps(float (&d)[32], const uint32_t (&w)[96], uint32_t b_lo) {
    if constexpr (S < 24) {
        wgmma_rs16<(S >= CHAINS), (S >> 2) * 128 + (S & 3) * 2, S % CHAINS * 8>(d, &w[4 * S], b_lo);
        piece_steps<S + 1>(d, w, b_lo);
    }
}

__device__ __forceinline__ uint32_t pack_bf16(float lo, float hi) {
    uint32_t r;
    asm("cvt.rn.bf16x2.f32 %0, %1, %2;" : "=r"(r) : "f"(hi), "f"(lo));
    return r;
}

template <int C>
__device__ __forceinline__ void reload_w(uint32_t (&w)[96], const char* base, uint32_t tid16, uint32_t on) {
#define W4(i) "+r"(w[16 * C + 4 * i]), "+r"(w[16 * C + 4 * i + 1]), "+r"(w[16 * C + 4 * i + 2]), "+r"(w[16 * C + 4 * i + 3])
    asm volatile("{\n.reg .pred p;\n.reg .b64 a;\nsetp.ne.u32 p, %19, 0;\ncvt.u64.u32 a, %18;\nadd.u64 a, a, %16;\n"
                 "@p ld.global.cg.v4.u32 {%0,%1,%2,%3}, [a + %17];\n"
                 "@p ld.global.cg.v4.u32 {%4,%5,%6,%7}, [a + %17 + 2048];\n"
                 "@p ld.global.cg.v4.u32 {%8,%9,%10,%11}, [a + %17 + 4096];\n"
                 "@p ld.global.cg.v4.u32 {%12,%13,%14,%15}, [a + %17 + 6144];\n}\n"
                 : W4(0), W4(1), W4(2), W4(3)
                 : "l"(base), "n"(C * 8192), "r"(tid16), "r"(on) : "memory");
#undef W4
}

template <int C>
__device__ __forceinline__ uint32_t entry(uint2 e) { return C < 4 ? e.x >> (8 * C) : e.y >> (8 * (C - 4)); }

template <int C>
__device__ __forceinline__ bool issue_chunk(float (&acc)[32], const uint32_t (&w)[96], uint2 e, uint32_t bars, uint32_t b_lo0, bool ready) {
    if (!ready) mbar_wait(bars + kBarFull + (entry<C>(e) & 0xF8), entry<C>(e) & 1);
    const bool next = C < 5 && mbar_test(bars + kBarFull + (entry<C + 1>(e) & 0xF8), entry<C + 1>(e) & 1);
    const uint32_t b_lo = b_lo0 + (entry<C>(e) & 0xF8) * 64;
    if (!NO_MMA) {
        WG_FENCE();
        if (C == 0) wgmma_rs_first(acc, &w[0], b_lo, e.y & (F_FINE << 24));
        else wgmma_rs<0>(acc, &w[16 * C], b_lo);
        wgmma_rs<2>(acc, &w[16 * C + 4], b_lo);
        wgmma_rs<4>(acc, &w[16 * C + 8], b_lo);
        wgmma_rs<6>(acc, &w[16 * C + 12], b_lo);
        WG_COMMIT();
    }
    return next;
}
template <int C, int PENDING, int MODE>
__device__ __forceinline__ void retire_chunk(uint32_t (&w)[96], uint2 e, const uint8_t (*ws)[3][8], int wg, uint32_t sbase, uint32_t rel_bar, bool rel, const char* swap, uint32_t tid16) {
    if (!NO_MMA) WG_WAIT(PENDING);
    if (rel) mbar_arrive_cluster<1>(rel_bar + (entry<C>(e) & 0xF8));
    if (MODE == 1 && C < 6 - DEFER) reload_w<C>(w, swap, tid16, 1);
    if (MODE == 2 && C >= 6 - NSTG) {
        const uint32_t x = ws[e.y >> 31][wg][C];
        mbar_wait(sbase + kOffBar + kBarSwap + 64 * wg + 8 * C, e.y >> 31);
        const uint32_t a = sbase + (x & 0xF8) * 1024 + tid16;
#pragma unroll
        for (int q = 0; q < 4; q++)
            asm volatile("ld.shared.v4.u32 {%0,%1,%2,%3}, [%4];" : "=r"(w[16 * C + 4 * q]), "=r"(w[16 * C + 4 * q + 1]), "=r"(w[16 * C + 4 * q + 2]), "=r"(w[16 * C + 4 * q + 3])
                         : "r"(a + q * 2048) : "memory");
        asm volatile("bar.sync %0, 128;" ::"r"(4 + wg + ((w[16 * C] | w[16 * C + 4] | w[16 * C + 8] | w[16 * C + 12]) & x & 1)) : "memory");
        if (rel) mbar_arrive_cluster<3>(rel_bar + (x & 0xF8));
    }
}

__device__ __forceinline__ int pub_slot(int g) { return g == 0 ? kSlotL + 1 : g == 1 ? kSlotW + 11 : kSlotW + 14; }
__device__ __forceinline__ int fine_group(uint32_t pos, int ci) {
    const uint32_t q = (pos & 0xFFF) + ci;
    return SHAPE ? q + q / 12 * 12 : 2 * q + (q / 6 + ((pos >> 12) & 1)) * 12;
}
constexpr int kRankF = SHAPE ? 12 : 1, kRankC = SHAPE ? 2 : 1, kSeg = SHAPE ? 16 : 32;
template <int L0, int L1>
__device__ __forceinline__ void prefetch_tile(uint32_t pos, int ci, int rank, int lane, const char* fine, const char* coarse) {
    const bool f = pos & 0x8000;
    const uint32_t row = f ? (fine_group(pos, ci) + kRankF * rank) * 32 : (((pos & 0xFFF) + kRankC * rank) * kGroup + ci) * kSeg;
    const char* p = (f ? fine : coarse) + (size_t)row * 768 + lane * 128;
    const char* q = SHAPE && !f ? p + (kGroup - 1) * kSeg * 768 : p;
#pragma unroll
    for (int l = L0; l < L1; l++) prefetch_l2((l < 3 ? p : q) + l * 4096);
}

__global__ void __cluster_dims__(2, 1, 1) __launch_bounds__(512, 1)
fpn_lateral_kernel(Scratch* const scr, const char* __restrict__ fine, const char* __restrict__ coarse,
                   const char* __restrict__ wlat, const char* __restrict__ wout,
                   const __grid_constant__ CUtensorMap tm_fine, const __grid_constant__ CUtensorMap tm_coarse,
                   const __grid_constant__ CUtensorMap tm_wlat, const __grid_constant__ CUtensorMap tm_wout,
                   const __grid_constant__ CUtensorMap tm_out, const __grid_constant__ Schedule sched) {
    extern __shared__ __align__(1024) unsigned char smem_raw[];
    if (threadIdx.x == 0) CURVE_REC(0, 0);
    uint32_t t_start;
    asm volatile("mov.u32 %0, %clock;" : "=r"(t_start));
    const uint32_t sbase = smem_u32(smem_raw);
    const uint32_t bars = sbase + kOffBar;
    const int rot = !ROT ? 0 : blockIdx.x < 4 * kPieces ? blockIdx.x & 2 : 1;
    const int npc = !ROT ? (blockIdx.x < 2 * kPieces ? 3 : 0) : blockIdx.x < 4 * kPieces ? 2 - (rot >> 1) : 0;
    const int pj = blockIdx.x >> (1 + ROT);
    auto slice = [&](int g) { return g + rot >= 3 ? g + rot - 3 : g + rot; };
    if (threadIdx.x == EARLY_T) {
        mbar_init(bars + kBarW, 1);
        if (WSPLIT) mbar_init(bars + kBarW2, 1);
        mbar_init(bars + kBarL, 1);
        asm volatile("fence.proxy.async.shared::cta;" ::: "memory");
        mbar_expect_tx(bars + kBarW, kTileBytes >> WSPLIT);
        if (WSPLIT) mbar_expect_tx(bars + kBarW2, kTileBytes >> WSPLIT);
        for (int c = 0; c < 2; c++) tma_load_2d(sbase + (kSlotW + 3 * c) * kChunk, &tm_wout, (blockIdx.x & 1) * 192 + rot * 64, c * 192, bars + (c ? kBarW2 : kBarW));
        prefetch_tm(&tm_coarse);
        if (npc) {
            mbar_expect_tx(bars + kBarL, 6 * 2048);
            tma_load_3d(sbase + kSlotL * kChunk, &tm_wlat, pj * 16, bars + kBarL);
        }
        asm volatile("fence.mbarrier_init.release.cluster;" ::: "memory");
        CURVE_REC(1, 47);
    }
    {
        constexpr int kWw = (36 * WR + 31) / 32;
        const uint32_t t = threadIdx.x - 32, b = blockIdx.x, c = (t >> 5) - kWw, l = ((b >> 1) % (64 / WR)) * (36 * WR) + t;
        const uint32_t row = ((kPos0 + kRankC * (b & 1) + ((t >> 4) & 1)) * kGroup + (b >> 1)) * kSeg + (t & 15);
        const char* p = t >= 32 * kWw ? coarse + row * 768 + c * 128 : (b & 1 ? wlat : wout) + l * 128;
        if (t < 36 * WR || c < TOPPF) prefetch_l2(p);
    }
    const int warp_id = __shfl_sync(0xffffffffu, (int)(threadIdx.x >> 5), 0);
    const int lane = threadIdx.x & 31;
    const int wg = warp_id >> 2;
    const int rank = blockIdx.x & 1;
    const int cid = blockIdx.x >> 1;
    const int pat = cid % NPAT, ci = cid / NPAT;
    const Tile* const tiles = sched.tile[pat];

    if (wg == 3) {
        asm volatile("setmaxnreg.dec.sync.aligned.u32 32;");
        const int j = warp_id & 3;
        const bool lead = elect_one();
        if (j == 3) {
            uint32_t c0;
            asm volatile("mov.u32 %0, %clock;" : "=r"(c0));
            if (lead) CURVE_REC(1, 46);
            if (lead) {
                mbar_init(bars + kBarW + 8, 1);
                mbar_init(bars + kBarW + 16, 1);
                if (WSPLIT) mbar_init(bars + kBarW2 + 8, 1), mbar_init(bars + kBarW2 + 16, 1);
                asm volatile("fence.mbarrier_init.release.cluster;" ::: "memory");
                asm volatile("fence.proxy.async.shared::cta;" ::: "memory");
            }
            __syncwarp();
            CLUSTER_ARRIVE();
            if (lead) {
                for (int g = 1; g < 3; g++) {
                    mbar_expect_tx(bars + kBarW + 8 * g, kTileBytes >> WSPLIT);
                    if (WSPLIT) mbar_expect_tx(bars + kBarW2 + 8 * g, kTileBytes >> WSPLIT);
                }
                for (int g = 2; g < 2 + W_PRE; g++) tma_load_2d(sbase + (kSlotW + 3 * g) * kChunk, &tm_wout, rank * 192 + slice(g >> 1) * 64, (g & 1) * 192, bars + (g & 1 ? kBarW2 : kBarW) + 8 * (g >> 1));
            }
            __syncwarp();
            CLUSTER_WAIT();
            if (lead) {
                int g = 2 + W_PRE;
#pragma unroll 1
                for (int c = 0; c < 6; c++) {
                    mbar_expect_tx(bars + kBarFull + 8 * c, kChunk);
                    tma_load_5d_mc(sbase + rank * 4096 + c * kChunk, &tm_coarse, c * 64, ci * (kSeg / 8), kPos0 + kRankC * rank, bars + kBarFull + 8 * c, 0);
                    CURVE_REC(1, 52 + c);
                    if ((W_MIX >> c & 1) && g < 6) {
                        tma_load_2d(sbase + (kSlotW + 3 * g) * kChunk, &tm_wout, rank * 192 + slice(g >> 1) * 64, (g & 1) * 192, bars + (g & 1 ? kBarW2 : kBarW) + 8 * (g >> 1));
                        g++;
                    }
                }
#pragma unroll 1
                for (; g < 6; g++) {
                    tma_load_2d(sbase + (kSlotW + 3 * g) * kChunk, &tm_wout, rank * 192 + slice(g >> 1) * 64, (g & 1) * 192, bars + (g & 1 ? kBarW2 : kBarW) + 8 * (g >> 1));
                    CURVE_REC(1, 47 + (g >> 1));
                }
            }
            __syncwarp();
            uint32_t cur = sched.pf_from, u = 0, pw = sched.pw_ev[0] == 1;
            const char* p = nullptr;
#pragma unroll 1
            for (uint32_t n = 0; cur < 6 * kTiles; n++) {
                uint32_t v;
                asm volatile("ld.volatile.shared.u32 %0, [%1];" : "=r"(v) : "r"(bars + kStarted) : "memory");
                uint32_t tgt = sched.tgt[v];
                if (cur < sched.t_max) {
                    uint32_t c;
                    asm volatile("mov.u32 %0, %clock;" : "=r"(c));
                    if ((int)(c - c0) >= (int)(sched.t_a + cur * sched.t_d)) tgt = max(tgt, cur + 1);
                }
#pragma unroll 1
                for (; cur < tgt; cur++) {
                    if (u == 0) {
                        const uint32_t pos = tiles[cur / 6].pos;
                        const bool f = pos & 0x8000;
                        const uint32_t row = f ? (fine_group(pos, ci) + kRankF * rank) * 32 + lane : (((pos & 0xFFF) + kRankC * rank + (lane >> 4)) * kGroup + ci) * kSeg + (lane & 15);
                        p = (f ? fine : coarse) + (size_t)row * 768;
                    }
                    prefetch_l2(p);
                    p += 128;
                    u = u == 5 ? 0 : u + 1;
                }
                if (pw < 2 && v >= sched.pw_ev[pw]) {
                    const char* q = (const char*)&g_wfrag[pw][rank][0][0][0] + lane * 128;
#pragma unroll 1
                    for (int l = ci % sched.pw_div; l < 36; l += sched.pw_div) prefetch_l2(q + l * 4096);
                    pw++;
                }
                if (n == 0x1000000) __trap();
                __nanosleep(sched.fsleep);
            }
        } else if (j == 2) {
            if (lead) CURVE_REC(1, 58);
            CLUSTER_ARRIVE();
            if (lead) {
                uint32_t v;
                asm volatile("ld.relaxed.gpu.global.u32 %0, [%1];" : "=r"(v) : "l"(&g_ready) : "memory");
            }
            if (lead) {
                CURVE_REC(1, 59);
                prefetch_tm(&tm_fine);
                prefetch_tm(&tm_out);
            }
            __syncwarp();
            CLUSTER_WAIT();
            if (lead) {
                if (npc) {
                    mbar_wait(bars + kBarPiece, 0);
                    asm volatile("fence.proxy.async.shared::cta;" ::: "memory");
                    for (int i = 0; i < 2 * npc; i++)
                        asm volatile("cp.async.bulk.global.shared::cta.bulk_group [%0], [%1], 2048;"
                                     ::"l"(&g_wfrag[i & 1][rank][slice(i >> 1)][pj][0]), "r"(sbase + pub_slot(i >> 1) * kChunk + 4096 + (i & 1) * 2048) : "memory");
                    asm volatile("cp.async.bulk.commit_group;" ::: "memory");
                    asm volatile("cp.async.bulk.wait_group.read 0;" ::: "memory");
                    for (int i = 0; i < 2 * npc; i++) {
                        uint32_t b;
                        asm("mapa.shared::cluster.u32 %0, %1, %2;" : "=r"(b) : "r"(bars + kBarEmpty + 8 * pub_slot(i >> 1)), "r"(i & 1));
                        asm volatile("mbarrier.arrive.shared::cluster.b64 _, [%0], %1;" ::"r"(b), "r"(i < 2 ? 1 : 3) : "memory");
                    }
                    asm volatile("cp.async.bulk.wait_group 0;" ::: "memory");
                    asm volatile("red.relaxed.gpu.global.add.u32 [%0], 1;" ::"l"(&g_ready) : "memory");
                    CURVE_REC(2, 61);
                }
                uint32_t v, n = 0;
                for (;;) {
                    asm volatile("ld.acquire.gpu.global.u32 %0, [%1];" : "=r"(v) : "l"(&g_ready) : "memory");
                    if (v >= (2 * kPieces << ROT)) break;
                    if (++n == 0x100000) __trap();
                    __nanosleep(50);
                }
                CURVE_REC(2, 62);
                mbar_arrive(bars + kBarReady);
                asm volatile("fence.proxy.async.global;" ::: "memory");
                mbar_arrive(bars + kBarReady2);
                if (atomicAdd(&g_done, 1) == gridDim.x - 1) {
                    g_ready = 0;
                    g_done = 0;
                }
                asm volatile("st.volatile.shared.u32 [%0], %1;" ::"r"(bars + kAllowed), "r"(rank == 0 || sched.gate1 ? sched.pace_from : kTiles) : "memory");
                if (rank == 0 || sched.gate1) {
                    const uint16_t* vt = sched.vt[pat];
                    uint32_t* const ctr = g_progress[sched.pgroup * pat];
                    const int members = sched.members, last = sched.pace_to - 1;
                    asm volatile("ld.relaxed.gpu.global.u32 %0, [%1];" : "=r"(v) : "l"(ctr) : "memory");
                    const uint32_t base = v - v % (members * 1024);
                    int counted = rank == 0 ? sched.pace_from - 1 : last, allowed = sched.pace_from;
#pragma unroll 1
                    for (n = 0; n < 0x10000 && (allowed <= last || counted < last); n++) {
                        int started;
                        asm volatile("ld.volatile.shared.u32 %0, [%1];" : "=r"(started) : "r"(bars + kStarted) : "memory");
                        started = (started + EV - 1) / EV;
                        if (counted < last && counted < started) {
                            const int upto = min(started, last);
                            asm volatile("red.relaxed.gpu.global.add.u32 [%0], %1;" ::"l"(ctr), "r"(vt[upto] - vt[counted]) : "memory");
                            counted = upto;
                        }
                        if (allowed <= last && started + 1 >= allowed) {
                            asm volatile("ld.relaxed.gpu.global.u32 %0, [%1];" : "=r"(v) : "l"(ctr) : "memory");
                            while (allowed <= last && (int)(v - base) >= sched.need[pat][allowed]) allowed++;
                            asm volatile("st.volatile.shared.u32 [%0], %1;" ::"r"(bars + kAllowed), "r"(allowed > last ? kTiles : allowed) : "memory");
                        }
                        __nanosleep(sched.psleep);
                    }
                    asm volatile("st.volatile.shared.u32 [%0], %1;" ::"r"(bars + kAllowed), "r"(kTiles) : "memory");
                    if (counted < last) asm volatile("red.relaxed.gpu.global.add.u32 [%0], %1;" ::"l"(ctr), "r"(vt[last] - vt[counted]) : "memory");
                }
            }
        } else if (j == 1) {
            if (lead) CURVE_REC(3, 51);
            if (sbase & 1023) __trap();
            if (lead) {
                asm volatile("st.shared.u32 [%0], %1;" ::"r"(bars + kStarted), "r"(0) : "memory");
                asm volatile("st.shared.u32 [%0], %1;" ::"r"(bars + kAllowed), "r"(8) : "memory");
                if (kSlots > 24) {
                    mbar_init(bars + kBarFull + 8 * 24, 1);
                    mbar_init(bars + kBarEmpty + 8 * 24, 6);
                }
                for (int i = 0; i < 3 + 6 * OBUF; i++) mbar_init(bars + kBarPiece + 8 * i, i == 0 ? max(4 * npc, 1) : i < 3 + 3 * OBUF ? 1 : 4);
                asm volatile("fence.acq_rel.cta;" ::: "memory");
                asm volatile("fence.mbarrier_init.release.cluster;" ::: "memory");
                CURVE_REC(3, 52);
            }
            __syncwarp();
            CLUSTER_ARRIVE();
            CLUSTER_WAIT();
            if (lead) {
                uint32_t k = 0, last[3] = {t_start, t_start, t_start};
                uint64_t pol_first, pol_normal;
                asm volatile("createpolicy.fractional.L2::evict_first.b64 %0, 1.0;" : "=l"(pol_first));
                asm volatile("createpolicy.fractional.L2::evict_normal.b64 %0, 1.0;" : "=l"(pol_normal));
#pragma unroll 1
                for (int t = 0; t < kTiles; t++) {
                    const uint32_t pos = tiles[t].pos, ef = sched.sef[t] & 64 ? 7 : 0, gap = (sched.sef[t] & 63) * 128;
                    if (!(pos & 0x8000)) continue;
                    const int row = fine_group(pos, ci);
#pragma unroll
                    for (int g = 0; g < 3; g++) {
                        mbar_wait1(bars + kBarStaged + 8 * g, k & 1);
                        if (g == 2) CURVE_REC(1, t);
                        {
                            uint32_t c;
                            last[g] += gap;
#pragma unroll 1
                            for (int n = 0; n < 4096; n++) {
                                asm volatile("mov.u32 %0, %clock;" : "=r"(c));
                                if ((int)(c - last[g]) >= 0) break;
                                __nanosleep(20);
                            }
                            if ((int)(c - last[g]) > sched.gslack) last[g] = c - sched.gslack;
                        }
                        asm volatile("fence.proxy.async.shared::cta;" ::: "memory");
                        tma_store_4d(&tm_out, sbase + kOffOut + g * kChunk, rank * 192 + slice(g) * 64, row, ef >> g & 1 ? pol_first : pol_normal);
                        asm volatile("cp.async.bulk.commit_group;" ::: "memory");
                        if (g > 0) {
                            asm volatile("cp.async.bulk.wait_group.read 1;" ::: "memory");
                            mbar_arrive(bars + kBarFree + 8 * g - 8);
                        }
                    }
                    asm volatile("cp.async.bulk.wait_group.read 0;" ::: "memory");
                    mbar_arrive(bars + kBarFree + 16);
                    CURVE_REC(3, t);
                    k++;
                }
                asm volatile("cp.async.bulk.wait_group.read 0;" ::: "memory");
            }
        } else {
            if (lead) CURVE_REC(1, 50);
            CLUSTER_ARRIVE();
            uint4 e = *(const uint4*)&tiles[1];
            asm volatile("" : "+r"(e.x), "+r"(e.y), "+r"(e.w));
            CLUSTER_WAIT();
            if (lead) CURVE_REC(1, 51);
            if (lead) {
                uint32_t dst0 = sbase + rank * 4096, bar0 = bars;
                asm volatile("" : "+r"(dst0), "+r"(bar0));
                uint32_t wk = 0, wi = 0;
                int allowed = 0;
                uint64_t pol_first, pol_normal;
                asm volatile("createpolicy.fractional.L2::evict_first.b64 %0, 1.0;" : "=l"(pol_first));
                asm volatile("createpolicy.fractional.L2::evict_normal.b64 %0, 1.0;" : "=l"(pol_normal));
#pragma unroll 1
                for (int t = EARLY ? 1 : 0; t < kTiles; t++) {
                    if (t > 1) e = *(const uint4*)&tiles[t];
                    const bool f = e.w & 0x8000;
                    const uint64_t pol = e.w & 0x4000 ? pol_first : pol_normal;
                    const CUtensorMap* tm = f ? &tm_fine : &tm_coarse;
                    const int c3 = f ? 0 : ci * (kSeg / 8), c4 = f ? fine_group(e.w, ci) + kRankF * rank : (e.w & 0xFFF) + kRankC * rank;
                    for (uint32_t n = 0; t >= allowed; n++) {
                        asm volatile("ld.volatile.shared.u32 %0, [%1];" : "=r"(allowed) : "r"(bar0 + kAllowed) : "memory");
                        if (n == 0x4000000) __trap();
                        if (n) __nanosleep(20);
                    }
                    if (t) CURVE_REC(0, t);
#pragma unroll
                    for (int c = 0; c < 6; c++) {
                        if (c % (6 / EV) == 0) asm volatile("st.volatile.shared.u32 [%0], %1;" ::"r"(bar0 + kStarted), "r"(EV * t + 1 + c / (6 / EV)) : "memory");
                        const uint32_t x = c < 4 ? e.x >> (8 * c) : e.y >> (8 * (c - 4)), s8 = x & 0xF8;
                        mbar_wait1(bar0 + kBarEmpty + s8, (x >> 1) & 1);
                        mbar_expect_tx(bar0 + kBarFull + s8, kChunk);
                        tma_load_5d_mc(dst0 + s8 * 1024, tm, c * 64, c3, c4, bar0 + kBarFull + s8, pol);
#pragma unroll 1
                        for (uint32_t n = (e.w >> (16 + 2 * c)) & 3; n; n--) {
                            if (wk == 0) mbar_wait(bar0 + kBarReady2, 0);
                            const uint32_t o = sched.worder[wk], y = (&sched.wslot[pat][wi][0][0])[o];
                            mbar_wait1(bar0 + kBarEmpty + (y & 0xF8), (y >> 1) & 1);
                            mbar_expect_tx(bar0 + kBarSwap + 8 * o, kChunk);
                            bulk_load(sbase + (y & 0xF8) * 1024, (const char*)&g_wfrag[0][rank][0][0][0] + (6 * slice(o >> 3) + (o & 7)) * kChunk, bar0 + kBarSwap + 8 * o);
                            if (++wk == 3 * NSTG) wk = 0, wi++;
                        }
                    }
                }
            }
        }
        __syncwarp();
    } else {
        if (elect_one()) {
            for (int i = 2 * warp_id; i < 2 * warp_id + 2; i++) {
                mbar_init(bars + kBarSwap + 8 * i, 1);
                if (i >= kSlots) continue;
                mbar_init(bars + kBarFull + 8 * i, 1);
                mbar_init(bars + kBarEmpty + 8 * i, 6);
            }
            asm volatile("fence.mbarrier_init.release.cluster;" ::: "memory");
        }
        __syncwarp();
        CLUSTER_ARRIVE();
        asm volatile("setmaxnreg.inc.sync.aligned.u32 160;");
        const int tid = threadIdx.x & 127;
        const int warp = tid >> 5;
        const bool rel = tid < 2;
        uint32_t rel_bar;
        asm("mapa.shared::cluster.u32 %0, %1, %2;" : "=r"(rel_bar) : "r"(bars + kBarEmpty), "r"(tid & 1));
        const uint32_t b_lo0 = ((sbase & 0x3FFFF) >> 4) | 0x10000u;
        const uint32_t frag_off = ((lane >> 4) * 8 + (lane & 7)) * 128 + (((2 * warp + ((lane >> 3) & 1)) ^ (lane & 7)) << 4);
        uint32_t st_addr = sbase + kOffOut + OBUF * wg * kChunk + frag_off, tid16 = tid * 16;
        asm volatile("" : "+r"(st_addr), "+r"(tid16));
        uint4* const wf = &g_wfrag[0][rank][slice(wg)][pj][tid];
        constexpr int kSet = 2 * 3 * 24 * 128;

        float acc[32];
        uint32_t w[96], p[16];

        auto load_w = [&]() {
        mbar_wait(bars + kBarW + 8 * wg, 0);
        if (tid == 0) CURVE_REC(3, 48 + wg);
        const uint32_t w_addr = sbase + (kSlotW + 6 * wg) * kChunk + frag_off;
#pragma unroll
        for (int s = 0; s < 24; s++) {
            if (WSPLIT && s == 12) mbar_wait(bars + kBarW2 + 8 * wg, 0);
            asm volatile("ldmatrix.sync.aligned.m8n8.x4.trans.shared.b16 {%0,%1,%2,%3}, [%4];"
                         : "=r"(w[4 * s]), "=r"(w[4 * s + 1]), "=r"(w[4 * s + 2]), "=r"(w[4 * s + 3]) : "r"(w_addr + s * 2048) : "memory");
        }
        if (wg < npc) {
            asm volatile("ldmatrix.sync.aligned.m8n8.x4.trans.shared.b16 {%0,%1,%2,%3}, [%4];"
                         : "=r"(p[0]), "=r"(p[1]), "=r"(p[2]), "=r"(p[3]) : "r"(w_addr + pj * 2048) : "memory");
            if (!PUBTMA) wf[0] = make_uint4(p[0], p[1], p[2], p[3]);
        }
        asm volatile("bar.sync %0, 128;" ::"r"(4 + wg) : "memory");
        {
            const uint32_t m = (wg == 2 ? 0x3F : 0xFFF) & ~(PUBTMA && wg && wg < npc ? 3u << 2 * (pub_slot(wg) - kSlotW - 6 * wg) : 0u);
            asm volatile("{\n.reg .pred p;\nsetp.ne.u32 p, %1, 0;\n@p mbarrier.arrive.shared::cluster.b64 _, [%0], 3;\n}\n"
                         ::"r"(rel_bar + 8 * (kSlotW + 6 * wg + (tid >> 1))), "r"(tid < 12 ? m >> tid & 1 : 0) : "memory");
        }
        if (threadIdx.x == 0) CURVE_REC(2, 59);
        if (wg < npc) {
            mbar_wait(bars + kBarL, 0);
            if (threadIdx.x == 0) CURVE_REC(3, 61);
            WG_FENCE();
            piece_steps<0>(acc, w, b_lo0 + kSlotL * 512);
            WG_COMMIT();
            WG_WAIT(0);
#pragma unroll
            for (int i = 0; i < 8; i++) {
                asm volatile("" : "+f"(acc[i]), "+f"(acc[8 + i]), "+f"(acc[16 + i]), "+f"(acc[24 + i]));
                if (CHAINS == 2) acc[i] += acc[8 + i];
                if (CHAINS == 4) acc[i] = (acc[i] + acc[8 + i]) + (acc[16 + i] + acc[24 + i]);
            }
            const uint32_t a = sbase + pub_slot(wg) * kChunk + 4096 + tid16;
            asm volatile("st.shared.v4.u32 [%0], {%1,%2,%3,%4};" ::"r"(a), "r"(p[0]), "r"(p[1]), "r"(p[2]), "r"(p[3]) : "memory");
            asm volatile("st.shared.v4.u32 [%0], {%1,%2,%3,%4};" ::"r"(a + 2048), "r"(pack_bf16(acc[0], acc[1])), "r"(pack_bf16(acc[2], acc[3])),
                         "r"(pack_bf16(acc[4], acc[5])), "r"(pack_bf16(acc[6], acc[7])) : "memory");
            __syncwarp();
            if (threadIdx.x == 0) CURVE_REC(3, 62);
            if (lane == 0) mbar_arrive(bars + kBarPiece);
        }
        if (tid < (PUBTMA && wg == 0 && npc ? 2 : 4)) mbar_arrive_cluster<1>(rel_bar + 8 * (kSlotL + (tid >> 1)));
        if (threadIdx.x == 256) CURVE_REC(2, 60);
        };
        if (tid == 0) CURVE_REC(3, 46);
        CLUSTER_WAIT();
        if (tid == 0) CURVE_REC(3, 47);
#pragma unroll
        for (int i = 0; i < 16; i++) p[i] = 0;

        const int tok_in = 1 + wg, tok_out = wg == 2 ? 1 : wg + 2;
#pragma unroll 1
        for (int t = 0; t < kTiles; t++) {
            const uint2 e = *(const uint2*)&tiles[t];
            const uint32_t fl = e.y >> 24, pe = tiles[t].p[wg];
            const uint32_t p_addr = sbase + (pe & 0xF8) * 1024 + tid16;
            if ((~fl & (F_FINE | F_P)) == 0) {
#pragma unroll
                for (int q = 0; q < 4; q++)
                    asm volatile("ld.shared.v4.u32 {%0,%1,%2,%3}, [%4];" : "=r"(p[4 * q]), "=r"(p[4 * q + 1]), "=r"(p[4 * q + 2]), "=r"(p[4 * q + 3])
                                 : "r"(p_addr + q * 2048) : "memory");
            }
            const char* swap = (const char*)&g_wfrag[1][rank][slice(wg)][0][0];
            auto init = [&](auto quarter) {
                constexpr int Q = decltype(quarter)::value;
#pragma unroll
                for (int i = 0; i < 8; i++)
                    asm volatile("shl.b32 %0, %4, 16;\nshl.b32 %1, %4, 16;\nand.b32 %2, %4, 0xffff0000;\nand.b32 %3, %4, 0xffff0000;"
                                 : "=f"(acc[4 * i]), "=f"(acc[4 * i + 1]), "=f"(acc[4 * i + 2]), "=f"(acc[4 * i + 3]) : "r"(p[4 * Q + (i & 3)]));
            };
            if (fl & F_FINE) {
                if (fl & F_Q2) {
                    if (fl & F_Q1) init(std::integral_constant<int, 3>());
                    else init(std::integral_constant<int, 2>());
                } else {
                    if (fl & F_Q1) init(std::integral_constant<int, 1>());
                    else {
                        if (DEFER >= 3) reload_w<3>(w, swap, tid16, ~fl & F_P);
                        if (DEFER >= 2) reload_w<4>(w, swap, tid16, ~fl & F_P);
                        if (DEFER >= 1) reload_w<5>(w, swap, tid16, ~fl & F_P);
                        init(std::integral_constant<int, 0>());
                    }
                }
            }
            if (fl & F_READY) {
                if (INLOOP && t == 0) load_w();
                else mbar_wait(bars + kBarReady, 0);
            }
            mbar_wait(bars + kBarFull + (e.x & 0xF8), e.x & 1);
            asm volatile("{\n.reg .pred p;\nsetp.eq.u32 p, %1, 0;\n@p bar.sync %0, 256;\n}\n" ::"r"(tok_in), "r"(pe & 1) : "memory");
            auto body = [&](auto mode) {
                constexpr int M = decltype(mode)::value;
                if (M == 1 && DEFER) asm volatile("{\n.reg .pred p;\nsetp.ne.u32 p, %0, 0;\n@p trap;\n}\n" ::"r"(w[95] & e.x & 4));
                bool rdy = issue_chunk<0>(acc, w, e, bars, b_lo0, true);
                CREC0(0);
                rdy = issue_chunk<1>(acc, w, e, bars, b_lo0, rdy);
                CREC0(1);
                if (TOKEN_K == 2) asm volatile("{\n.reg .pred p;\nsetp.eq.u32 p, %1, 0;\n@p bar.arrive %0, 256;\n}\n" ::"r"(tok_out), "r"(pe & 4) : "memory");
                retire_chunk<0, 1, M>(w, e, sched.wslot[pat], wg, sbase, rel_bar, rel, swap, tid16);
                if (M == 0 && rel && (~fl & (F_FINE | F_P)) == 0) mbar_arrive_cluster<3>(rel_bar + (pe & 0xF8));
                rdy = issue_chunk<2>(acc, w, e, bars, b_lo0, rdy);
                CREC0(2);
                if (TOKEN_K == 3) asm volatile("{\n.reg .pred p;\nsetp.eq.u32 p, %1, 0;\n@p bar.arrive %0, 256;\n}\n" ::"r"(tok_out), "r"(pe & 4) : "memory");
                retire_chunk<1, 1, M>(w, e, sched.wslot[pat], wg, sbase, rel_bar, rel, swap, tid16);
                rdy = issue_chunk<3>(acc, w, e, bars, b_lo0, rdy);
                CREC0(3);
                retire_chunk<2, 1, M>(w, e, sched.wslot[pat], wg, sbase, rel_bar, rel, swap, tid16);
                rdy = issue_chunk<4>(acc, w, e, bars, b_lo0, rdy);
                CREC0(4);
                retire_chunk<3, 1, M>(w, e, sched.wslot[pat], wg, sbase, rel_bar, rel, swap, tid16);
                rdy = issue_chunk<5>(acc, w, e, bars, b_lo0, rdy);
                CREC0(5);
                retire_chunk<4, 1, M>(w, e, sched.wslot[pat], wg, sbase, rel_bar, rel, swap, tid16);
                if (M != 1) mbar_wait(bars + (fl & F_FINE ? kBarFree + 8 * wg : kBarEmpty + (pe & 0xF8)), (pe >> 1) & 1);
                retire_chunk<5, 0, M>(w, e, sched.wslot[pat], wg, sbase, rel_bar, rel, swap, tid16);
            };
            if (!(fl & F_SWAP)) body(std::integral_constant<int, 0>());
            else if (fl & F_STAGED) body(std::integral_constant<int, 2>());
            else body(std::integral_constant<int, 1>());
            if (fl & F_FINE) {
#pragma unroll
                for (int q = 0; q < 4; q++)
                    asm volatile("stmatrix.sync.aligned.m8n8.x4.trans.shared.b16 [%0], {%1,%2,%3,%4};" ::"r"(st_addr + q * 2048),
                                 "r"(pack_bf16(acc[8 * q], acc[8 * q + 1])), "r"(pack_bf16(acc[8 * q + 2], acc[8 * q + 3])),
                                 "r"(pack_bf16(acc[8 * q + 4], acc[8 * q + 5])), "r"(pack_bf16(acc[8 * q + 6], acc[8 * q + 7])) : "memory");
                __syncwarp();
                asm volatile("{\n.reg .pred p;\nelect.sync _|p, 0xffffffff;\n@p mbarrier.arrive.shared::cta.b64 _, [%0];\n}\n" ::"r"(bars + kBarStaged + 8 * wg) : "memory");
            } else {
#pragma unroll
                for (int q = 0; q < 4; q++) {
                    p[4 * q] = pack_bf16(acc[8 * q], acc[8 * q + 2]);
                    p[4 * q + 1] = pack_bf16(acc[8 * q + 1], acc[8 * q + 3]);
                    p[4 * q + 2] = pack_bf16(acc[8 * q + 4], acc[8 * q + 6]);
                    p[4 * q + 3] = pack_bf16(acc[8 * q + 5], acc[8 * q + 7]);
                    if (fl & F_P)
                        asm volatile("st.shared.v4.u32 [%0], {%1,%2,%3,%4};" ::"r"(p_addr + q * 2048),
                                     "r"(p[4 * q]), "r"(p[4 * q + 1]), "r"(p[4 * q + 2]), "r"(p[4 * q + 3]) : "memory");
                }
            }
        }
    }
    CLUSTER_ARRIVE();
    CLUSTER_WAIT();
    if (threadIdx.x == 0) CURVE_REC(0, 63);
}

void build_schedule(int pat, Tile* tl, uint8_t (*wslot)[3][8], uint8_t* worder, const int* gs) {
    const int take[3] = {TAKE}, give[3] = {GIVE};
    const int staged = envi("STAGED", 1), wadv = envi("WADV", 1), wrel = envi("WREL", 2), wslack = envi("WSLACK", 0), wmax = envi("WMAX", 3);
    int coarse_of[16];
    int n = 0, nsw = 0, swt[2] = {};
    int units[kTiles];
    auto unit = [&](int t) { return units[t]; };
    for (int g = 0, i0 = 0; gs[g]; i0 += gs[g], g++) {
        for (int i = 1; i <= gs[g]; i++, n++) {
            units[n] = i0 + i % gs[g];
            tl[n].pos = (units[n] * NPAT + pat) * (SHAPE ? 4 : 2);
            tl[n].flags = i < gs[g] ? F_P : F_SWAP | (g == 0 ? F_READY : 0);
            coarse_of[unit(n)] = n;
        }
        for (int i = 0; i < 4 * gs[g]; i++, n++) {
            units[n] = i0 + i / 4;
            tl[n].pos = 0x8000 + (SHAPE ? ((units[n] * NPAT + pat) * 4 + (i & 3)) * kGroup : ((units[n] * NPAT + pat) * 2 + (i & 3) / 2) * kGroup + (i & 1) * 0x1000);
            tl[n].flags = F_FINE | (i >= 4 && (i & 3) == 0 ? F_P : 0) | (i & 1 ? F_Q1 : 0) | (i & 2 ? F_Q2 : 0);
            if (i == 4 * gs[g] - 1 && gs[g + 1]) {
                tl[n].flags |= staged ? F_SWAP | F_STAGED | (nsw ? F_SW1 : 0) : F_SWAP;
                if (staged) swt[nsw++] = n;
            }
        }
    }
    int nwo = 0;
    for (int need = -4; need < 6; need++)
        for (int g = 0; g < 3; g++) {
            const int c = need - give[g];
            if (c < 6 - NSTG || c > 5) continue;
            worder[nwo++] = g * 8 + c;
            for (int i = 0; i < nsw && !wslack; i++) {
                const int j = 6 * swt[i] + need + 4 - wadv;
                tl[j / 6].wcnt += 1 << (2 * (j % 6));
            }
        }
    int uses[kSlots], loads[kSlots], queue[512], head = 0, tail = 0, slot_of[6 * kTiles];
    for (int s = 0; s < kSlots; s++) uses[s] = s >= kSlotL, loads[s] = 0;
    auto take_p = [&](int t, int w, int s) { tl[t].p[w] = s * 8 + ((uses[s] + 1) & 1) * 2; uses[s]++; };
    bool taken[kSlots] = {};
    for (int w = 0; w < 3; w++)
        if (take[w] < 0 && (tl[0].flags & F_P)) take_p(0, w, kSlotW + 6 * w + 2), taken[kSlotW + 6 * w + 2] = true;
    for (int s = 0; s < kSlotL; s++) queue[tail++] = s;
    for (int s = kSlotW; s < kSlots; s++) if (!taken[s]) queue[tail++] = s;
    for (int s = kSlotL; s < kSlotW; s++) queue[tail++] = s;
    int r = 0, wk = 0, wi = 0;
    auto get_slot = [&]() {
        for (; head == tail; r++) {
            bool to_p = false;
            for (int w = 0; w < 3; w++) {
                int x = r - take[w];
                if (x >= 0 && x % 6 == 0 && x / 6 < kTiles && (tl[x / 6].flags & (F_FINE | F_P)) == F_P) take_p(x / 6, w, slot_of[r]), to_p = true;
            }
            if (!to_p) queue[tail++] = slot_of[r];
            for (int w = 0; w < 3; w++) {
                int x = r - give[w];
                if (x >= 0 && x % 6 == 0 && x / 6 < kTiles && (tl[x / 6].flags & (F_FINE | F_P)) == (F_FINE | F_P)) {
                    tl[x / 6].p[w] = tl[coarse_of[unit(x / 6)]].p[w];
                    queue[tail++] = tl[x / 6].p[w] >> 3;
                }
                x -= wrel;
                if (x >= 0 && x / 6 < kTiles && (tl[x / 6].flags & F_STAGED) && x % 6 >= 6 - NSTG) queue[tail++] = wslot[tl[x / 6].flags >> 7][w][x % 6] >> 3;
            }
        }
        return queue[head++];
    };
    for (int c = 0; c < 6 * kTiles; c++) {
        int s = get_slot();
        slot_of[c] = s;
        tl[c / 6].chunk[c % 6] = s * 8 + ((uses[s] + 1) & 1) * 2 + (loads[s] & 1);
        if (c % 6 == 0 && c) tl[c / 6 - 1].chunk[6] = tl[c / 6].chunk[0];
        uses[s]++, loads[s]++;
        for (int k = wslack ? wmax : (tl[c / 6].wcnt >> (2 * (c % 6))) & 3; k; k--) {
            if (wslack) {
                if (wi == nsw || 6 * swt[wi] + (worder[wk] & 7) + give[worder[wk] >> 3] - r > wslack) break;
                tl[c / 6].wcnt += 1 << (2 * (c % 6));
            }
            s = get_slot();
            (&wslot[wi][0][0])[worder[wk]] = s * 8 + ((uses[s] + 1) & 1) * 2;
            uses[s]++;
            if (++wk == 3 * NSTG) wk = 0, wi++;
        }
    }
    for (int t = 0; t < kTiles; t++)
        if ((tl[t].flags & (F_FINE | F_P)) == (F_FINE | F_P)) memcpy(tl[t].p, tl[coarse_of[unit(t)]].p, 3);
    for (int t = 0, k = 1; t < kTiles; t++)
        if (tl[t].flags & F_FINE) {
            for (int w = 0; w < 3; w++) tl[t].p[w] = (tl[t].p[w] & 0xF8) | (k & 1) * 2;
            k++;
        }
    if (INLOOP) tl[0].flags |= F_READY;
    const char* free_run = envs("NOTOK", "7100000000000000000000000000000000000000000001");
    for (int t = 0; t <= kTiles; t++)
        for (int w = 0; w < 3; w++)
            if ((free_run[t] - '0') >> w & 1) {
                tl[t].p[w] |= 1;
                if (w) tl[t].p[w - 1] |= 4;
                else if (t) tl[t - 1].p[2] |= 4;
            }
}

typedef CUresult (*EncodeFn)(CUtensorMap*, CUtensorMapDataType, cuuint32_t, void*, const cuuint64_t*, const cuuint64_t*,
                             const cuuint32_t*, const cuuint32_t*, CUtensorMapInterleave, CUtensorMapSwizzle,
                             CUtensorMapL2promotion, CUtensorMapFloatOOBfill);

void encode_2d(EncodeFn enc, CUtensorMap* tm, const void* ptr, uint64_t rows, uint32_t box_rows, CUtensorMapL2promotion promo) {
    cuuint64_t dims[2] = {(cuuint64_t)kC, rows};
    cuuint64_t strides[1] = {(cuuint64_t)kC * 2};
    cuuint32_t box[2] = {64, box_rows};
    cuuint32_t es[2] = {1, 1};
    enc(tm, CU_TENSOR_MAP_DATA_TYPE_BFLOAT16, 2, const_cast<void*>(ptr), dims, strides, box, es, CU_TENSOR_MAP_INTERLEAVE_NONE,
        CU_TENSOR_MAP_SWIZZLE_128B, promo, CU_TENSOR_MAP_FLOAT_OOB_FILL_NONE);
}

}

extern "C" void kernel_launch(void* const* d_in, const int* in_sizes, int n_in, void* d_out, int out_size) {
    (void)in_sizes; (void)n_in; (void)out_size;
    static EncodeFn enc = nullptr;
    static Schedule sched;
    static Scratch* scr;
    if (!enc) {
        cudaGetSymbolAddress((void**)&scr, g_scratch);
        void* fn = nullptr;
        cudaDriverEntryPointQueryResult qr;
        cudaGetDriverEntryPoint("cuTensorMapEncodeTiled", &fn, cudaEnableDefault, &qr);
        enc = (EncodeFn)fn;
        cudaFuncSetAttribute(fpn_lateral_kernel, cudaFuncAttributeMaxDynamicSharedMemorySize, kSmemBytes);
        if (envi("CARVE", 0)) cudaFuncSetAttribute(fpn_lateral_kernel, cudaFuncAttributePreferredSharedMemoryCarveout, envi("CARVE", 0));
        cudaLaunchConfig_t cfg = {};
        cfg.gridDim = dim3(2);
        cfg.blockDim = dim3(512);
        cfg.dynamicSmemBytes = kSmemBytes;
        cudaLaunchAttribute at;
        at.id = cudaLaunchAttributeClusterDimension;
        at.val.clusterDim.x = 2; at.val.clusterDim.y = 1; at.val.clusterDim.z = 1;
        cfg.attrs = &at; cfg.numAttrs = 1;
        int ncl = 0;
        if (cudaOccupancyMaxActiveClusters(&ncl, fpn_lateral_kernel, &cfg) != cudaSuccess) { (void)cudaGetLastError(); ncl = 0; }
        auto digit = [](char ch) { return ch > '9' ? ch - 'a' + 10 : ch - '0'; };
        const char* pn[4] = {"PATA", "PATB", "PATC", "PATD"};
        const char* pd[4] = {"45", "45", "36", "63"};
        sched.pgroup = envi("PGROUP", 0), sched.members = sched.pgroup ? kGroup : kClusters;
        for (int q = 0; q < NPAT; q++) {
            int gs[8] = {};
            const char* sa = envs(pn[q], pd[q]);
            for (int i = 0; sa[i]; i++) gs[i] = sa[i] - '0';
            build_schedule(q, sched.tile[q], sched.wslot[q], sched.worder, gs);
        }
        {
            const char* gaps = envs("GAPS", "00000jjjmmnllonnmiioooooooqkmnl000000ignoon00");
            const char* z = "000000000000000000000000000000000000000000000";
            for (int t = 0; t < kTiles; t++) {
                sched.sef[t] = digit(gaps[t]) + (envs("SEF", z)[t] - '0') * 64;
                if (envs("LEF", z)[t] - '0') sched.tile[0][t].pos |= 0x4000;
            }
            sched.gslack = envi("GSLACK", 0);
            const char* lead = envs("LEAD3", "0000000003579cefhnqnmmmmmmmqllllikjiihhdcdeee975accc666668acbba2466889999aca9abbba7a888a8a666666676666666666666666666666666666666666220");
            sched.pf_from = envi("PFFROM", 18);
            int pos = sched.pf_from;
            sched.tgt[0] = pos;
            for (int e = 0; e < EV * kTiles; e++) {
                const int x = (e + 1) * (6 / EV) + digit(lead[e]);
                if (pos < x) pos = x;
                if (pos > 6 * kTiles) pos = 6 * kTiles;
                sched.tgt[e + 1] = pos;
            }
            sched.pw_ev[0] = envi("PW0", 0) * EV / 6 + 1, sched.pw_ev[1] = envi("PW1", 144) * EV / 6 + 1, sched.pw_div = envi("PWDIV", 8);
            sched.t_a = envi("TA", 0), sched.t_d = envi("TD", 290), sched.t_max = envi("TMAX", 0), sched.fsleep = envi("FSLEEP", 0);
        }
        sched.gate1 = envi("GATE1", 1), sched.psleep = envi("PSLEEP", 20);
        sched.pace_from = envi("PACE_FROM", 15), sched.pace_to = envi("PACE_TO", 45);
        const char* v5 = "555555555555555555555555555555555555555555555";
        const char* vts[4] = {envs("VTA", v5), envs("VTB", v5), envs("VTC", v5), envs("VTD", v5)};
        int total = 0;
        for (int q = 0; q < NPAT; q++) {
            int sum[kTiles + 1] = {};
            for (int t = sched.pace_from; t < sched.pace_to; t++) sum[t] = sum[t - 1] + vts[q][t] - '0';
            total = sum[sched.pace_to - 1];
            for (int t = sched.pace_from; t < sched.pace_to; t++) {
                sched.vt[q][t] = sum[t] * 1024 / total;
                const int slack = digit(envs("SLK", "000000000jhedcouhgkhcde87768998a884444456577c")[t]) * 8;
                sched.need[q][t] = ncl >= kClusters ? sched.vt[q][t] * sched.members - slack * 5 * 1024 / total * sched.members / 64 : -1;
            }
        }
    }
    CUtensorMap tm_fine, tm_coarse, tm_wlat, tm_wout, tm_out;
    const cuuint32_t ones[5] = {1, 1, 1, 1, 1};
    {
        cuuint64_t dims[5] = {(cuuint64_t)kC, 2, 4, 4, (cuuint64_t)kFinePix / 32};
        cuuint64_t strides[4] = {768, 2 * 768, 8 * 768, 32 * 768};
        cuuint32_t box[5] = {64, 2, 4, 4, 1};
        enc(&tm_fine, CU_TENSOR_MAP_DATA_TYPE_BFLOAT16, 5, d_in[0], dims, strides, box, ones, CU_TENSOR_MAP_INTERLEAVE_NONE,
            CU_TENSOR_MAP_SWIZZLE_128B, CU_TENSOR_MAP_L2_PROMOTION_L2_128B, CU_TENSOR_MAP_FLOAT_OOB_FILL_NONE);
    }
    {
        cuuint64_t dims[3] = {64, (cuuint64_t)kC, 6};
        cuuint64_t strides[2] = {768, 128};
        cuuint32_t box[3] = {64, 16, 6};
        cuuint32_t es[3] = {1, 1, 1};
        enc(&tm_wlat, CU_TENSOR_MAP_DATA_TYPE_BFLOAT16, 3, d_in[2], dims, strides, box, es, CU_TENSOR_MAP_INTERLEAVE_NONE,
            CU_TENSOR_MAP_SWIZZLE_128B, CU_TENSOR_MAP_L2_PROMOTION_L2_256B, CU_TENSOR_MAP_FLOAT_OOB_FILL_NONE);
    }
    encode_2d(enc, &tm_wout, d_in[3], kC, 192, CU_TENSOR_MAP_L2_PROMOTION_L2_256B);
    {
        cuuint64_t dims[4] = {(cuuint64_t)kC, 32, 2, (cuuint64_t)kFinePix / 32 - kRankF};
        cuuint64_t strides[3] = {768, kRankF * 32 * 768, 32 * 768};
        cuuint32_t box[4] = {64, 32, 2, 1};
        enc(&tm_out, CU_TENSOR_MAP_DATA_TYPE_BFLOAT16, 4, d_out, dims, strides, box, ones, CU_TENSOR_MAP_INTERLEAVE_NONE,
            CU_TENSOR_MAP_SWIZZLE_128B, CU_TENSOR_MAP_L2_PROMOTION_NONE, CU_TENSOR_MAP_FLOAT_OOB_FILL_NONE);
    }
    {
        cuuint64_t dims[5] = {(cuuint64_t)kC, 2, 4, kGroup * kSeg / 8, (cuuint64_t)kCoarsePix / (kGroup * kSeg)};
        cuuint64_t strides[4] = {4 * 768, 768, 8 * 768, kGroup * kSeg * 768};
        cuuint32_t box[5] = {64, 2, 4, kSeg / 8, 32 / kSeg};
        enc(&tm_coarse, CU_TENSOR_MAP_DATA_TYPE_BFLOAT16, 5, d_in[1], dims, strides, box, ones, CU_TENSOR_MAP_INTERLEAVE_NONE,
            CU_TENSOR_MAP_SWIZZLE_128B, CU_TENSOR_MAP_L2_PROMOTION_L2_128B, CU_TENSOR_MAP_FLOAT_OOB_FILL_NONE);
    }
    fpn_lateral_kernel<<<2 * kClusters, 512, kSmemBytes>>>(scr, (const char*)d_in[0], (const char*)d_in[1], (const char*)d_in[2], (const char*)d_in[3],
                                                          tm_fine, tm_coarse, tm_wlat, tm_wout, tm_out, sched);
}
```

```cpp
#include <cuda_runtime.h>
#include <cuda_bf16.h>
#include <cuda.h>
#include <stdint.h>
#include <string.h>
#include <type_traits>
#include <stdlib.h>

#define TOKEN_K 3
#define TAKE -2, 0, 2
#define GIVE -4, -2, 0
#define L_POS 0
#define NSTG 6
#define EV 3
#define STPOL 1
#define NO_MMA 0
#define EARLY 1
#define EARLY_T 0
#define W_PRE 0
#define TOPPF 1
#define TLBW 1
#define W_MIX 0x1E
#define WR 1
#define CHAINS 1
#define ROT 0
#define PUBTMA 1
#define DEFER 2
#define INLOOP 1
#define WSPLIT 1
#define TPF_N 0
#define TPF_A 400
#define TPF_D 300
#define NPAT 1
#define SHAPE 1
#define OBUF 1
#define LD_EF 1
#define CURVE_REC(k, i) do {} while (0)

#define CREC0(c) do {} while (0)
namespace {

constexpr int kC = 384;
constexpr int kFinePix = 384 * 384;
constexpr int kCoarsePix = 192 * 192;
constexpr int kClusters = 64;
constexpr int kTiles = 45;
#define SLOTS (28 - 3 * OBUF)
constexpr int kSlots = SLOTS;
#define GT 1
#define ILV 0
constexpr int kColR = ILV ? 64 : 192, kColG = ILV ? 128 : 64;
constexpr int kChunk = 8192;
constexpr int kTileBytes = 6 * kChunk;
constexpr int kOffOut = kSlots * kChunk;
constexpr int kOffBar = kOffOut + 3 * OBUF * kChunk;
constexpr int kSmemBytes = kOffBar + 1024;
constexpr int kSlotL = kSlots + 3 * OBUF - 20;
constexpr int kSlotW = kSlots + 3 * OBUF - 18;
constexpr int kBarFull = 0, kBarEmpty = 8 * kSlots, kBarW = 16 * kSlots, kBarL = kBarW + 24;
constexpr int kBarPiece = kBarL + 8, kBarReady = kBarPiece + 8, kBarGo = kBarReady + 8, kBarFree = kBarGo + 8, kBarStaged = kBarFree + 24 * OBUF;
constexpr int kBarSwap = kBarStaged + 24 * OBUF;
constexpr int kBarReady2 = kBarSwap + 56;
constexpr int kStarted = kBarSwap + 192, kAllowed = kStarted + 4;
constexpr int kBarW2 = WSPLIT ? kStarted + 8 : kBarW;
constexpr int kPos0 = 4;
constexpr int kPieces = 24;

enum : uint32_t { F_FINE = 1, F_P = 2, F_Q1 = 4, F_SWAP = 8, F_READY = 16, F_Q2 = 32, F_STAGED = 64, F_SW1 = 128 };
struct alignas(16) Tile {
    uint8_t chunk[7];
    uint8_t flags;
    uint8_t p[3];
    uint8_t pw;
    uint16_t pos;
    uint16_t wcnt;
};
constexpr int kGroup = kClusters / NPAT;
struct Schedule {
    Tile tile[NPAT][kTiles + 1];
    uint16_t tgt[EV * kTiles + 2];
    alignas(8) uint8_t wslot[NPAT][2][3][8];
    uint8_t worder[24];
    uint8_t sef[48];
    int members, pgroup, gslack, gunit;
    int pace_from, pace_to, gate1, psleep, pf_from, pw_ev[2], pw_div, t_a, t_d, t_max, fsleep;
    int need[NPAT][kTiles + 1];
    uint16_t vt[NPAT][kTiles + 1];
};
static int envi(const char*, int d) { return d; }
static const char* envs(const char*, const char* d) { return d; }

struct Scratch {
    uint4 wfrag[2][2][3][24][128];
    uint32_t ready, pad0[31];
    uint32_t done, pad1[31];
    uint32_t progress[4][32];
};
__device__ Scratch g_scratch;
#define g_wfrag scr->wfrag
#define g_ready scr->ready
#define g_done scr->done
#define g_progress scr->progress

__device__ __forceinline__ uint32_t smem_u32(const void* p) { return (uint32_t)__cvta_generic_to_shared(p); }

__device__ __forceinline__ void mbar_init(uint32_t bar, uint32_t count) {
    asm volatile("mbarrier.init.shared::cta.b64 [%0], %1;" ::"r"(bar), "r"(count) : "memory");
}
__device__ __forceinline__ void mbar_expect_tx(uint32_t bar, uint32_t bytes) {
    asm volatile("mbarrier.arrive.expect_tx.shared::cta.b64 _, [%0], %1;" ::"r"(bar), "r"(bytes) : "memory");
}
__device__ __forceinline__ void mbar_wait(uint32_t bar, uint32_t parity) {
    asm volatile(
        "{\n"
        ".reg .pred p;\n"
        ".reg .u32 n;\n"
        "mov.u32 n, 0;\n"
        "WAIT_LOOP:\n"
        "mbarrier.try_wait.parity.shared::cta.b64 p, [%0], %1;\n"
        "@p bra WAIT_DONE;\n"
        "add.u32 n, n, 1;\n"
        "setp.lt.u32 p, n, 0x400000;\n"
        "@p bra WAIT_LOOP;\n"
        "trap;\n"
        "WAIT_DONE:\n"
        "}\n" ::"r"(bar), "r"(parity) : "memory");
}
__device__ __forceinline__ void mbar_wait1(uint32_t bar, uint32_t parity) {
    uint32_t r;
    asm volatile("{\n.reg .pred p;\nmbarrier.try_wait.parity.shared::cta.b64 p, [%1], %2;\nselp.u32 %0, 1, 0, p;\n}\n" : "=r"(r) : "r"(bar), "r"(parity) : "memory");
    if (!r) mbar_wait(bar, parity);
}
__device__ __forceinline__ bool mbar_test(uint32_t bar, uint32_t parity) {
    uint32_t r;
    asm volatile("{\n.reg .pred p;\nmbarrier.test_wait.parity.shared::cta.b64 p, [%1], %2;\nselp.u32 %0, 1, 0, p;\n}\n" : "=r"(r) : "r"(bar), "r"(parity) : "memory");
    return r != 0;
}
__device__ __forceinline__ void mbar_arrive(uint32_t bar) {
    asm volatile("mbarrier.arrive.shared::cta.b64 _, [%0];" ::"r"(bar) : "memory");
}
template <int N>
__device__ __forceinline__ void mbar_arrive_cluster(uint32_t bar) {
    if (N == 1) asm volatile("mbarrier.arrive.shared::cluster.b64 _, [%0];" ::"r"(bar) : "memory");
    else asm volatile("mbarrier.arrive.shared::cluster.b64 _, [%0], %1;" ::"r"(bar), "n"(N) : "memory");
}
__device__ __forceinline__ void bulk_load(uint32_t dst, const void* src, uint32_t bar) {
    asm volatile("cp.async.bulk.shared::cluster.global.mbarrier::complete_tx::bytes [%0], [%1], %2, [%3];"
                 ::"r"(dst), "l"(src), "n"(kChunk), "r"(bar) : "memory");
}
__device__ __forceinline__ void tma_load_2d(uint32_t dst, const CUtensorMap* tm, int c0, int c1, uint32_t bar) {
    asm volatile("cp.async.bulk.tensor.2d.shared::cluster.global.mbarrier::complete_tx::bytes [%0], [%1, {%2, %3}], [%4];"
                 ::"r"(dst), "l"(tm), "r"(c0), "r"(c1), "r"(bar) : "memory");
}
__device__ __forceinline__ void tma_load_3d(uint32_t dst, const CUtensorMap* tm, int c1, uint32_t bar) {
    asm volatile("cp.async.bulk.tensor.3d.shared::cluster.global.mbarrier::complete_tx::bytes [%0], [%1, {%2, %3, %2}], [%4];"
                 ::"r"(dst), "l"(tm), "r"(0), "r"(c1), "r"(bar) : "memory");
}
template <bool HINT>
__device__ __forceinline__ void tma_load_5d_mc(uint32_t dst, const CUtensorMap* tm, int c0, int c3, int c4, uint32_t bar, uint64_t pol) {
    if (HINT) asm volatile("cp.async.bulk.tensor.5d.shared::cluster.global.mbarrier::complete_tx::bytes.multicast::cluster.L2::cache_hint [%0], [%1, {%2, %3, %3, %4, %5}], [%6], %7, %8;"
                 ::"r"(dst), "l"(tm), "r"(c0), "r"(0), "r"(c3), "r"(c4), "r"(bar), "h"((uint16_t)3), "l"(pol) : "memory");
    else asm volatile("cp.async.bulk.tensor.5d.shared::cluster.global.mbarrier::complete_tx::bytes.multicast::cluster [%0], [%1, {%2, %3, %3, %4, %5}], [%6], %7;"
                 ::"r"(dst), "l"(tm), "r"(c0), "r"(0), "r"(c3), "r"(c4), "r"(bar), "h"((uint16_t)3) : "memory");
}
__device__ __forceinline__ void tma_store_4d(const CUtensorMap* tm, uint32_t src, int c0, int c3, uint64_t pol) {
    if (STPOL) asm volatile("cp.async.bulk.tensor.4d.global.shared::cta.bulk_group.L2::cache_hint [%0, {%2, %3, %3, %4}], [%1], %5;"
                 ::"l"(tm), "r"(src), "r"(c0), "r"(0), "r"(c3), "l"(pol) : "memory");
    else asm volatile("cp.async.bulk.tensor.4d.global.shared::cta.bulk_group [%0, {%2, %3, %3, %4}], [%1];"
                 ::"l"(tm), "r"(src), "r"(c0), "r"(0), "r"(c3) : "memory");
}
__device__ __forceinline__ void prefetch_l2(const void* p) {
    asm volatile("prefetch.global.L2 [%0];" ::"l"(p) : "memory");
}
__device__ __forceinline__ void prefetch_tm(const CUtensorMap* tm) {
    asm volatile("prefetch.tensormap [%0];" ::"l"(tm) : "memory");
}
__device__ __forceinline__ uint32_t now_ns() {
    uint32_t t;
    asm volatile("mov.u32 %0, %globaltimer_lo;" : "=r"(t));
    return t;
}
__device__ __forceinline__ bool elect_one() {
    uint32_t p;
    asm volatile("{\n.reg .pred p;\nelect.sync _|p, 0xffffffff;\nselp.u32 %0, 1, 0, p;\n}\n" : "=r"(p));
    return p != 0;
}
#define CLUSTER_ARRIVE() asm volatile("barrier.cluster.arrive.relaxed.aligned;" ::: "memory")
#define CLUSTER_WAIT() asm volatile("barrier.cluster.wait.acquire.aligned;" ::: "memory")

#define WG_FENCE() asm volatile("wgmma.fence.sync.aligned;" ::: "memory")
#define WG_COMMIT() asm volatile("wgmma.commit_group.sync.aligned;" ::: "memory")
#define WG_WAIT(n) asm volatile("wgmma.wait_group.sync.aligned %0;" ::"n"(n) : "memory")

#define ACC32 "{%0,%1,%2,%3,%4,%5,%6,%7,%8,%9,%10,%11,%12,%13,%14,%15,%16,%17,%18,%19,%20,%21,%22,%23,%24,%25,%26,%27,%28,%29,%30,%31}"
#define ACC8(b) "+f"(d[b]), "+f"(d[b + 1]), "+f"(d[b + 2]), "+f"(d[b + 3]), "+f"(d[b + 4]), "+f"(d[b + 5]), "+f"(d[b + 6]), "+f"(d[b + 7])

#define DESC_HI "0x40000040"
template <int BOFF>
__device__ __forceinline__ void wgmma_rs(float (&d)[32], const uint32_t* a, uint32_t b_lo) {
    asm volatile("{\n.reg .b32 tb;\n.reg .b64 db;\nadd.u32 tb, %36, %37;\nmov.b64 db, {tb, " DESC_HI "};\n"
                 "wgmma.mma_async.sync.aligned.m64n64k16.f32.bf16.bf16 " ACC32 ", {%32,%33,%34,%35}, db, 1, 1, 1, 0;\n}\n"
                 : ACC8(0), ACC8(8), ACC8(16), ACC8(24)
                 : "r"(a[0]), "r"(a[1]), "r"(a[2]), "r"(a[3]), "r"(b_lo), "n"(BOFF));
}
__device__ __forceinline__ void wgmma_rs_first(float (&d)[32], const uint32_t* a, uint32_t b_lo, uint32_t accum) {
    asm volatile("{\n.reg .pred p;\n.reg .b64 db;\nsetp.ne.u32 p, %37, 0;\nmov.b64 db, {%36, " DESC_HI "};\n"
                 "wgmma.mma_async.sync.aligned.m64n64k16.f32.bf16.bf16 " ACC32 ", {%32,%33,%34,%35}, db, p, 1, 1, 0;\n}\n"
                 : ACC8(0), ACC8(8), ACC8(16), ACC8(24)
                 : "r"(a[0]), "r"(a[1]), "r"(a[2]), "r"(a[3]), "r"(b_lo), "r"(accum));
}
template <int ACCUM, int BOFF, int D>
__device__ __forceinline__ void wgmma_rs16(float (&d)[32], const uint32_t* a, uint32_t b_lo) {
    asm volatile("{\n.reg .b32 tb;\n.reg .b64 db;\nadd.u32 tb, %12, %13;\nmov.b64 db, {tb, " DESC_HI "};\n"
                 "wgmma.mma_async.sync.aligned.m64n16k16.f32.bf16.bf16 {%0,%1,%2,%3,%4,%5,%6,%7}, {%8,%9,%10,%11}, db, %14, 1, 1, 0;\n}\n"
                 : ACC8(D)
                 : "r"(a[0]), "r"(a[1]), "r"(a[2]), "r"(a[3]), "r"(b_lo), "n"(BOFF), "n"(ACCUM));
}
template <int S>
__device__ __forceinline__ void piece_steps(float (&d)[32], const uint32_t (&w)[96], uint32_t b_lo) {
    if constexpr (S < 24) {
        wgmma_rs16<(S >= CHAINS), (S >> 2) * 128 + (S & 3) * 2, S % CHAINS * 8>(d, &w[4 * S], b_lo);
        piece_steps<S + 1>(d, w, b_lo);
    }
}

__device__ __forceinline__ uint32_t pack_bf16(float lo, float hi) {
    uint32_t r;
    asm("cvt.rn.bf16x2.f32 %0, %1, %2;" : "=r"(r) : "f"(hi), "f"(lo));
    return r;
}

template <int C>
__device__ __forceinline__ void reload_w(uint32_t (&w)[96], const char* base, uint32_t tid16, uint32_t on) {
#define W4(i) "+r"(w[16 * C + 4 * i]), "+r"(w[16 * C + 4 * i + 1]), "+r"(w[16 * C + 4 * i + 2]), "+r"(w[16 * C + 4 * i + 3])
    asm volatile("{\n.reg .pred p;\n.reg .b64 a;\nsetp.ne.u32 p, %19, 0;\ncvt.u64.u32 a, %18;\nadd.u64 a, a, %16;\n"
                 "@p ld.global.cg.v4.u32 {%0,%1,%2,%3}, [a + %17];\n"
                 "@p ld.global.cg.v4.u32 {%4,%5,%6,%7}, [a + %17 + 2048];\n"
                 "@p ld.global.cg.v4.u32 {%8,%9,%10,%11}, [a + %17 + 4096];\n"
                 "@p ld.global.cg.v4.u32 {%12,%13,%14,%15}, [a + %17 + 6144];\n}\n"
                 : W4(0), W4(1), W4(2), W4(3)
                 : "l"(base), "n"(C * 8192), "r"(tid16), "r"(on) : "memory");
#undef W4
}

template <int C>
__device__ __forceinline__ uint32_t entry(uint2 e) { return C < 4 ? e.x >> (8 * C) : e.y >> (8 * (C - 4)); }

template <int C>
__device__ __forceinline__ bool issue_chunk(float (&acc)[32], const uint32_t (&w)[96], uint2 e, uint32_t bars, uint32_t b_lo0, bool ready) {
    if (!ready) mbar_wait(bars + kBarFull + (entry<C>(e) & 0xF8), entry<C>(e) & 1);
    const bool next = C < 5 && mbar_test(bars + kBarFull + (entry<C + 1>(e) & 0xF8), entry<C + 1>(e) & 1);
    const uint32_t b_lo = b_lo0 + (entry<C>(e) & 0xF8) * 64;
    if (!NO_MMA) {
        WG_FENCE();
        if (C == 0) wgmma_rs_first(acc, &w[0], b_lo, e.y & (F_FINE << 24));
        else wgmma_rs<0>(acc, &w[16 * C], b_lo);
        wgmma_rs<2>(acc, &w[16 * C + 4], b_lo);
        wgmma_rs<4>(acc, &w[16 * C + 8], b_lo);
        wgmma_rs<6>(acc, &w[16 * C + 12], b_lo);
        WG_COMMIT();
    }
    return next;
}
template <int C, int PENDING, int MODE>
__device__ __forceinline__ void retire_chunk(uint32_t (&w)[96], uint2 e, const uint8_t (*ws)[3][8], int wg, uint32_t sbase, uint32_t rel_bar, bool rel, const char* swap, uint32_t tid16) {
    if (!NO_MMA) WG_WAIT(PENDING);
    if (rel) mbar_arrive_cluster<1>(rel_bar + (entry<C>(e) & 0xF8));
    if (MODE == 1 && C < 6 - DEFER) reload_w<C>(w, swap, tid16, 1);
    if (MODE == 2 && C >= 6 - NSTG) {
        const uint32_t x = ws[e.y >> 31][wg][C];
        mbar_wait(sbase + kOffBar + kBarSwap + 64 * wg + 8 * C, e.y >> 31);
        const uint32_t a = sbase + (x & 0xF8) * 1024 + tid16;
#pragma unroll
        for (int q = 0; q < 4; q++)
            asm volatile("ld.shared.v4.u32 {%0,%1,%2,%3}, [%4];" : "=r"(w[16 * C + 4 * q]), "=r"(w[16 * C + 4 * q + 1]), "=r"(w[16 * C + 4 * q + 2]), "=r"(w[16 * C + 4 * q + 3])
                         : "r"(a + q * 2048) : "memory");
        asm volatile("bar.sync %0, 128;" ::"r"(4 + wg + ((w[16 * C] | w[16 * C + 4] | w[16 * C + 8] | w[16 * C + 12]) & x & 1)) : "memory");
        if (rel) mbar_arrive_cluster<3>(rel_bar + (x & 0xF8));
    }
}

__device__ __forceinline__ int pub_slot(int g) { return g == 0 ? kSlotL + 1 : g == 1 ? kSlotW + 11 : kSlotW + 14; }
__device__ __forceinline__ int fine_group(uint32_t pos, int ci) {
    const uint32_t q = (pos & 0xFFF) + ci;
    return SHAPE ? q + q / 12 * 12 : 2 * q + (q / 6 + ((pos >> 12) & 1)) * 12;
}
constexpr int kRankF = SHAPE ? 12 : 1, kRankC = SHAPE ? 2 : 1, kSeg = SHAPE ? 16 : 32;
template <int L0, int L1>
__device__ __forceinline__ void prefetch_tile(uint32_t pos, int ci, int rank, int lane, const char* fine, const char* coarse) {
    const bool f = pos & 0x8000;
    const uint32_t row = f ? (fine_group(pos, ci) + kRankF * rank) * 32 : (((pos & 0xFFF) + kRankC * rank) * kGroup + ci) * kSeg;
    const char* p = (f ? fine : coarse) + (size_t)row * 768 + lane * 128;
    const char* q = SHAPE && !f ? p + (kGroup - 1) * kSeg * 768 : p;
#pragma unroll
    for (int l = L0; l < L1; l++) prefetch_l2((l < 3 ? p : q) + l * 4096);
}

__global__ void __cluster_dims__(2, 1, 1) __launch_bounds__(512, 1)
fpn_lateral_kernel(Scratch* const scr, const char* __restrict__ fine, const char* __restrict__ coarse,
                   const char* __restrict__ wlat, const char* __restrict__ wout,
                   const __grid_constant__ CUtensorMap tm_fine, const __grid_constant__ CUtensorMap tm_coarse,
                   const __grid_constant__ CUtensorMap tm_wlat, const __grid_constant__ CUtensorMap tm_wout,
                   const __grid_constant__ CUtensorMap tm_out, const __grid_constant__ Schedule sched) {
    extern __shared__ __align__(1024) unsigned char smem_raw[];
    if (threadIdx.x == 0) CURVE_REC(0, 0);
    uint32_t t_start;
    asm volatile("mov.u32 %0, %clock;" : "=r"(t_start));
    const uint32_t sbase = smem_u32(smem_raw);
    const uint32_t bars = sbase + kOffBar;
    const int rot = !ROT ? 0 : blockIdx.x < 4 * kPieces ? blockIdx.x & 2 : 1;
    const int npc = !ROT ? (blockIdx.x < 2 * kPieces ? 3 : 0) : blockIdx.x < 4 * kPieces ? 2 - (rot >> 1) : 0;
    const int pj = blockIdx.x >> (1 + ROT);
    auto slice = [&](int g) { return g + rot >= 3 ? g + rot - 3 : g + rot; };
    if (threadIdx.x == EARLY_T) {
        mbar_init(bars + kBarW, 1);
        if (WSPLIT) mbar_init(bars + kBarW2, 1);
        mbar_init(bars + kBarL, 1);
        asm volatile("fence.proxy.async.shared::cta;" ::: "memory");
        mbar_expect_tx(bars + kBarW, kTileBytes >> WSPLIT);
        if (WSPLIT) mbar_expect_tx(bars + kBarW2, kTileBytes >> WSPLIT);
        for (int c = 0; c < 2; c++) tma_load_2d(sbase + (kSlotW + 3 * c) * kChunk, &tm_wout, (blockIdx.x & 1) * kColR + rot * kColG, c * 192, bars + (c ? kBarW2 : kBarW));
        prefetch_tm(&tm_coarse);
        if (npc) {
            mbar_expect_tx(bars + kBarL, 6 * 2048);
            tma_load_3d(sbase + kSlotL * kChunk, &tm_wlat, pj * 16, bars + kBarL);
        }
        asm volatile("fence.mbarrier_init.release.cluster;" ::: "memory");
        CURVE_REC(1, 47);
    }
    {
        constexpr int kWw = (36 * WR + 31) / 32;
        const uint32_t t = threadIdx.x - 32, b = blockIdx.x, c = (t >> 5) - kWw, l = ((b >> 1) % (64 / WR)) * (36 * WR) + t;
        const uint32_t row = ((kPos0 + kRankC * (b & 1) + ((t >> 4) & 1)) * kGroup + (b >> 1)) * kSeg + (t & 15);
        const char* p = t >= 32 * kWw ? coarse + row * 768 + c * 128 : (b & 1 ? wlat : wout) + l * 128;
        if (t < 36 * WR || c < TOPPF) prefetch_l2(p);
    }
    const int warp_id = __shfl_sync(0xffffffffu, (int)(threadIdx.x >> 5), 0);
    const int lane = threadIdx.x & 31;
    const int wg = warp_id >> 2;
    const int rank = blockIdx.x & 1;
    const int cid = blockIdx.x >> 1;
    const int pat = cid % NPAT, ci = cid / NPAT;
    const Tile* const tiles = sched.tile[pat];

    if (wg == 3) {
        asm volatile("setmaxnreg.dec.sync.aligned.u32 32;");
        const int j = warp_id & 3;
        const bool lead = elect_one();
        if (j == 3) {
            uint32_t c0;
            asm volatile("mov.u32 %0, %clock;" : "=r"(c0));
            if (lead) CURVE_REC(1, 46);
            if (lead) {
                mbar_init(bars + kBarW + 8, 1);
                mbar_init(bars + kBarW + 16, 1);
                if (WSPLIT) mbar_init(bars + kBarW2 + 8, 1), mbar_init(bars + kBarW2 + 16, 1);
                asm volatile("fence.mbarrier_init.release.cluster;" ::: "memory");
                asm volatile("fence.proxy.async.shared::cta;" ::: "memory");
            }
            __syncwarp();
            CLUSTER_ARRIVE();
            if (lead) {
                for (int g = 1; g < 3; g++) {
                    mbar_expect_tx(bars + kBarW + 8 * g, kTileBytes >> WSPLIT);
                    if (WSPLIT) mbar_expect_tx(bars + kBarW2 + 8 * g, kTileBytes >> WSPLIT);
                }
                for (int g = 2; g < 2 + W_PRE; g++) tma_load_2d(sbase + (kSlotW + 3 * g) * kChunk, &tm_wout, rank * kColR + slice(g >> 1) * kColG, (g & 1) * 192, bars + (g & 1 ? kBarW2 : kBarW) + 8 * (g >> 1));
            }
            __syncwarp();
            CLUSTER_WAIT();
            if (lead) {
                int g = 2 + W_PRE;
#pragma unroll 1
                for (int c = 0; c < 6; c++) {
                    mbar_expect_tx(bars + kBarFull + 8 * c, kChunk);
                    tma_load_5d_mc<false>(sbase + rank * 4096 + c * kChunk, &tm_coarse, c * 64, ci * (kSeg / 8), kPos0 + kRankC * rank, bars + kBarFull + 8 * c, 0);
                    CURVE_REC(1, 52 + c);
                    if ((W_MIX >> c & 1) && g < 6) {
                        tma_load_2d(sbase + (kSlotW + 3 * g) * kChunk, &tm_wout, rank * kColR + slice(g >> 1) * kColG, (g & 1) * 192, bars + (g & 1 ? kBarW2 : kBarW) + 8 * (g >> 1));
                        g++;
                    }
                }
#pragma unroll 1
                for (; g < 6; g++) {
                    tma_load_2d(sbase + (kSlotW + 3 * g) * kChunk, &tm_wout, rank * kColR + slice(g >> 1) * kColG, (g & 1) * 192, bars + (g & 1 ? kBarW2 : kBarW) + 8 * (g >> 1));
                    CURVE_REC(1, 47 + (g >> 1));
                }
            }
            __syncwarp();
            uint32_t cur = sched.pf_from, u = 0, pw = sched.pw_ev[0] == 1;
            const char* p = nullptr;
#pragma unroll 1
            for (uint32_t n = 0; cur < 6 * kTiles; n++) {
                uint32_t v;
                asm volatile("ld.volatile.shared.u32 %0, [%1];" : "=r"(v) : "r"(bars + kStarted) : "memory");
                uint32_t tgt = sched.tgt[v];
                if (cur < sched.t_max) {
                    uint32_t c;
                    asm volatile("mov.u32 %0, %clock;" : "=r"(c));
                    if ((int)(c - c0) >= (int)(sched.t_a + cur * sched.t_d)) tgt = max(tgt, cur + 1);
                }
#pragma unroll 1
                for (; cur < tgt; cur++) {
                    if (u == 0) {
                        const uint32_t pos = tiles[cur / 6].pos;
                        const bool f = pos & 0x8000;
                        const uint32_t row = f ? (fine_group(pos, ci) + kRankF * rank) * 32 + lane : (((pos & 0xFFF) + kRankC * rank + (lane >> 4)) * kGroup + ci) * kSeg + (lane & 15);
                        p = (f ? fine : coarse) + (size_t)row * 768;
                    }
                    prefetch_l2(p);
                    p += 128;
                    u = u == 5 ? 0 : u + 1;
                }
                if (pw < 2 && v >= sched.pw_ev[pw]) {
                    const char* q = (const char*)&g_wfrag[pw][rank][0][0][0] + lane * 128;
#pragma unroll 1
                    for (int l = ci % sched.pw_div; l < 36; l += sched.pw_div) prefetch_l2(q + l * 4096);
                    pw++;
                }
                if (n == 0x1000000) __trap();
                __nanosleep(sched.fsleep);
            }
        } else if (j == 2) {
            if (lead) CURVE_REC(1, 58);
            CLUSTER_ARRIVE();
            if (lead) {
                uint32_t v;
                asm volatile("ld.relaxed.gpu.global.u32 %0, [%1];" : "=r"(v) : "l"(&g_ready) : "memory");
            }
            if (lead) {
                CURVE_REC(1, 59);
                prefetch_tm(&tm_fine);
                prefetch_tm(&tm_out);
            }
            __syncwarp();
            CLUSTER_WAIT();
            if (lead) {
                if (npc) {
                    mbar_wait(bars + kBarPiece, 0);
                    asm volatile("fence.proxy.async.shared::cta;" ::: "memory");
                    for (int i = 0; i < 2 * npc; i++)
                        asm volatile("cp.async.bulk.global.shared::cta.bulk_group [%0], [%1], 2048;"
                                     ::"l"(&g_wfrag[i & 1][rank][slice(i >> 1)][pj][0]), "r"(sbase + pub_slot(i >> 1) * kChunk + 4096 + (i & 1) * 2048) : "memory");
                    asm volatile("cp.async.bulk.commit_group;" ::: "memory");
                    asm volatile("cp.async.bulk.wait_group.read 0;" ::: "memory");
                    for (int i = 0; i < 2 * npc; i++) {
                        uint32_t b;
                        asm("mapa.shared::cluster.u32 %0, %1, %2;" : "=r"(b) : "r"(bars + kBarEmpty + 8 * pub_slot(i >> 1)), "r"(i & 1));
                        asm volatile("mbarrier.arrive.shared::cluster.b64 _, [%0], %1;" ::"r"(b), "r"(i < 2 ? 1 : 3) : "memory");
                    }
                    asm volatile("cp.async.bulk.wait_group 0;" ::: "memory");
                    asm volatile("red.relaxed.gpu.global.add.u32 [%0], 1;" ::"l"(&g_ready) : "memory");
                    CURVE_REC(2, 61);
                }
                uint32_t v, n = 0;
                for (;;) {
                    asm volatile("ld.acquire.gpu.global.u32 %0, [%1];" : "=r"(v) : "l"(&g_ready) : "memory");
                    if (v >= (2 * kPieces << ROT)) break;
                    if (++n == 0x100000) __trap();
                    __nanosleep(50);
                }
                CURVE_REC(2, 62);
                mbar_arrive(bars + kBarReady);
                asm volatile("fence.proxy.async.global;" ::: "memory");
                mbar_arrive(bars + kBarReady2);
                if (atomicAdd(&g_done, 1) == gridDim.x - 1) {
                    g_ready = 0;
                    g_done = 0;
                }
                asm volatile("st.volatile.shared.u32 [%0], %1;" ::"r"(bars + kAllowed), "r"(rank == 0 || sched.gate1 ? sched.pace_from : kTiles) : "memory");
                if (rank == 0 || sched.gate1) {
                    const uint16_t* vt = sched.vt[pat];
                    uint32_t* const ctr = g_progress[sched.pgroup * pat];
                    const int members = sched.members, last = sched.pace_to - 1;
                    asm volatile("ld.relaxed.gpu.global.u32 %0, [%1];" : "=r"(v) : "l"(ctr) : "memory");
                    const uint32_t base = v - v % (members * 1024);
                    int counted = rank == 0 ? sched.pace_from - 1 : last, allowed = sched.pace_from;
#pragma unroll 1
                    for (n = 0; n < 0x10000 && (allowed <= last || counted < last); n++) {
                        int started;
                        asm volatile("ld.volatile.shared.u32 %0, [%1];" : "=r"(started) : "r"(bars + kStarted) : "memory");
                        started = (started + EV - 1) / EV;
                        if (counted < last && counted < started) {
                            const int upto = min(started, last);
                            asm volatile("red.relaxed.gpu.global.add.u32 [%0], %1;" ::"l"(ctr), "r"(vt[upto] - vt[counted]) : "memory");
                            counted = upto;
                        }
                        if (allowed <= last && started + 1 >= allowed) {
                            asm volatile("ld.relaxed.gpu.global.u32 %0, [%1];" : "=r"(v) : "l"(ctr) : "memory");
                            while (allowed <= last && (int)(v - base) >= sched.need[pat][allowed]) allowed++;
                            asm volatile("st.volatile.shared.u32 [%0], %1;" ::"r"(bars + kAllowed), "r"(allowed > last ? kTiles : allowed) : "memory");
                        }
                        __nanosleep(sched.psleep);
                    }
                    asm volatile("st.volatile.shared.u32 [%0], %1;" ::"r"(bars + kAllowed), "r"(kTiles) : "memory");
                    if (counted < last) asm volatile("red.relaxed.gpu.global.add.u32 [%0], %1;" ::"l"(ctr), "r"(vt[last] - vt[counted]) : "memory");
                }
            }
        } else if (j == 1) {
            if (lead) CURVE_REC(3, 51);
            if (sbase & 1023) __trap();
            if (lead) {
                asm volatile("st.shared.u32 [%0], %1;" ::"r"(bars + kStarted), "r"(0) : "memory");
                asm volatile("st.shared.u32 [%0], %1;" ::"r"(bars + kAllowed), "r"(8) : "memory");
                if (kSlots > 24) {
                    mbar_init(bars + kBarFull + 8 * 24, 1);
                    mbar_init(bars + kBarEmpty + 8 * 24, 6);
                }
                for (int i = 0; i < 3 + 6 * OBUF; i++) mbar_init(bars + kBarPiece + 8 * i, i == 0 ? max(4 * npc, 1) : i < 3 + 3 * OBUF ? 1 : 4);
                asm volatile("fence.acq_rel.cta;" ::: "memory");
                asm volatile("fence.mbarrier_init.release.cluster;" ::: "memory");
                CURVE_REC(3, 52);
            }
            __syncwarp();
            CLUSTER_ARRIVE();
            CLUSTER_WAIT();
            if (lead) {
                const uint32_t t0 = now_ns();
                uint32_t k = 0, last[3] = {t0, t0, t0};
                uint64_t pol_first, pol_normal;
                asm volatile("createpolicy.fractional.L2::evict_first.b64 %0, 1.0;" : "=l"(pol_first));
                asm volatile("createpolicy.fractional.L2::evict_normal.b64 %0, 1.0;" : "=l"(pol_normal));
#pragma unroll 1
                for (int t = 0; t < kTiles; t++) {
                    const uint32_t pos = tiles[t].pos, ef = sched.sef[t] >> 6, gap = (sched.sef[t] & 63) * sched.gunit;
                    if (!(pos & 0x8000)) continue;
                    const int row = fine_group(pos, ci);
#pragma unroll
                    for (int g = 0; g < 3; g++) {
                        mbar_wait1(bars + kBarStaged + 8 * g, k & 1);
                        if (g == 2) CURVE_REC(1, t);
                        {
                            uint32_t c;
                            last[g] += gap;
#pragma unroll 1
                            for (int n = 0; n < 4096; n++) {
                                c = now_ns();
                                if ((int)(c - last[g]) >= 0) break;
                                __nanosleep(20);
                            }
                            if ((int)(c - last[g]) > sched.gslack) last[g] = c - sched.gslack;
                        }
                        asm volatile("fence.proxy.async.shared::cta;" ::: "memory");
                        tma_store_4d(&tm_out, sbase + kOffOut + g * kChunk, rank * kColR + slice(g) * kColG, row, ef > g ? pol_first : pol_normal);
                        asm volatile("cp.async.bulk.commit_group;" ::: "memory");
                        if (g > 0) {
                            asm volatile("cp.async.bulk.wait_group.read 1;" ::: "memory");
                            mbar_arrive(bars + kBarFree + 8 * g - 8);
                        }
                    }
                    asm volatile("cp.async.bulk.wait_group.read 0;" ::: "memory");
                    mbar_arrive(bars + kBarFree + 16);
                    CURVE_REC(3, t);
                    k++;
                }
                asm volatile("cp.async.bulk.wait_group.read 0;" ::: "memory");
            }
        } else {
            if (lead) CURVE_REC(1, 50);
            CLUSTER_ARRIVE();
            uint4 e = *(const uint4*)&tiles[1];
            asm volatile("" : "+r"(e.x), "+r"(e.y), "+r"(e.w));
            CLUSTER_WAIT();
            if (lead) CURVE_REC(1, 51);
            if (lead) {
                uint32_t dst0 = sbase + rank * 4096, bar0 = bars;
                asm volatile("" : "+r"(dst0), "+r"(bar0));
                uint32_t wk = 0, wi = 0;
                int allowed = 0;
                uint64_t pol_first, pol_normal;
                asm volatile("createpolicy.fractional.L2::evict_first.b64 %0, 1.0;" : "=l"(pol_first));
                asm volatile("createpolicy.fractional.L2::evict_normal.b64 %0, 1.0;" : "=l"(pol_normal));
#pragma unroll 1
                for (int t = EARLY ? 1 : 0; t < kTiles; t++) {
                    if (t > 1) e = *(const uint4*)&tiles[t];
                    const bool f = e.w & 0x8000;
                    const CUtensorMap* tm = f ? &tm_fine : &tm_coarse;
                    const int c3 = f ? 0 : ci * (kSeg / 8), c4 = f ? fine_group(e.w, ci) + kRankF * rank : (e.w & 0xFFF) + kRankC * rank;
                    for (uint32_t n = 0; t >= allowed; n++) {
                        asm volatile("ld.volatile.shared.u32 %0, [%1];" : "=r"(allowed) : "r"(bar0 + kAllowed) : "memory");
                        if (n == 0x4000000) __trap();
                        if (n) __nanosleep(20);
                    }
                    if (t) CURVE_REC(0, t);
#pragma unroll
                    for (int c = 0; c < 6; c++) {
                        if (c % (6 / EV) == 0) asm volatile("st.volatile.shared.u32 [%0], %1;" ::"r"(bar0 + kStarted), "r"(EV * t + 1 + c / (6 / EV)) : "memory");
                        const uint32_t x = c < 4 ? e.x >> (8 * c) : e.y >> (8 * (c - 4)), s8 = x & 0xF8;
                        mbar_wait1(bar0 + kBarEmpty + s8, (x >> 1) & 1);
                        mbar_expect_tx(bar0 + kBarFull + s8, kChunk);
                        tma_load_5d_mc<LD_EF>(dst0 + s8 * 1024, tm, c * 64, c3, c4, bar0 + kBarFull + s8, x & 4 ? pol_first : pol_normal);
#pragma unroll 1
                        for (uint32_t n = (e.w >> (16 + 2 * c)) & 3; n; n--) {
                            if (wk == 0) mbar_wait(bar0 + kBarReady2, 0);
                            const uint32_t o = sched.worder[wk], y = (&sched.wslot[pat][wi][0][0])[o];
                            mbar_wait1(bar0 + kBarEmpty + (y & 0xF8), (y >> 1) & 1);
                            mbar_expect_tx(bar0 + kBarSwap + 8 * o, kChunk);
                            bulk_load(sbase + (y & 0xF8) * 1024, (const char*)&g_wfrag[0][rank][0][0][0] + (6 * slice(o >> 3) + (o & 7)) * kChunk, bar0 + kBarSwap + 8 * o);
                            if (++wk == 3 * NSTG) wk = 0, wi++;
                        }
                    }
                }
            }
        }
        __syncwarp();
    } else {
        if (elect_one()) {
            for (int i = 2 * warp_id; i < 2 * warp_id + 2; i++) {
                mbar_init(bars + kBarSwap + 8 * i, 1);
                if (i >= kSlots) continue;
                mbar_init(bars + kBarFull + 8 * i, 1);
                mbar_init(bars + kBarEmpty + 8 * i, 6);
            }
            asm volatile("fence.mbarrier_init.release.cluster;" ::: "memory");
        }
        __syncwarp();
        CLUSTER_ARRIVE();
        asm volatile("setmaxnreg.inc.sync.aligned.u32 160;");
        const int tid = threadIdx.x & 127;
        const int warp = tid >> 5;
        const bool rel = tid < 2;
        uint32_t rel_bar;
        asm("mapa.shared::cluster.u32 %0, %1, %2;" : "=r"(rel_bar) : "r"(bars + kBarEmpty), "r"(tid & 1));
        const uint32_t b_lo0 = ((sbase & 0x3FFFF) >> 4) | 0x10000u;
        const uint32_t frag_off = ((lane >> 4) * 8 + (lane & 7)) * 128 + (((2 * warp + ((lane >> 3) & 1)) ^ (lane & 7)) << 4);
        uint32_t st_addr = sbase + kOffOut + OBUF * wg * kChunk + frag_off, tid16 = tid * 16;
        asm volatile("" : "+r"(st_addr), "+r"(tid16));
        uint4* const wf = &g_wfrag[0][rank][slice(wg)][pj][tid];
        constexpr int kSet = 2 * 3 * 24 * 128;

        float acc[32];
        uint32_t w[96], p[16];

        auto load_w = [&]() {
        mbar_wait(bars + kBarW + 8 * wg, 0);
        if (tid == 0) CURVE_REC(3, 48 + wg);
        const uint32_t w_addr = sbase + (kSlotW + 6 * wg) * kChunk + frag_off;
#pragma unroll
        for (int s = 0; s < 24; s++) {
            if (WSPLIT && s == 12) mbar_wait(bars + kBarW2 + 8 * wg, 0);
            asm volatile("ldmatrix.sync.aligned.m8n8.x4.trans.shared.b16 {%0,%1,%2,%3}, [%4];"
                         : "=r"(w[4 * s]), "=r"(w[4 * s + 1]), "=r"(w[4 * s + 2]), "=r"(w[4 * s + 3]) : "r"(w_addr + s * 2048) : "memory");
        }
        if (wg < npc) {
            asm volatile("ldmatrix.sync.aligned.m8n8.x4.trans.shared.b16 {%0,%1,%2,%3}, [%4];"
                         : "=r"(p[0]), "=r"(p[1]), "=r"(p[2]), "=r"(p[3]) : "r"(w_addr + pj * 2048) : "memory");
            if (!PUBTMA) wf[0] = make_uint4(p[0], p[1], p[2], p[3]);
        }
        asm volatile("bar.sync %0, 128;" ::"r"(4 + wg) : "memory");
        {
            const uint32_t m = (wg == 2 ? 0x3F : 0xFFF) & ~(PUBTMA && wg && wg < npc ? 3u << 2 * (pub_slot(wg) - kSlotW - 6 * wg) : 0u);
            asm volatile("{\n.reg .pred p;\nsetp.ne.u32 p, %1, 0;\n@p mbarrier.arrive.shared::cluster.b64 _, [%0], 3;\n}\n"
                         ::"r"(rel_bar + 8 * (kSlotW + 6 * wg + (tid >> 1))), "r"(tid < 12 ? m >> tid & 1 : 0) : "memory");
        }
        if (threadIdx.x == 0) CURVE_REC(2, 59);
        if (wg < npc) {
            mbar_wait(bars + kBarL, 0);
            if (threadIdx.x == 0) CURVE_REC(3, 61);
            WG_FENCE();
            piece_steps<0>(acc, w, b_lo0 + kSlotL * 512);
            WG_COMMIT();
            WG_WAIT(0);
#pragma unroll
            for (int i = 0; i < 8; i++) {
                asm volatile("" : "+f"(acc[i]), "+f"(acc[8 + i]), "+f"(acc[16 + i]), "+f"(acc[24 + i]));
                if (CHAINS == 2) acc[i] += acc[8 + i];
                if (CHAINS == 4) acc[i] = (acc[i] + acc[8 + i]) + (acc[16 + i] + acc[24 + i]);
            }
            const uint32_t a = sbase + pub_slot(wg) * kChunk + 4096 + tid16;
            asm volatile("st.shared.v4.u32 [%0], {%1,%2,%3,%4};" ::"r"(a), "r"(p[0]), "r"(p[1]), "r"(p[2]), "r"(p[3]) : "memory");
            asm volatile("st.shared.v4.u32 [%0], {%1,%2,%3,%4};" ::"r"(a + 2048), "r"(pack_bf16(acc[0], acc[1])), "r"(pack_bf16(acc[2], acc[3])),
                         "r"(pack_bf16(acc[4], acc[5])), "r"(pack_bf16(acc[6], acc[7])) : "memory");
            __syncwarp();
            if (threadIdx.x == 0) CURVE_REC(3, 62);
            if (lane == 0) mbar_arrive(bars + kBarPiece);
        }
        if (tid < (PUBTMA && wg == 0 && npc ? 2 : 4)) mbar_arrive_cluster<1>(rel_bar + 8 * (kSlotL + (tid >> 1)));
        if (threadIdx.x == 256) CURVE_REC(2, 60);
        };
        if (tid == 0) CURVE_REC(3, 46);
        CLUSTER_WAIT();
        if (tid == 0) CURVE_REC(3, 47);
#pragma unroll
        for (int i = 0; i < 16; i++) p[i] = 0;

        const int tok_in = 1 + wg, tok_out = wg == 2 ? 1 : wg + 2;
#pragma unroll 1
        for (int t = 0; t < kTiles; t++) {
            const uint2 e = *(const uint2*)&tiles[t];
            const uint32_t fl = e.y >> 24, pe = tiles[t].p[wg];
            const uint32_t p_addr = sbase + (pe & 0xF8) * 1024 + tid16;
            if ((~fl & (F_FINE | F_P)) == 0) {
#pragma unroll
                for (int q = 0; q < 4; q++)
                    asm volatile("ld.shared.v4.u32 {%0,%1,%2,%3}, [%4];" : "=r"(p[4 * q]), "=r"(p[4 * q + 1]), "=r"(p[4 * q + 2]), "=r"(p[4 * q + 3])
                                 : "r"(p_addr + q * 2048) : "memory");
            }
            const char* swap = (const char*)&g_wfrag[1][rank][slice(wg)][0][0];
            auto init = [&](auto quarter) {
                constexpr int Q = decltype(quarter)::value;
#pragma unroll
                for (int i = 0; i < 8; i++)
                    asm volatile("shl.b32 %0, %4, 16;\nshl.b32 %1, %4, 16;\nand.b32 %2, %4, 0xffff0000;\nand.b32 %3, %4, 0xffff0000;"
                                 : "=f"(acc[4 * i]), "=f"(acc[4 * i + 1]), "=f"(acc[4 * i + 2]), "=f"(acc[4 * i + 3]) : "r"(p[4 * Q + (i & 3)]));
            };
            if (fl & F_FINE) {
                if (fl & F_Q2) {
                    if (fl & F_Q1) init(std::integral_constant<int, 3>());
                    else init(std::integral_constant<int, 2>());
                } else {
                    if (fl & F_Q1) init(std::integral_constant<int, 1>());
                    else {
                        if (DEFER >= 3) reload_w<3>(w, swap, tid16, ~fl & F_P);
                        if (DEFER >= 2) reload_w<4>(w, swap, tid16, ~fl & F_P);
                        if (DEFER >= 1) reload_w<5>(w, swap, tid16, ~fl & F_P);
                        init(std::integral_constant<int, 0>());
                    }
                }
            }
            if (fl & F_READY) {
                if (INLOOP && t == 0) load_w();
                else mbar_wait(bars + kBarReady, 0);
            }
            mbar_wait(bars + kBarFull + (e.x & 0xF8), e.x & 1);
            asm volatile("{\n.reg .pred p;\nsetp.eq.u32 p, %1, 0;\n@p bar.sync %0, 256;\n}\n" ::"r"(tok_in), "r"(pe & 1) : "memory");
            auto body = [&](auto mode) {
                constexpr int M = decltype(mode)::value;
                if (M == 1 && DEFER) asm volatile("{\n.reg .pred p;\nsetp.ne.u32 p, %0, 0;\n@p trap;\n}\n" ::"r"(w[95] & e.y & 0x40000));
                bool rdy = issue_chunk<0>(acc, w, e, bars, b_lo0, true);
                CREC0(0);
                rdy = issue_chunk<1>(acc, w, e, bars, b_lo0, rdy);
                CREC0(1);
                if (TOKEN_K == 2) asm volatile("{\n.reg .pred p;\nsetp.eq.u32 p, %1, 0;\n@p bar.arrive %0, 256;\n}\n" ::"r"(tok_out), "r"(pe & 4) : "memory");
                retire_chunk<0, 1, M>(w, e, sched.wslot[pat], wg, sbase, rel_bar, rel, swap, tid16);
                if (M == 0 && rel && (~fl & (F_FINE | F_P)) == 0) mbar_arrive_cluster<3>(rel_bar + (pe & 0xF8));
                rdy = issue_chunk<2>(acc, w, e, bars, b_lo0, rdy);
                CREC0(2);
                if (TOKEN_K == 3) asm volatile("{\n.reg .pred p;\nsetp.eq.u32 p, %1, 0;\n@p bar.arrive %0, 256;\n}\n" ::"r"(tok_out), "r"(pe & 4) : "memory");
                retire_chunk<1, 1, M>(w, e, sched.wslot[pat], wg, sbase, rel_bar, rel, swap, tid16);
                rdy = issue_chunk<3>(acc, w, e, bars, b_lo0, rdy);
                CREC0(3);
                retire_chunk<2, 1, M>(w, e, sched.wslot[pat], wg, sbase, rel_bar, rel, swap, tid16);
                rdy = issue_chunk<4>(acc, w, e, bars, b_lo0, rdy);
                CREC0(4);
                retire_chunk<3, 1, M>(w, e, sched.wslot[pat], wg, sbase, rel_bar, rel, swap, tid16);
                rdy = issue_chunk<5>(acc, w, e, bars, b_lo0, rdy);
                CREC0(5);
                retire_chunk<4, 1, M>(w, e, sched.wslot[pat], wg, sbase, rel_bar, rel, swap, tid16);
                if (M != 1) mbar_wait(bars + (fl & F_FINE ? kBarFree + 8 * wg : kBarEmpty + (pe & 0xF8)), (pe >> 1) & 1);
                retire_chunk<5, 0, M>(w, e, sched.wslot[pat], wg, sbase, rel_bar, rel, swap, tid16);
            };
            if (!(fl & F_SWAP)) body(std::integral_constant<int, 0>());
            else if (fl & F_STAGED) body(std::integral_constant<int, 2>());
            else body(std::integral_constant<int, 1>());
            if (fl & F_FINE) {
#pragma unroll
                for (int q = 0; q < 4; q++)
                    asm volatile("stmatrix.sync.aligned.m8n8.x4.trans.shared.b16 [%0], {%1,%2,%3,%4};" ::"r"(st_addr + q * 2048),
                                 "r"(pack_bf16(acc[8 * q], acc[8 * q + 1])), "r"(pack_bf16(acc[8 * q + 2], acc[8 * q + 3])),
                                 "r"(pack_bf16(acc[8 * q + 4], acc[8 * q + 5])), "r"(pack_bf16(acc[8 * q + 6], acc[8 * q + 7])) : "memory");
                __syncwarp();
                asm volatile("{\n.reg .pred p;\nelect.sync _|p, 0xffffffff;\n@p mbarrier.arrive.shared::cta.b64 _, [%0];\n}\n" ::"r"(bars + kBarStaged + 8 * wg) : "memory");
            } else {
#pragma unroll
                for (int q = 0; q < 4; q++) {
                    p[4 * q] = pack_bf16(acc[8 * q], acc[8 * q + 2]);
                    p[4 * q + 1] = pack_bf16(acc[8 * q + 1], acc[8 * q + 3]);
                    p[4 * q + 2] = pack_bf16(acc[8 * q + 4], acc[8 * q + 6]);
                    p[4 * q + 3] = pack_bf16(acc[8 * q + 5], acc[8 * q + 7]);
                    if (fl & F_P)
                        asm volatile("st.shared.v4.u32 [%0], {%1,%2,%3,%4};" ::"r"(p_addr + q * 2048),
                                     "r"(p[4 * q]), "r"(p[4 * q + 1]), "r"(p[4 * q + 2]), "r"(p[4 * q + 3]) : "memory");
                }
            }
        }
    }
    CLUSTER_ARRIVE();
    CLUSTER_WAIT();
    if (threadIdx.x == 0) CURVE_REC(0, 63);
}

void build_schedule(int pat, Tile* tl, uint8_t (*wslot)[3][8], uint8_t* worder, const int* gs) {
    const int take[3] = {TAKE}, give[3] = {GIVE};
    const int staged = envi("STAGED", 1), wadv = envi("WADV", 1), wrel = envi("WREL", 2), wslack = envi("WSLACK", 0), wmax = envi("WMAX", 3);
    int coarse_of[16];
    int n = 0, nsw = 0, swt[2] = {};
    int units[kTiles];
    auto unit = [&](int t) { return units[t]; };
    for (int g = 0, i0 = 0; gs[g]; i0 += gs[g], g++) {
        for (int i = 1; i <= gs[g]; i++, n++) {
            units[n] = i0 + i % gs[g];
            tl[n].pos = (units[n] * NPAT + pat) * (SHAPE ? 4 : 2);
            tl[n].flags = i < gs[g] ? F_P : F_SWAP | (g == 0 ? F_READY : 0);
            coarse_of[unit(n)] = n;
        }
        for (int i = 0; i < 4 * gs[g]; i++, n++) {
            units[n] = i0 + i / 4;
            tl[n].pos = 0x8000 + (SHAPE ? ((units[n] * NPAT + pat) * 4 + (i & 3)) * kGroup : ((units[n] * NPAT + pat) * 2 + (i & 3) / 2) * kGroup + (i & 1) * 0x1000);
            tl[n].flags = F_FINE | (i >= 4 && (i & 3) == 0 ? F_P : 0) | (i & 1 ? F_Q1 : 0) | (i & 2 ? F_Q2 : 0);
            if (i == 4 * gs[g] - 1 && gs[g + 1]) {
                tl[n].flags |= staged ? F_SWAP | F_STAGED | (nsw ? F_SW1 : 0) : F_SWAP;
                if (staged) swt[nsw++] = n;
            }
        }
    }
    int nwo = 0;
    for (int need = -4; need < 6; need++)
        for (int g = 0; g < 3; g++) {
            const int c = need - give[g];
            if (c < 6 - NSTG || c > 5) continue;
            worder[nwo++] = g * 8 + c;
            for (int i = 0; i < nsw && !wslack; i++) {
                const int j = 6 * swt[i] + need + 4 - wadv;
                tl[j / 6].wcnt += 1 << (2 * (j % 6));
            }
        }
    int uses[kSlots], loads[kSlots], queue[512], head = 0, tail = 0, slot_of[6 * kTiles];
    for (int s = 0; s < kSlots; s++) uses[s] = s >= kSlotL, loads[s] = 0;
    auto take_p = [&](int t, int w, int s) { tl[t].p[w] = s * 8 + ((uses[s] + 1) & 1) * 2; uses[s]++; };
    bool taken[kSlots] = {};
    for (int w = 0; w < 3; w++)
        if (take[w] < 0 && (tl[0].flags & F_P)) take_p(0, w, kSlotW + 6 * w + 2), taken[kSlotW + 6 * w + 2] = true;
    for (int s = 0; s < kSlotL; s++) queue[tail++] = s;
    for (int s = kSlotW; s < kSlots; s++) if (!taken[s]) queue[tail++] = s;
    for (int s = kSlotL; s < kSlotW; s++) queue[tail++] = s;
    int r = 0, wk = 0, wi = 0;
    auto get_slot = [&]() {
        for (; head == tail; r++) {
            bool to_p = false;
            for (int w = 0; w < 3; w++) {
                int x = r - take[w];
                if (x >= 0 && x % 6 == 0 && x / 6 < kTiles && (tl[x / 6].flags & (F_FINE | F_P)) == F_P) take_p(x / 6, w, slot_of[r]), to_p = true;
            }
            if (!to_p) queue[tail++] = slot_of[r];
            for (int w = 0; w < 3; w++) {
                int x = r - give[w];
                if (x >= 0 && x % 6 == 0 && x / 6 < kTiles && (tl[x / 6].flags & (F_FINE | F_P)) == (F_FINE | F_P)) {
                    tl[x / 6].p[w] = tl[coarse_of[unit(x / 6)]].p[w];
                    queue[tail++] = tl[x / 6].p[w] >> 3;
                }
                x -= wrel;
                if (x >= 0 && x / 6 < kTiles && (tl[x / 6].flags & F_STAGED) && x % 6 >= 6 - NSTG) queue[tail++] = wslot[tl[x / 6].flags >> 7][w][x % 6] >> 3;
            }
        }
        return queue[head++];
    };
    for (int c = 0; c < 6 * kTiles; c++) {
        int s = get_slot();
        slot_of[c] = s;
        tl[c / 6].chunk[c % 6] = s * 8 + ((uses[s] + 1) & 1) * 2 + (loads[s] & 1);
        if (c % 6 == 0 && c) tl[c / 6 - 1].chunk[6] = tl[c / 6].chunk[0];
        uses[s]++, loads[s]++;
        for (int k = wslack ? wmax : (tl[c / 6].wcnt >> (2 * (c % 6))) & 3; k; k--) {
            if (wslack) {
                if (wi == nsw || 6 * swt[wi] + (worder[wk] & 7) + give[worder[wk] >> 3] - r > wslack) break;
                tl[c / 6].wcnt += 1 << (2 * (c % 6));
            }
            s = get_slot();
            (&wslot[wi][0][0])[worder[wk]] = s * 8 + ((uses[s] + 1) & 1) * 2;
            uses[s]++;
            if (++wk == 3 * NSTG) wk = 0, wi++;
        }
    }
    for (int t = 0; t < kTiles; t++)
        if ((tl[t].flags & (F_FINE | F_P)) == (F_FINE | F_P)) memcpy(tl[t].p, tl[coarse_of[unit(t)]].p, 3);
    for (int t = 0, k = 1; t < kTiles; t++)
        if (tl[t].flags & F_FINE) {
            for (int w = 0; w < 3; w++) tl[t].p[w] = (tl[t].p[w] & 0xF8) | (k & 1) * 2;
            k++;
        }
    if (INLOOP) tl[0].flags |= F_READY;
    const char* free_run = envs("NOTOK", "7100000000000000000000000000000000000000000001");
    for (int t = 0; t <= kTiles; t++)
        for (int w = 0; w < 3; w++)
            if ((free_run[t] - '0') >> w & 1) {
                tl[t].p[w] |= 1;
                if (w) tl[t].p[w - 1] |= 4;
                else if (t) tl[t - 1].p[2] |= 4;
            }
}

typedef CUresult (*EncodeFn)(CUtensorMap*, CUtensorMapDataType, cuuint32_t, void*, const cuuint64_t*, const cuuint64_t*,
                             const cuuint32_t*, const cuuint32_t*, CUtensorMapInterleave, CUtensorMapSwizzle,
                             CUtensorMapL2promotion, CUtensorMapFloatOOBfill);

void encode_2d(EncodeFn enc, CUtensorMap* tm, const void* ptr, uint64_t rows, uint32_t box_rows, CUtensorMapL2promotion promo) {
    cuuint64_t dims[2] = {(cuuint64_t)kC, rows};
    cuuint64_t strides[1] = {(cuuint64_t)kC * 2};
    cuuint32_t box[2] = {64, box_rows};
    cuuint32_t es[2] = {1, 1};
    enc(tm, CU_TENSOR_MAP_DATA_TYPE_BFLOAT16, 2, const_cast<void*>(ptr), dims, strides, box, es, CU_TENSOR_MAP_INTERLEAVE_NONE,
        CU_TENSOR_MAP_SWIZZLE_128B, promo, CU_TENSOR_MAP_FLOAT_OOB_FILL_NONE);
}

}

extern "C" void kernel_launch(void* const* d_in, const int* in_sizes, int n_in, void* d_out, int out_size) {
    (void)in_sizes; (void)n_in; (void)out_size;
    static EncodeFn enc = nullptr;
    static Schedule sched;
    static Scratch* scr;
    if (!enc) {
        cudaGetSymbolAddress((void**)&scr, g_scratch);
        void* fn = nullptr;
        cudaDriverEntryPointQueryResult qr;
        cudaGetDriverEntryPoint("cuTensorMapEncodeTiled", &fn, cudaEnableDefault, &qr);
        enc = (EncodeFn)fn;
        cudaFuncSetAttribute(fpn_lateral_kernel, cudaFuncAttributeMaxDynamicSharedMemorySize, kSmemBytes);
        if (envi("CARVE", 0)) cudaFuncSetAttribute(fpn_lateral_kernel, cudaFuncAttributePreferredSharedMemoryCarveout, envi("CARVE", 0));
        cudaLaunchConfig_t cfg = {};
        cfg.gridDim = dim3(2);
        cfg.blockDim = dim3(512);
        cfg.dynamicSmemBytes = kSmemBytes;
        cudaLaunchAttribute at;
        at.id = cudaLaunchAttributeClusterDimension;
        at.val.clusterDim.x = 2; at.val.clusterDim.y = 1; at.val.clusterDim.z = 1;
        cfg.attrs = &at; cfg.numAttrs = 1;
        int ncl = 0;
        if (cudaOccupancyMaxActiveClusters(&ncl, fpn_lateral_kernel, &cfg) != cudaSuccess) { (void)cudaGetLastError(); ncl = 0; }
        auto digit = [](char ch) { return ch > '9' ? ch - 'a' + 10 : ch - '0'; };
        const char* pn[4] = {"PATA", "PATB", "PATC", "PATD"};
        const char* pd[4] = {"45", "45", "36", "63"};
        sched.pgroup = envi("PGROUP", 0), sched.members = sched.pgroup ? kGroup : kClusters;
        for (int q = 0; q < NPAT; q++) {
            int gs[8] = {};
            const char* sa = envs(pn[q], pd[q]);
            for (int i = 0; sa[i]; i++) gs[i] = sa[i] - '0';
            build_schedule(q, sched.tile[q], sched.wslot[q], sched.worder, gs);
        }
        {
            const char* gaps = envs("GAPS", "00000mlknmnllonnmfemmnoqqjloqpn0000njjitvt000");
            const char* sef = envs("SEF", "000000000000000000000000000000000000000000000");
            const char* lef = envs("LEF", "600000000000000000000000000000000000006666666");
            const uint8_t masks[7] = {0, 1, 9, 0x15, 0x1B, 0x1F, 0x3F};
            for (int t = 0; t < kTiles; t++) {
                sched.sef[t] = digit(gaps[t]) + (sef[t] - '0') * 64;
                for (int c = 0; c < 6; c++) sched.tile[0][t].chunk[c] |= (masks[lef[t] - '0'] >> c & 1) * 4;
            }
            sched.gslack = envi("GSLACK", 0), sched.gunit = envi("GUNIT", 73);
            const char* lead = envs("LEAD3", "00000000035798ecekqnmmmnmmmqllnnkkjiihhdcdeee975accc666669acbba24668899996869bcccb8a888a8a666655654466666666666666666626666666666666220");
            sched.pf_from = envi("PFFROM", 24);
            int pos = sched.pf_from;
            sched.tgt[0] = pos;
            for (int e = 0; e < EV * kTiles; e++) {
                const int x = (e + 1) * (6 / EV) + digit(lead[e]);
                if (pos < x) pos = x;
                if (pos > 6 * kTiles) pos = 6 * kTiles;
                sched.tgt[e + 1] = pos;
            }
            sched.pw_ev[0] = envi("PW0", 0) * EV / 6 + 1, sched.pw_ev[1] = envi("PW1", 142) * EV / 6 + 1, sched.pw_div = envi("PWDIV", 4);
            sched.t_a = envi("TA", 0), sched.t_d = envi("TD", 290), sched.t_max = envi("TMAX", 0), sched.fsleep = envi("FSLEEP", 0);
        }
        sched.gate1 = envi("GATE1", 1), sched.psleep = envi("PSLEEP", 20);
        sched.pace_from = envi("PACE_FROM", 15), sched.pace_to = envi("PACE_TO", 45);
        const char* v5 = envs("VTA", "555555555555555555555555553355555555555555555");
        const char* vts[4] = {v5, envs("VTB", v5), envs("VTC", v5), envs("VTD", v5)};
        int total = 0;
        for (int q = 0; q < NPAT; q++) {
            int sum[kTiles + 1] = {};
            for (int t = sched.pace_from; t < sched.pace_to; t++) sum[t] = sum[t - 1] + vts[q][t] - '0';
            total = sum[sched.pace_to - 1];
            for (int t = sched.pace_from; t < sched.pace_to; t++) {
                sched.vt[q][t] = sum[t] * 1024 / total;
                const int slack = digit(envs("SLK", "000000000jhgffrzifmjebc7aa57ca9a884444456577c")[t]) * 8;
                sched.need[q][t] = ncl >= kClusters ? sched.vt[q][t] * sched.members - slack * 5 * 1024 / total * sched.members / 64 : -1;
            }
        }
    }
    CUtensorMap tm_fine, tm_coarse, tm_wlat, tm_wout, tm_out;
    const cuuint32_t ones[5] = {1, 1, 1, 1, 1};
    {
        cuuint64_t dims[5] = {(cuuint64_t)kC, 2, 4, 4, (cuuint64_t)kFinePix / 32};
        cuuint64_t strides[4] = {768, 2 * 768, 8 * 768, 32 * 768};
        cuuint32_t box[5] = {64, 2, 4, 4, 1};
        enc(&tm_fine, CU_TENSOR_MAP_DATA_TYPE_BFLOAT16, 5, d_in[0], dims, strides, box, ones, CU_TENSOR_MAP_INTERLEAVE_NONE,
            CU_TENSOR_MAP_SWIZZLE_128B, CU_TENSOR_MAP_L2_PROMOTION_L2_128B, CU_TENSOR_MAP_FLOAT_OOB_FILL_NONE);
    }
    {
        cuuint64_t dims[3] = {64, (cuuint64_t)kC, 6};
        cuuint64_t strides[2] = {768, 128};
        cuuint32_t box[3] = {64, 16, 6};
        cuuint32_t es[3] = {1, 1, 1};
        enc(&tm_wlat, CU_TENSOR_MAP_DATA_TYPE_BFLOAT16, 3, d_in[2], dims, strides, box, es, CU_TENSOR_MAP_INTERLEAVE_NONE,
            CU_TENSOR_MAP_SWIZZLE_128B, CU_TENSOR_MAP_L2_PROMOTION_L2_256B, CU_TENSOR_MAP_FLOAT_OOB_FILL_NONE);
    }
    encode_2d(enc, &tm_wout, d_in[3], kC, 192, CU_TENSOR_MAP_L2_PROMOTION_L2_256B);
    {
        cuuint64_t dims[4] = {(cuuint64_t)kC, 32, 2, (cuuint64_t)kFinePix / 32 - kRankF};
        cuuint64_t strides[3] = {768, kRankF * 32 * 768, 32 * 768};
        cuuint32_t box[4] = {64, 32, 2, 1};
        enc(&tm_out, CU_TENSOR_MAP_DATA_TYPE_BFLOAT16, 4, d_out, dims, strides, box, ones, CU_TENSOR_MAP_INTERLEAVE_NONE,
            CU_TENSOR_MAP_SWIZZLE_128B, CU_TENSOR_MAP_L2_PROMOTION_NONE, CU_TENSOR_MAP_FLOAT_OOB_FILL_NONE);
    }
    {
        cuuint64_t dims[5] = {(cuuint64_t)kC, 2, 4, kGroup * kSeg / 8, (cuuint64_t)kCoarsePix / (kGroup * kSeg)};
        cuuint64_t strides[4] = {4 * 768, 768, 8 * 768, kGroup * kSeg * 768};
        cuuint32_t box[5] = {64, 2, 4, kSeg / 8, 32 / kSeg};
        enc(&tm_coarse, CU_TENSOR_MAP_DATA_TYPE_BFLOAT16, 5, d_in[1], dims, strides, box, ones, CU_TENSOR_MAP_INTERLEAVE_NONE,
            CU_TENSOR_MAP_SWIZZLE_128B, CU_TENSOR_MAP_L2_PROMOTION_L2_128B, CU_TENSOR_MAP_FLOAT_OOB_FILL_NONE);
    }
    fpn_lateral_kernel<<<2 * kClusters, 512, kSmemBytes>>>(scr, (const char*)d_in[0], (const char*)d_in[1], (const char*)d_in[2], (const char*)d_in[3],
                                                          tm_fine, tm_coarse, tm_wlat, tm_wout, tm_out, sched);
}
```

```cpp
#include <cuda_runtime.h>
#include <cuda_bf16.h>
#include <cuda.h>
#include <stdint.h>
#include <string.h>
#include <type_traits>
#include <stdlib.h>

#define TOKEN_K 3
#define TAKE -2, 0, 2
#define GIVE -4, -2, 0
#define L_POS 0
#define NSTG 6
#define EV 3
#define STPOL 0
#define NO_MMA 0
#define EARLY 1
#define EARLY_T 0
#define W_PRE 0
#define TOPPF 1
#define TLBW 1
#define W_MIX 0x1E
#define WR 1
#define CHAINS 1
#define ROT 0
#define PUBTMA 1
#define DEFER 2
#define INLOOP 1
#define WSPLIT 1
#define TPF_N 0
#define TPF_A 400
#define TPF_D 300
#define FIN 2
#define NPAT 1
#define SHAPE 1
#define OBUF 1
#define LD_EF 1
#define CURVE_REC(k, i) do {} while (0)

#define CREC0(c) do {} while (0)
namespace {

constexpr int kC = 384;
constexpr int kFinePix = 384 * 384;
constexpr int kCoarsePix = 192 * 192;
constexpr int kClusters = 66;
constexpr int kTiles = 44;
constexpr int kFull = 2304 - 34 * kClusters;
constexpr int kVt = 65536 / kClusters;
#define SLOTS (28 - 3 * OBUF)
constexpr int kSlots = SLOTS;
#define GT 1
#define ILV 0
constexpr int kColR = ILV ? 64 : 192, kColG = ILV ? 128 : 64;
constexpr int kChunk = 8192;
constexpr int kTileBytes = 6 * kChunk;
constexpr int kOffOut = kSlots * kChunk;
constexpr int kOffBar = kOffOut + 3 * OBUF * kChunk;
constexpr int kSmemBytes = kOffBar + 1024;
constexpr int kSlotL = kSlots + 3 * OBUF - 20;
constexpr int kSlotW = kSlots + 3 * OBUF - 18;
constexpr int kBarFull = 0, kBarEmpty = 8 * kSlots, kBarStaged = kBarEmpty + 8 * (kSlots + 3), kBarW = kBarStaged + 8 * (kSlots + 3), kBarL = kBarW + 24;
constexpr int kBarPiece = kBarL + 8, kBarReady = kBarPiece + 8;
constexpr int kBarSwap = kBarReady + 8;
constexpr int kBarReady2 = kBarSwap + 56;
constexpr int kStarted = kBarSwap + 192, kAllowed = kStarted + 4;
constexpr int kBarW2 = WSPLIT ? kStarted + 8 : kBarW;
constexpr int kPos0 = 4;
constexpr int kPieces = 24;

enum : uint32_t { F_FINE = 1, F_P = 2, F_Q1 = 4, F_SWAP = 8, F_READY = 16, F_Q2 = 32, F_STAGED = 64, F_SW1 = 128 };
struct alignas(16) Tile {
    uint8_t chunk[7];
    uint8_t flags;
    uint8_t p[3];
    uint8_t pw;
    uint16_t pos;
    uint16_t wcnt;
};
constexpr int kGroup = kClusters / NPAT;
struct Schedule {
    Tile tile[NPAT][kTiles + 1];
    uint16_t tgt[EV * kTiles + 2];
    alignas(8) uint8_t wslot[NPAT][2][3][8];
    uint8_t worder[24];
    uint16_t po[kTiles][4];
    uint32_t fin[2];
    uint16_t gap[48];
    int members, pgroup, gslack, gap_to;
    int pace_from, pace_to, gate1, psleep, pf_from, pw_ev[2], pw_div, t_a, t_d, t_max, fsleep;
    int need[NPAT][kTiles + 1];
    uint16_t vt[NPAT][kTiles + 1];
};
static int envi(const char*, int d) { return d; }
static const char* envs(const char*, const char* d) { return d; }

struct Scratch {
    uint4 wfrag[2][2][3][24][128];
    uint32_t ready, pad0[31];
    uint32_t done, pad1[31];
    uint32_t progress[4][32];
};
__device__ Scratch g_scratch;
#define g_wfrag scr->wfrag
#define g_ready scr->ready
#define g_done scr->done
#define g_progress scr->progress

__device__ __forceinline__ uint32_t smem_u32(const void* p) { return (uint32_t)__cvta_generic_to_shared(p); }

__device__ __forceinline__ void mbar_init(uint32_t bar, uint32_t count) {
    asm volatile("mbarrier.init.shared::cta.b64 [%0], %1;" ::"r"(bar), "r"(count) : "memory");
}
__device__ __forceinline__ void mbar_expect_tx(uint32_t bar, uint32_t bytes) {
    asm volatile("mbarrier.arrive.expect_tx.shared::cta.b64 _, [%0], %1;" ::"r"(bar), "r"(bytes) : "memory");
}
__device__ __forceinline__ void mbar_wait(uint32_t bar, uint32_t parity) {
    asm volatile(
        "{\n"
        ".reg .pred p;\n"
        ".reg .u32 n;\n"
        "mov.u32 n, 0;\n"
        "WAIT_LOOP:\n"
        "mbarrier.try_wait.parity.shared::cta.b64 p, [%0], %1;\n"
        "@p bra WAIT_DONE;\n"
        "add.u32 n, n, 1;\n"
        "setp.lt.u32 p, n, 0x400000;\n"
        "@p bra WAIT_LOOP;\n"
        "trap;\n"
        "WAIT_DONE:\n"
        "}\n" ::"r"(bar), "r"(parity) : "memory");
}
__device__ __forceinline__ void mbar_wait1(uint32_t bar, uint32_t parity) {
    uint32_t r;
    asm volatile("{\n.reg .pred p;\nmbarrier.try_wait.parity.shared::cta.b64 p, [%1], %2;\nselp.u32 %0, 1, 0, p;\n}\n" : "=r"(r) : "r"(bar), "r"(parity) : "memory");
    if (!r) mbar_wait(bar, parity);
}
__device__ __forceinline__ bool mbar_test(uint32_t bar, uint32_t parity) {
    uint32_t r;
    asm volatile("{\n.reg .pred p;\nmbarrier.test_wait.parity.shared::cta.b64 p, [%1], %2;\nselp.u32 %0, 1, 0, p;\n}\n" : "=r"(r) : "r"(bar), "r"(parity) : "memory");
    return r != 0;
}
__device__ __forceinline__ void mbar_arrive(uint32_t bar) {
    asm volatile("mbarrier.arrive.shared::cta.b64 _, [%0];" ::"r"(bar) : "memory");
}
template <int N>
__device__ __forceinline__ void mbar_arrive_cluster(uint32_t bar) {
    if (N == 1) asm volatile("mbarrier.arrive.shared::cluster.b64 _, [%0];" ::"r"(bar) : "memory");
    else asm volatile("mbarrier.arrive.shared::cluster.b64 _, [%0], %1;" ::"r"(bar), "n"(N) : "memory");
}
__device__ __forceinline__ void bulk_load(uint32_t dst, const void* src, uint32_t bar) {
    asm volatile("cp.async.bulk.shared::cluster.global.mbarrier::complete_tx::bytes [%0], [%1], %2, [%3];"
                 ::"r"(dst), "l"(src), "n"(kChunk), "r"(bar) : "memory");
}
__device__ __forceinline__ void tma_load_2d(uint32_t dst, const CUtensorMap* tm, int c0, int c1, uint32_t bar) {
    asm volatile("cp.async.bulk.tensor.2d.shared::cluster.global.mbarrier::complete_tx::bytes [%0], [%1, {%2, %3}], [%4];"
                 ::"r"(dst), "l"(tm), "r"(c0), "r"(c1), "r"(bar) : "memory");
}
__device__ __forceinline__ void tma_load_3d(uint32_t dst, const CUtensorMap* tm, int c1, uint32_t bar) {
    asm volatile("cp.async.bulk.tensor.3d.shared::cluster.global.mbarrier::complete_tx::bytes [%0], [%1, {%2, %3, %2}], [%4];"
                 ::"r"(dst), "l"(tm), "r"(0), "r"(c1), "r"(bar) : "memory");
}
template <bool HINT>
__device__ __forceinline__ void tma_load_5d_mc(uint32_t dst, const CUtensorMap* tm, int c0, int c3, int c4, uint32_t bar, uint64_t pol) {
    if (HINT) asm volatile("cp.async.bulk.tensor.5d.shared::cluster.global.mbarrier::complete_tx::bytes.multicast::cluster.L2::cache_hint [%0], [%1, {%2, %3, %3, %4, %5}], [%6], %7, %8;"
                 ::"r"(dst), "l"(tm), "r"(c0), "r"(0), "r"(c3), "r"(c4), "r"(bar), "h"((uint16_t)3), "l"(pol) : "memory");
    else asm volatile("cp.async.bulk.tensor.5d.shared::cluster.global.mbarrier::complete_tx::bytes.multicast::cluster [%0], [%1, {%2, %3, %3, %4, %5}], [%6], %7;"
                 ::"r"(dst), "l"(tm), "r"(c0), "r"(0), "r"(c3), "r"(c4), "r"(bar), "h"((uint16_t)3) : "memory");
}
__device__ __forceinline__ void tma_store_4d(const CUtensorMap* tm, uint32_t src, int c0, int c3, uint64_t pol) {
    if (STPOL) asm volatile("cp.async.bulk.tensor.4d.global.shared::cta.bulk_group.L2::cache_hint [%0, {%2, %3, %3, %4}], [%1], %5;"
                 ::"l"(tm), "r"(src), "r"(c0), "r"(0), "r"(c3), "l"(pol) : "memory");
    else asm volatile("cp.async.bulk.tensor.4d.global.shared::cta.bulk_group [%0, {%2, %3, %3, %4}], [%1];"
                 ::"l"(tm), "r"(src), "r"(c0), "r"(0), "r"(c3) : "memory");
}
__device__ __forceinline__ void prefetch_l2(const void* p) {
    asm volatile("prefetch.global.L2 [%0];" ::"l"(p) : "memory");
}
__device__ __forceinline__ void prefetch_tm(const CUtensorMap* tm) {
    asm volatile("prefetch.tensormap [%0];" ::"l"(tm) : "memory");
}
__device__ __forceinline__ uint32_t now_ns() {
    uint32_t t;
    asm volatile("mov.u32 %0, %globaltimer_lo;" : "=r"(t));
    return t;
}
__device__ __forceinline__ bool elect_one() {
    uint32_t p;
    asm volatile("{\n.reg .pred p;\nelect.sync _|p, 0xffffffff;\nselp.u32 %0, 1, 0, p;\n}\n" : "=r"(p));
    return p != 0;
}
#define CLUSTER_ARRIVE() asm volatile("barrier.cluster.arrive.relaxed.aligned;" ::: "memory")
#define CLUSTER_WAIT() asm volatile("barrier.cluster.wait.acquire.aligned;" ::: "memory")

#define WG_FENCE() asm volatile("wgmma.fence.sync.aligned;" ::: "memory")
#define WG_COMMIT() asm volatile("wgmma.commit_group.sync.aligned;" ::: "memory")
#define WG_WAIT(n) asm volatile("wgmma.wait_group.sync.aligned %0;" ::"n"(n) : "memory")

#define ACC32 "{%0,%1,%2,%3,%4,%5,%6,%7,%8,%9,%10,%11,%12,%13,%14,%15,%16,%17,%18,%19,%20,%21,%22,%23,%24,%25,%26,%27,%28,%29,%30,%31}"
#define ACC8(b) "+f"(d[b]), "+f"(d[b + 1]), "+f"(d[b + 2]), "+f"(d[b + 3]), "+f"(d[b + 4]), "+f"(d[b + 5]), "+f"(d[b + 6]), "+f"(d[b + 7])

#define DESC_HI "0x40000040"
template <int BOFF>
__device__ __forceinline__ void wgmma_rs(float (&d)[32], const uint32_t* a, uint32_t b_lo) {
    asm volatile("{\n.reg .b32 tb;\n.reg .b64 db;\nadd.u32 tb, %36, %37;\nmov.b64 db, {tb, " DESC_HI "};\n"
                 "wgmma.mma_async.sync.aligned.m64n64k16.f32.bf16.bf16 " ACC32 ", {%32,%33,%34,%35}, db, 1, 1, 1, 0;\n}\n"
                 : ACC8(0), ACC8(8), ACC8(16), ACC8(24)
                 : "r"(a[0]), "r"(a[1]), "r"(a[2]), "r"(a[3]), "r"(b_lo), "n"(BOFF));
}
__device__ __forceinline__ void wgmma_rs_first(float (&d)[32], const uint32_t* a, uint32_t b_lo, uint32_t accum) {
    asm volatile("{\n.reg .pred p;\n.reg .b64 db;\nsetp.ne.u32 p, %37, 0;\nmov.b64 db, {%36, " DESC_HI "};\n"
                 "wgmma.mma_async.sync.aligned.m64n64k16.f32.bf16.bf16 " ACC32 ", {%32,%33,%34,%35}, db, p, 1, 1, 0;\n}\n"
                 : ACC8(0), ACC8(8), ACC8(16), ACC8(24)
                 : "r"(a[0]), "r"(a[1]), "r"(a[2]), "r"(a[3]), "r"(b_lo), "r"(accum));
}
template <int ACCUM, int BOFF, int D>
__device__ __forceinline__ void wgmma_rs16(float (&d)[32], const uint32_t* a, uint32_t b_lo) {
    asm volatile("{\n.reg .b32 tb;\n.reg .b64 db;\nadd.u32 tb, %12, %13;\nmov.b64 db, {tb, " DESC_HI "};\n"
                 "wgmma.mma_async.sync.aligned.m64n16k16.f32.bf16.bf16 {%0,%1,%2,%3,%4,%5,%6,%7}, {%8,%9,%10,%11}, db, %14, 1, 1, 0;\n}\n"
                 : ACC8(D)
                 : "r"(a[0]), "r"(a[1]), "r"(a[2]), "r"(a[3]), "r"(b_lo), "n"(BOFF), "n"(ACCUM));
}
template <int S>
__device__ __forceinline__ void piece_steps(float (&d)[32], const uint32_t (&w)[96], uint32_t b_lo) {
    if constexpr (S < 24) {
        wgmma_rs16<(S >= CHAINS), (S >> 2) * 128 + (S & 3) * 2, S % CHAINS * 8>(d, &w[4 * S], b_lo);
        piece_steps<S + 1>(d, w, b_lo);
    }
}

__device__ __forceinline__ uint32_t pack_bf16(float lo, float hi) {
    uint32_t r;
    asm("cvt.rn.bf16x2.f32 %0, %1, %2;" : "=r"(r) : "f"(hi), "f"(lo));
    return r;
}

template <int C>
__device__ __forceinline__ void reload_w(uint32_t (&w)[96], const char* base, uint32_t tid16, uint32_t on) {
#define W4(i) "+r"(w[16 * C + 4 * i]), "+r"(w[16 * C + 4 * i + 1]), "+r"(w[16 * C + 4 * i + 2]), "+r"(w[16 * C + 4 * i + 3])
    asm volatile("{\n.reg .pred p;\n.reg .b64 a;\nsetp.ne.u32 p, %19, 0;\ncvt.u64.u32 a, %18;\nadd.u64 a, a, %16;\n"
                 "@p ld.global.cg.v4.u32 {%0,%1,%2,%3}, [a + %17];\n"
                 "@p ld.global.cg.v4.u32 {%4,%5,%6,%7}, [a + %17 + 2048];\n"
                 "@p ld.global.cg.v4.u32 {%8,%9,%10,%11}, [a + %17 + 4096];\n"
                 "@p ld.global.cg.v4.u32 {%12,%13,%14,%15}, [a + %17 + 6144];\n}\n"
                 : W4(0), W4(1), W4(2), W4(3)
                 : "l"(base), "n"(C * 8192), "r"(tid16), "r"(on) : "memory");
#undef W4
}

template <int C>
__device__ __forceinline__ uint32_t entry(uint2 e) { return C < 4 ? e.x >> (8 * C) : e.y >> (8 * (C - 4)); }

template <int C>
__device__ __forceinline__ bool issue_chunk(float (&acc)[32], const uint32_t (&w)[96], uint2 e, uint32_t bars, uint32_t b_lo0, bool ready) {
    if (!ready) mbar_wait(bars + kBarFull + (entry<C>(e) & 0xF8), entry<C>(e) & 1);
    const bool next = C < 5 && mbar_test(bars + kBarFull + (entry<C + 1>(e) & 0xF8), entry<C + 1>(e) & 1);
    const uint32_t b_lo = b_lo0 + (entry<C>(e) & 0xF8) * 64;
    if (!NO_MMA) {
        WG_FENCE();
        if (C == 0) wgmma_rs_first(acc, &w[0], b_lo, e.y & (F_FINE << 24));
        else wgmma_rs<0>(acc, &w[16 * C], b_lo);
        wgmma_rs<2>(acc, &w[16 * C + 4], b_lo);
        wgmma_rs<4>(acc, &w[16 * C + 8], b_lo);
        wgmma_rs<6>(acc, &w[16 * C + 12], b_lo);
        WG_COMMIT();
    }
    return next;
}
template <int C, int PENDING, int MODE>
__device__ __forceinline__ void retire_chunk(uint32_t (&w)[96], uint2 e, const uint8_t (*ws)[3][8], int wg, uint32_t sbase, uint32_t rel_bar, bool rel, const char* swap, uint32_t tid16) {
    if (!NO_MMA) WG_WAIT(PENDING);
    if (rel) mbar_arrive_cluster<1>(rel_bar + (entry<C>(e) & 0xF8));
    if (MODE == 1 && C < 6 - DEFER) reload_w<C>(w, swap, tid16, 1);
    if (MODE == 2 && C >= 6 - NSTG) {
        const uint32_t x = ws[e.y >> 31][wg][C];
        mbar_wait(sbase + kOffBar + kBarSwap + 64 * wg + 8 * C, e.y >> 31);
        const uint32_t a = sbase + (x & 0xF8) * 1024 + tid16;
#pragma unroll
        for (int q = 0; q < 4; q++)
            asm volatile("ld.shared.v4.u32 {%0,%1,%2,%3}, [%4];" : "=r"(w[16 * C + 4 * q]), "=r"(w[16 * C + 4 * q + 1]), "=r"(w[16 * C + 4 * q + 2]), "=r"(w[16 * C + 4 * q + 3])
                         : "r"(a + q * 2048) : "memory");
        asm volatile("bar.sync %0, 128;" ::"r"(4 + wg + ((w[16 * C] | w[16 * C + 4] | w[16 * C + 8] | w[16 * C + 12]) & x & 1)) : "memory");
        if (rel) mbar_arrive_cluster<3>(rel_bar + (x & 0xF8));
    }
}

__device__ __forceinline__ int pub_slot(int g) { return g == 0 ? kSlotL + 1 : g == 1 ? kSlotW + 11 : kSlotW + 14; }
__device__ __forceinline__ int fine_group(uint32_t pos, int ci) {
    const uint32_t q = (pos & 0xFFF) + ci;
    return SHAPE ? q + q / 12 * 12 : 2 * q + (q / 6 + ((pos >> 12) & 1)) * 12;
}
constexpr int kRankF = SHAPE ? 12 : 1, kRankC = SHAPE ? 2 : 1, kSeg = SHAPE ? 16 : 32;
template <int L0, int L1>
__device__ __forceinline__ void prefetch_tile(uint32_t pos, int ci, int rank, int lane, const char* fine, const char* coarse) {
    const bool f = pos & 0x8000;
    const uint32_t row = f ? (fine_group(pos, ci) + kRankF * rank) * 32 : (((pos & 0xFFF) + kRankC * rank) * kGroup + ci) * kSeg;
    const char* p = (f ? fine : coarse) + (size_t)row * 768 + lane * 128;
    const char* q = SHAPE && !f ? p + (kGroup - 1) * kSeg * 768 : p;
#pragma unroll
    for (int l = L0; l < L1; l++) prefetch_l2((l < 3 ? p : q) + l * 4096);
}

__global__ void __cluster_dims__(2, 1, 1) __launch_bounds__(512, 1)
fpn_lateral_kernel(Scratch* const scr, const char* __restrict__ fine, const char* __restrict__ coarse,
                   const char* __restrict__ wlat, const char* __restrict__ wout,
                   const __grid_constant__ CUtensorMap tm_fine, const __grid_constant__ CUtensorMap tm_coarse, const __grid_constant__ CUtensorMap tm_coarse2,
                   const __grid_constant__ CUtensorMap tm_wlat, const __grid_constant__ CUtensorMap tm_wout,
                   const __grid_constant__ CUtensorMap tm_out, const __grid_constant__ Schedule sched) {
    extern __shared__ __align__(1024) unsigned char smem_raw[];
    if (threadIdx.x == 0) CURVE_REC(0, 0);
    uint32_t t_start;
    asm volatile("mov.u32 %0, %clock;" : "=r"(t_start));
    const uint32_t sbase = smem_u32(smem_raw);
    const uint32_t bars = sbase + kOffBar;
    const int rot = !ROT ? 0 : blockIdx.x < 4 * kPieces ? blockIdx.x & 2 : 1;
    const int npc = !ROT ? (blockIdx.x < 2 * kPieces ? 3 : 0) : blockIdx.x < 4 * kPieces ? 2 - (rot >> 1) : 0;
    const int pj = blockIdx.x >> (1 + ROT);
    auto slice = [&](int g) { return g + rot >= 3 ? g + rot - 3 : g + rot; };
    if (threadIdx.x == EARLY_T) {
        mbar_init(bars + kBarW, 1);
        if (WSPLIT) mbar_init(bars + kBarW2, 1);
        mbar_init(bars + kBarL, 1);
        asm volatile("fence.proxy.async.shared::cta;" ::: "memory");
        mbar_expect_tx(bars + kBarW, kTileBytes >> WSPLIT);
        if (WSPLIT) mbar_expect_tx(bars + kBarW2, kTileBytes >> WSPLIT);
        for (int c = 0; c < 2; c++) tma_load_2d(sbase + (kSlotW + 3 * c) * kChunk, &tm_wout, (blockIdx.x & 1) * kColR + rot * kColG, c * 192, bars + (c ? kBarW2 : kBarW));
        prefetch_tm(&tm_coarse);
        if (npc) {
            mbar_expect_tx(bars + kBarL, 6 * 2048);
            tma_load_3d(sbase + kSlotL * kChunk, &tm_wlat, pj * 16, bars + kBarL);
        }
        asm volatile("fence.mbarrier_init.release.cluster;" ::: "memory");
        CURVE_REC(1, 47);
    }
    {
        constexpr int kWw = (36 * WR + 31) / 32;
        const uint32_t t = threadIdx.x - 32, b = blockIdx.x, c = (t >> 5) - kWw, l = ((b >> 1) % (64 / WR)) * (36 * WR) + t;
        const uint32_t row = ((kPos0 + kRankC * (b & 1) + ((t >> 4) & 1)) * kGroup + (b >> 1)) * kSeg + (t & 15);
        const char* p = t >= 32 * kWw ? coarse + row * 768 + c * 128 : (b & 1 ? wlat : wout) + l * 128;
        if (t < 36 * WR || c < TOPPF) prefetch_l2(p);
    }
    const int warp_id = __shfl_sync(0xffffffffu, (int)(threadIdx.x >> 5), 0);
    const int lane = threadIdx.x & 31;
    const int wg = warp_id >> 2;
    const int rank = blockIdx.x & 1;
    const int cid = blockIdx.x >> 1;
    const int pat = cid % NPAT, ci = cid / NPAT;
    const Tile* const tiles = sched.tile[pat];

    if (wg == 3) {
        asm volatile("setmaxnreg.dec.sync.aligned.u32 32;");
        const int j = warp_id & 3;
        const bool lead = elect_one();
        if (j == 3) {
            uint32_t c0;
            asm volatile("mov.u32 %0, %clock;" : "=r"(c0));
            if (lead) CURVE_REC(1, 46);
            if (lead) {
                mbar_init(bars + kBarW + 8, 1);
                mbar_init(bars + kBarW + 16, 1);
                if (WSPLIT) mbar_init(bars + kBarW2 + 8, 1), mbar_init(bars + kBarW2 + 16, 1);
                asm volatile("fence.mbarrier_init.release.cluster;" ::: "memory");
                asm volatile("fence.proxy.async.shared::cta;" ::: "memory");
            }
            __syncwarp();
            CLUSTER_ARRIVE();
            if (lead) {
                for (int g = 1; g < 3; g++) {
                    mbar_expect_tx(bars + kBarW + 8 * g, kTileBytes >> WSPLIT);
                    if (WSPLIT) mbar_expect_tx(bars + kBarW2 + 8 * g, kTileBytes >> WSPLIT);
                }
                for (int g = 2; g < 2 + W_PRE; g++) tma_load_2d(sbase + (kSlotW + 3 * g) * kChunk, &tm_wout, rank * kColR + slice(g >> 1) * kColG, (g & 1) * 192, bars + (g & 1 ? kBarW2 : kBarW) + 8 * (g >> 1));
            }
            __syncwarp();
            CLUSTER_WAIT();
            if (lead) {
                int g = 2 + W_PRE;
#pragma unroll 1
                for (int c = 0; c < 6; c++) {
                    mbar_expect_tx(bars + kBarFull + 8 * c, kChunk);
                    tma_load_5d_mc<false>(sbase + rank * 4096 + c * kChunk, &tm_coarse, c * 64, ci * (kSeg / 8), kPos0 + kRankC * rank, bars + kBarFull + 8 * c, 0);
                    CURVE_REC(1, 52 + c);
                    if ((W_MIX >> c & 1) && g < 6) {
                        tma_load_2d(sbase + (kSlotW + 3 * g) * kChunk, &tm_wout, rank * kColR + slice(g >> 1) * kColG, (g & 1) * 192, bars + (g & 1 ? kBarW2 : kBarW) + 8 * (g >> 1));
                        g++;
                    }
                }
#pragma unroll 1
                for (; g < 6; g++) {
                    tma_load_2d(sbase + (kSlotW + 3 * g) * kChunk, &tm_wout, rank * kColR + slice(g >> 1) * kColG, (g & 1) * 192, bars + (g & 1 ? kBarW2 : kBarW) + 8 * (g >> 1));
                    CURVE_REC(1, 47 + (g >> 1));
                }
            }
            __syncwarp();
            uint32_t cur = sched.pf_from, u = 0, pw = sched.pw_ev[0] == 1;
            const char* p = nullptr;
            bool ok = false;
#pragma unroll 1
            for (uint32_t n = 0; cur < 6 * kTiles; n++) {
                uint32_t v;
                asm volatile("ld.volatile.shared.u32 %0, [%1];" : "=r"(v) : "r"(bars + kStarted) : "memory");
                uint32_t tgt = sched.tgt[v];
                if (cur < sched.t_max) {
                    uint32_t c;
                    asm volatile("mov.u32 %0, %clock;" : "=r"(c));
                    if ((int)(c - c0) >= (int)(sched.t_a + cur * sched.t_d)) tgt = max(tgt, cur + 1);
                }
#pragma unroll 1
                for (; cur < tgt; cur++) {
                    if (u == 0) {
                        const uint32_t pos = tiles[cur / 6].pos;
                        const bool f = pos & 0x8000;
                        const uint32_t row = f ? (fine_group(pos, ci) + kRankF * rank) * 32 + lane : (((pos & 0xFFF) + kRankC * rank + (lane >> 4)) * kGroup + ci) * kSeg + (lane & 15);
                        p = (f ? fine : coarse) + (size_t)row * 768;
                        ok = row < (f ? kFinePix : kCoarsePix);
                    }
                    if (ok) prefetch_l2(p);
                    p += 128;
                    u = u == 5 ? 0 : u + 1;
                }
                if (pw < 2 && v >= sched.pw_ev[pw]) {
                    const char* q = (const char*)&g_wfrag[pw][rank][0][0][0] + lane * 128;
#pragma unroll 1
                    for (int l = ci % sched.pw_div; l < 36; l += sched.pw_div) prefetch_l2(q + l * 4096);
                    pw++;
                }
                if (n == 0x1000000) __trap();
                __nanosleep(sched.fsleep);
            }
        } else if (j == 2) {
            if (lead) CURVE_REC(1, 58);
            CLUSTER_ARRIVE();
            if (lead) {
                uint32_t v;
                asm volatile("ld.relaxed.gpu.global.u32 %0, [%1];" : "=r"(v) : "l"(&g_ready) : "memory");
            }
            if (lead) {
                CURVE_REC(1, 59);
                prefetch_tm(&tm_fine);
                prefetch_tm(&tm_coarse2);
                prefetch_tm(&tm_out);
            }
            __syncwarp();
            CLUSTER_WAIT();
            if (lead) {
                if (npc) {
                    mbar_wait(bars + kBarPiece, 0);
                    asm volatile("fence.proxy.async.shared::cta;" ::: "memory");
                    for (int i = 0; i < 2 * npc; i++)
                        asm volatile("cp.async.bulk.global.shared::cta.bulk_group [%0], [%1], 2048;"
                                     ::"l"(&g_wfrag[i & 1][rank][slice(i >> 1)][pj][0]), "r"(sbase + pub_slot(i >> 1) * kChunk + 4096 + (i & 1) * 2048) : "memory");
                    asm volatile("cp.async.bulk.commit_group;" ::: "memory");
                    asm volatile("cp.async.bulk.wait_group.read 0;" ::: "memory");
                    for (int i = 0; i < 2 * npc; i++) {
                        uint32_t b;
                        asm("mapa.shared::cluster.u32 %0, %1, %2;" : "=r"(b) : "r"(bars + kBarEmpty + 8 * pub_slot(i >> 1)), "r"(i & 1));
                        asm volatile("mbarrier.arrive.shared::cluster.b64 _, [%0], %1;" ::"r"(b), "r"(i < 2 ? 1 : 3) : "memory");
                    }
                    asm volatile("cp.async.bulk.wait_group 0;" ::: "memory");
                    asm volatile("red.relaxed.gpu.global.add.u32 [%0], 1;" ::"l"(&g_ready) : "memory");
                    CURVE_REC(2, 61);
                }
                uint32_t v, n = 0;
                for (;;) {
                    asm volatile("ld.acquire.gpu.global.u32 %0, [%1];" : "=r"(v) : "l"(&g_ready) : "memory");
                    if (v >= (2 * kPieces << ROT)) break;
                    if (++n == 0x100000) __trap();
                    __nanosleep(50);
                }
                CURVE_REC(2, 62);
                mbar_arrive(bars + kBarReady);
                asm volatile("fence.proxy.async.global;" ::: "memory");
                mbar_arrive(bars + kBarReady2);
                if (atomicAdd(&g_done, 1) == gridDim.x - 1) {
                    g_ready = 0;
                    g_done = 0;
                }
                asm volatile("st.volatile.shared.u32 [%0], %1;" ::"r"(bars + kAllowed), "r"(rank == 0 || sched.gate1 ? sched.pace_from : kTiles) : "memory");
                if (rank == 0 || sched.gate1) {
                    const uint16_t* vt = sched.vt[pat];
                    uint32_t* const ctr = g_progress[sched.pgroup * pat];
                    const int last = sched.pace_to - 1;
                    asm volatile("ld.relaxed.gpu.global.u32 %0, [%1];" : "=r"(v) : "l"(ctr) : "memory");
                    const uint32_t base = v & ~0xFFFFu;
                    if (blockIdx.x == 0) asm volatile("red.relaxed.gpu.global.add.u32 [%0], %1;" ::"l"(ctr), "r"(65536 - kVt * kClusters) : "memory");
                    int counted = rank == 0 ? sched.pace_from - 1 : last, allowed = sched.pace_from;
#pragma unroll 1
                    for (n = 0; n < 0x10000 && (allowed <= last || counted < last); n++) {
                        int started;
                        asm volatile("ld.volatile.shared.u32 %0, [%1];" : "=r"(started) : "r"(bars + kStarted) : "memory");
                        started = (started + EV - 1) / EV;
                        if (counted < last && counted < started) {
                            const int upto = min(started, last);
                            asm volatile("red.relaxed.gpu.global.add.u32 [%0], %1;" ::"l"(ctr), "r"(vt[upto] - vt[counted]) : "memory");
                            counted = upto;
                        }
                        if (allowed <= last && started + 1 >= allowed) {
                            asm volatile("ld.relaxed.gpu.global.u32 %0, [%1];" : "=r"(v) : "l"(ctr) : "memory");
                            while (allowed <= last && (int)(v - base) >= sched.need[pat][allowed]) allowed++;
                            asm volatile("st.volatile.shared.u32 [%0], %1;" ::"r"(bars + kAllowed), "r"(allowed > last ? kTiles : allowed) : "memory");
                        }
                        __nanosleep(sched.psleep);
                    }
                    asm volatile("st.volatile.shared.u32 [%0], %1;" ::"r"(bars + kAllowed), "r"(kTiles) : "memory");
                    if (counted < last) asm volatile("red.relaxed.gpu.global.add.u32 [%0], %1;" ::"l"(ctr), "r"(vt[last] - vt[counted]) : "memory");
                }
            }
        } else if (j == 1) {
            if (lead) CURVE_REC(3, 51);
            if (sbase & 1023) __trap();
            if (lead) {
                asm volatile("st.shared.u32 [%0], %1;" ::"r"(bars + kStarted), "r"(0) : "memory");
                asm volatile("st.shared.u32 [%0], %1;" ::"r"(bars + kAllowed), "r"(8) : "memory");
                if (kSlots > 24) {
                    mbar_init(bars + kBarFull + 8 * 24, 1);
                    mbar_init(bars + kBarEmpty + 8 * 24, 6);
                }
                mbar_init(bars + kBarPiece, max(4 * npc, 1));
                mbar_init(bars + kBarReady, 1);
                for (int i = 0; i < 3; i++) mbar_init(bars + kBarEmpty + 8 * (kSlots + i), 1);
                for (int i = 24; i < kSlots + 3; i++) mbar_init(bars + kBarStaged + 8 * i, 4);
                asm volatile("fence.acq_rel.cta;" ::: "memory");
                asm volatile("fence.mbarrier_init.release.cluster;" ::: "memory");
                CURVE_REC(3, 52);
            }
            __syncwarp();
            CLUSTER_ARRIVE();
            CLUSTER_WAIT();
            if (lead) {
                const uint32_t t0 = now_ns();
                uint32_t last[3] = {t0, t0, t0}, peer;
                asm("mapa.shared::cluster.u32 %0, %1, %2;" : "=r"(peer) : "r"(bars + kBarEmpty), "r"(rank ^ 1));
                auto release = [&](uint32_t o) {
                    const uint32_t s8 = o & 0xF8;
                    if (s8 >= 8 * kSlots) mbar_arrive(bars + kBarEmpty + s8);
                    else {
                        asm volatile("mbarrier.arrive.shared::cta.b64 _, [%0], 3;" ::"r"(bars + kBarEmpty + s8) : "memory");
                        mbar_arrive_cluster<3>(peer + s8);
                    }
                };
                uint64_t pol_normal = 0;
                if (STPOL) asm volatile("createpolicy.fractional.L2::evict_normal.b64 %0, 1.0;" : "=l"(pol_normal));
#pragma unroll 1
                for (int t = 0; t < kTiles; t++) {
                    const uint32_t pos = tiles[t].pos, gap = sched.gap[t];
                    if (!(pos & 0x8000)) continue;
                    const int row = fine_group(pos, ci);
                    uint32_t prev = 0;
#pragma unroll
                    for (int g = 0; g < 3; g++) {
                        const uint32_t o = sched.po[t][g] >> 8, s8 = o & 0xF8;
                        mbar_wait1(bars + kBarStaged + s8, o & 1);
                        if (g == 2) CURVE_REC(1, t);
                        if (t < sched.gap_to) {
                            uint32_t c;
                            last[g] += gap;
#pragma unroll 1
                            for (int n = 0; n < 4096; n++) {
                                c = now_ns();
                                if ((int)(c - last[g]) >= 0) break;
                                __nanosleep(20);
                            }
                            if ((int)(c - last[g]) > sched.gslack) last[g] = c - sched.gslack;
                        }
                        asm volatile("fence.proxy.async.shared::cta;" ::: "memory");
                        tma_store_4d(&tm_out, sbase + s8 * 1024, rank * kColR + slice(g) * kColG, row, pol_normal);
                        asm volatile("cp.async.bulk.commit_group;" ::: "memory");
                        if (prev & 4) {
                            asm volatile("cp.async.bulk.wait_group.read 1;" ::: "memory");
                            release(prev);
                        }
                        prev = o;
                    }
                    if (prev & 4) {
                        asm volatile("cp.async.bulk.wait_group.read 0;" ::: "memory");
                        release(prev);
                    }
                    CURVE_REC(3, t);
                }
                asm volatile("cp.async.bulk.wait_group.read 0;" ::: "memory");
            }
        } else {
            if (lead) CURVE_REC(1, 50);
            CLUSTER_ARRIVE();
            uint4 e = *(const uint4*)&tiles[1];
            asm volatile("" : "+r"(e.x), "+r"(e.y), "+r"(e.w));
            CLUSTER_WAIT();
            if (lead) CURVE_REC(1, 51);
            if (lead) {
                uint32_t dst0 = sbase + rank * 4096, bar0 = bars;
                asm volatile("" : "+r"(dst0), "+r"(bar0));
                uint32_t wk = 0, wi = 0;
                int allowed = 0;
                uint64_t pol_first, pol_normal;
                asm volatile("createpolicy.fractional.L2::evict_first.b64 %0, 1.0;" : "=l"(pol_first));
                asm volatile("createpolicy.fractional.L2::evict_normal.b64 %0, 1.0;" : "=l"(pol_normal));
#pragma unroll 1
                for (int t = EARLY ? 1 : 0; t < kTiles; t++) {
                    if (t > 1) e = *(const uint4*)&tiles[t];
                    const bool f = e.w & 0x8000;
                    const CUtensorMap* tm = f ? &tm_fine : ci < kFull ? &tm_coarse : &tm_coarse2;
                    const int c3 = f ? 0 : ci * (kSeg / 8), c4 = f ? fine_group(e.w, ci) + kRankF * rank : (e.w & 0xFFF) + kRankC * rank;
                    for (uint32_t n = 0; t >= allowed; n++) {
                        asm volatile("ld.volatile.shared.u32 %0, [%1];" : "=r"(allowed) : "r"(bar0 + kAllowed) : "memory");
                        if (n == 0x4000000) __trap();
                        if (n) __nanosleep(20);
                    }
                    if (t) CURVE_REC(0, t);
#pragma unroll
                    for (int c = 0; c < 6; c++) {
                        if (c % (6 / EV) == 0) asm volatile("st.volatile.shared.u32 [%0], %1;" ::"r"(bar0 + kStarted), "r"(EV * t + 1 + c / (6 / EV)) : "memory");
                        const uint32_t x = c < 4 ? e.x >> (8 * c) : e.y >> (8 * (c - 4)), s8 = x & 0xF8;
                        mbar_wait1(bar0 + kBarEmpty + s8, (x >> 1) & 1);
                        mbar_expect_tx(bar0 + kBarFull + s8, kChunk);
                        tma_load_5d_mc<LD_EF>(dst0 + s8 * 1024, tm, c * 64, c3, c4, bar0 + kBarFull + s8, x & 4 ? pol_first : pol_normal);
#pragma unroll 1
                        for (uint32_t n = (e.w >> (16 + 2 * c)) & 3; n; n--) {
                            if (wk == 0) mbar_wait(bar0 + kBarReady2, 0);
                            const uint32_t o = sched.worder[wk], y = (&sched.wslot[pat][wi][0][0])[o];
                            mbar_wait1(bar0 + kBarEmpty + (y & 0xF8), (y >> 1) & 1);
                            mbar_expect_tx(bar0 + kBarSwap + 8 * o, kChunk);
                            bulk_load(sbase + (y & 0xF8) * 1024, (const char*)&g_wfrag[0][rank][0][0][0] + (6 * slice(o >> 3) + (o & 7)) * kChunk, bar0 + kBarSwap + 8 * o);
                            if (++wk == 3 * NSTG) wk = 0, wi++;
                        }
                    }
                }
            }
        }
        __syncwarp();
    } else {
        if (elect_one()) {
            for (int i = 2 * warp_id; i < 2 * warp_id + 2; i++) {
                mbar_init(bars + kBarSwap + 8 * i, 1);
                if (i >= kSlots) continue;
                mbar_init(bars + kBarFull + 8 * i, 1);
                mbar_init(bars + kBarEmpty + 8 * i, 6);
                mbar_init(bars + kBarStaged + 8 * i, 4);
            }
            asm volatile("fence.mbarrier_init.release.cluster;" ::: "memory");
        }
        __syncwarp();
        CLUSTER_ARRIVE();
        asm volatile("setmaxnreg.inc.sync.aligned.u32 160;");
        const int tid = threadIdx.x & 127;
        const int warp = tid >> 5;
        const bool rel = tid < 2;
        uint32_t rel_bar;
        asm("mapa.shared::cluster.u32 %0, %1, %2;" : "=r"(rel_bar) : "r"(bars + kBarEmpty), "r"(tid & 1));
        const uint32_t b_lo0 = ((sbase & 0x3FFFF) >> 4) | 0x10000u;
        const uint32_t frag_off = ((lane >> 4) * 8 + (lane & 7)) * 128 + (((2 * warp + ((lane >> 3) & 1)) ^ (lane & 7)) << 4);
        uint32_t st_addr = sbase + frag_off, tid16 = tid * 16;
        asm volatile("" : "+r"(st_addr), "+r"(tid16));
        uint4* const wf = &g_wfrag[0][rank][slice(wg)][pj][tid];
        constexpr int kSet = 2 * 3 * 24 * 128;

        float acc[32];
        uint32_t w[96], p[16];

        auto load_w = [&]() {
        mbar_wait(bars + kBarW + 8 * wg, 0);
        if (tid == 0) CURVE_REC(3, 48 + wg);
        const uint32_t w_addr = sbase + (kSlotW + 6 * wg) * kChunk + frag_off;
#pragma unroll
        for (int s = 0; s < 24; s++) {
            if (WSPLIT && s == 12) mbar_wait(bars + kBarW2 + 8 * wg, 0);
            asm volatile("ldmatrix.sync.aligned.m8n8.x4.trans.shared.b16 {%0,%1,%2,%3}, [%4];"
                         : "=r"(w[4 * s]), "=r"(w[4 * s + 1]), "=r"(w[4 * s + 2]), "=r"(w[4 * s + 3]) : "r"(w_addr + s * 2048) : "memory");
        }
        if (wg < npc) {
            asm volatile("ldmatrix.sync.aligned.m8n8.x4.trans.shared.b16 {%0,%1,%2,%3}, [%4];"
                         : "=r"(p[0]), "=r"(p[1]), "=r"(p[2]), "=r"(p[3]) : "r"(w_addr + pj * 2048) : "memory");
            if (!PUBTMA) wf[0] = make_uint4(p[0], p[1], p[2], p[3]);
        }
        asm volatile("bar.sync %0, 128;" ::"r"(4 + wg) : "memory");
        {
            const uint32_t m = (wg == 2 ? 0x3F : 0xFFF) & ~(PUBTMA && wg && wg < npc ? 3u << 2 * (pub_slot(wg) - kSlotW - 6 * wg) : 0u);
            asm volatile("{\n.reg .pred p;\nsetp.ne.u32 p, %1, 0;\n@p mbarrier.arrive.shared::cluster.b64 _, [%0], 3;\n}\n"
                         ::"r"(rel_bar + 8 * (kSlotW + 6 * wg + (tid >> 1))), "r"(tid < 12 ? m >> tid & 1 : 0) : "memory");
        }
        if (threadIdx.x == 0) CURVE_REC(2, 59);
        if (wg < npc) {
            mbar_wait(bars + kBarL, 0);
            if (threadIdx.x == 0) CURVE_REC(3, 61);
            WG_FENCE();
            piece_steps<0>(acc, w, b_lo0 + kSlotL * 512);
            WG_COMMIT();
            WG_WAIT(0);
#pragma unroll
            for (int i = 0; i < 8; i++) {
                asm volatile("" : "+f"(acc[i]), "+f"(acc[8 + i]), "+f"(acc[16 + i]), "+f"(acc[24 + i]));
                if (CHAINS == 2) acc[i] += acc[8 + i];
                if (CHAINS == 4) acc[i] = (acc[i] + acc[8 + i]) + (acc[16 + i] + acc[24 + i]);
            }
            const uint32_t a = sbase + pub_slot(wg) * kChunk + 4096 + tid16;
            asm volatile("st.shared.v4.u32 [%0], {%1,%2,%3,%4};" ::"r"(a), "r"(p[0]), "r"(p[1]), "r"(p[2]), "r"(p[3]) : "memory");
            asm volatile("st.shared.v4.u32 [%0], {%1,%2,%3,%4};" ::"r"(a + 2048), "r"(pack_bf16(acc[0], acc[1])), "r"(pack_bf16(acc[2], acc[3])),
                         "r"(pack_bf16(acc[4], acc[5])), "r"(pack_bf16(acc[6], acc[7])) : "memory");
            __syncwarp();
            if (threadIdx.x == 0) CURVE_REC(3, 62);
            if (lane == 0) mbar_arrive(bars + kBarPiece);
        }
        if (tid < (PUBTMA && wg == 0 && npc ? 2 : 4)) mbar_arrive_cluster<1>(rel_bar + 8 * (kSlotL + (tid >> 1)));
        if (threadIdx.x == 256) CURVE_REC(2, 60);
        };
        if (tid == 0) CURVE_REC(3, 46);
        CLUSTER_WAIT();
        if (tid == 0) CURVE_REC(3, 47);
#pragma unroll
        for (int i = 0; i < 16; i++) p[i] = 0;

        const int tok_in = 1 + wg, tok_out = wg == 2 ? 1 : wg + 2;
#pragma unroll 1
        for (int t = 0; t < kTiles; t++) {
            const uint2 e = *(const uint2*)&tiles[t];
            const uint32_t fl = e.y >> 24, pe = sched.po[t][wg];
            const uint32_t p_addr = sbase + (pe & 0xF8) * 1024 + tid16;
            if ((~fl & (F_FINE | F_P)) == 0) {
#pragma unroll
                for (int q = 0; q < 4; q++)
                    asm volatile("ld.shared.v4.u32 {%0,%1,%2,%3}, [%4];" : "=r"(p[4 * q]), "=r"(p[4 * q + 1]), "=r"(p[4 * q + 2]), "=r"(p[4 * q + 3])
                                 : "r"(p_addr + q * 2048) : "memory");
            }
            const char* swap = (const char*)&g_wfrag[1][rank][slice(wg)][0][0];
            auto init = [&](auto quarter) {
                constexpr int Q = decltype(quarter)::value;
#pragma unroll
                for (int i = 0; i < 8; i++)
                    asm volatile("shl.b32 %0, %4, 16;\nshl.b32 %1, %4, 16;\nand.b32 %2, %4, 0xffff0000;\nand.b32 %3, %4, 0xffff0000;"
                                 : "=f"(acc[4 * i]), "=f"(acc[4 * i + 1]), "=f"(acc[4 * i + 2]), "=f"(acc[4 * i + 3]) : "r"(p[4 * Q + (i & 3)]));
            };
            if (fl & F_FINE) {
                if (fl & F_Q2) {
                    if (fl & F_Q1) init(std::integral_constant<int, 3>());
                    else init(std::integral_constant<int, 2>());
                } else {
                    if (fl & F_Q1) init(std::integral_constant<int, 1>());
                    else {
                        if (DEFER >= 3) reload_w<3>(w, swap, tid16, ~fl & F_P);
                        if (DEFER >= 2) reload_w<4>(w, swap, tid16, ~fl & F_P);
                        if (DEFER >= 1) reload_w<5>(w, swap, tid16, ~fl & F_P);
                        init(std::integral_constant<int, 0>());
                    }
                }
            }
            if (fl & F_READY) {
                if (INLOOP && t == 0) load_w();
                else mbar_wait(bars + kBarReady, 0);
            }
            mbar_wait(bars + kBarFull + (e.x & 0xF8), e.x & 1);
            asm volatile("{\n.reg .pred p;\nsetp.eq.u32 p, %1, 0;\n@p bar.sync %0, 256;\n}\n" ::"r"(tok_in), "r"(pe & 1) : "memory");
            auto body = [&](auto mode) {
                constexpr int M = decltype(mode)::value;
                if (M == 1 && DEFER) asm volatile("{\n.reg .pred p;\nsetp.ne.u32 p, %0, 0;\n@p trap;\n}\n" ::"r"(w[95] & e.y & 0x40000));
                bool rdy = issue_chunk<0>(acc, w, e, bars, b_lo0, true);
                CREC0(0);
                rdy = issue_chunk<1>(acc, w, e, bars, b_lo0, rdy);
                CREC0(1);
                if (TOKEN_K == 2) asm volatile("{\n.reg .pred p;\nsetp.eq.u32 p, %1, 0;\n@p bar.arrive %0, 256;\n}\n" ::"r"(tok_out), "r"(pe & 4) : "memory");
                retire_chunk<0, 1, M>(w, e, sched.wslot[pat], wg, sbase, rel_bar, rel, swap, tid16);
                if (M == 0 && rel && (~fl & (F_FINE | F_P)) == 0) mbar_arrive_cluster<3>(rel_bar + (pe & 0xF8));
                rdy = issue_chunk<2>(acc, w, e, bars, b_lo0, rdy);
                CREC0(2);
                if (TOKEN_K == 3) asm volatile("{\n.reg .pred p;\nsetp.eq.u32 p, %1, 0;\n@p bar.arrive %0, 256;\n}\n" ::"r"(tok_out), "r"(pe & 4) : "memory");
                retire_chunk<1, 1, M>(w, e, sched.wslot[pat], wg, sbase, rel_bar, rel, swap, tid16);
                rdy = issue_chunk<3>(acc, w, e, bars, b_lo0, rdy);
                CREC0(3);
                retire_chunk<2, 1, M>(w, e, sched.wslot[pat], wg, sbase, rel_bar, rel, swap, tid16);
                rdy = issue_chunk<4>(acc, w, e, bars, b_lo0, rdy);
                CREC0(4);
                retire_chunk<3, 1, M>(w, e, sched.wslot[pat], wg, sbase, rel_bar, rel, swap, tid16);
                rdy = issue_chunk<5>(acc, w, e, bars, b_lo0, rdy);
                CREC0(5);
                retire_chunk<4, 1, M>(w, e, sched.wslot[pat], wg, sbase, rel_bar, rel, swap, tid16);
                if (M != 1) mbar_wait(bars + kBarEmpty + (pe >> 11) * 8, (pe >> 9) & 1);
                retire_chunk<5, 0, M>(w, e, sched.wslot[pat], wg, sbase, rel_bar, rel, swap, tid16);
            };
            if (!(fl & F_SWAP)) body(std::integral_constant<int, 0>());
            else if (fl & F_STAGED) body(std::integral_constant<int, 2>());
            else body(std::integral_constant<int, 1>());
            if (fl & F_FINE) {
#pragma unroll
                for (int q = 0; q < 4; q++)
                    asm volatile("stmatrix.sync.aligned.m8n8.x4.trans.shared.b16 [%0], {%1,%2,%3,%4};" ::"r"(st_addr + (pe >> 11) * kChunk + q * 2048),
                                 "r"(pack_bf16(acc[8 * q], acc[8 * q + 1])), "r"(pack_bf16(acc[8 * q + 2], acc[8 * q + 3])),
                                 "r"(pack_bf16(acc[8 * q + 4], acc[8 * q + 5])), "r"(pack_bf16(acc[8 * q + 6], acc[8 * q + 7])) : "memory");
                __syncwarp();
                asm volatile("{\n.reg .pred p;\nelect.sync _|p, 0xffffffff;\n@p mbarrier.arrive.shared::cta.b64 _, [%0];\n}\n" ::"r"(bars + kBarStaged + (pe >> 11) * 8) : "memory");
            } else {
#pragma unroll
                for (int q = 0; q < 4; q++) {
                    p[4 * q] = pack_bf16(acc[8 * q], acc[8 * q + 2]);
                    p[4 * q + 1] = pack_bf16(acc[8 * q + 1], acc[8 * q + 3]);
                    p[4 * q + 2] = pack_bf16(acc[8 * q + 4], acc[8 * q + 6]);
                    p[4 * q + 3] = pack_bf16(acc[8 * q + 5], acc[8 * q + 7]);
                    if (fl & F_P)
                        asm volatile("st.shared.v4.u32 [%0], {%1,%2,%3,%4};" ::"r"(p_addr + q * 2048),
                                     "r"(p[4 * q]), "r"(p[4 * q + 1]), "r"(p[4 * q + 2]), "r"(p[4 * q + 3]) : "memory");
                }
            }
        }
        if (warp_id == 11 && (sched.fin[0] >> lane & 1)) mbar_wait(bars + kBarEmpty + 8 * lane, sched.fin[1] >> lane & 1);
        __syncwarp();
    }
    CLUSTER_ARRIVE();
    CLUSTER_WAIT();
    if (threadIdx.x == 0) CURVE_REC(0, 63);
}

int digit(char ch) { return ch >= 'a' ? ch - 'a' + 10 : ch >= 'A' ? ch - 'A' + 36 : ch - '0'; }
void build_schedule(int pat, Tile* tl, uint16_t (*po)[4], uint32_t* fin, uint8_t (*wslot)[3][8], uint8_t* worder, const int* gs) {
    const char* park = envs("OUT", "000000000000000000000000000000000000000zzzzz");
    uint8_t out[kTiles][3] = {};
    int parked[kSlots] = {}, nth[kTiles][3];
    const int take[3] = {TAKE}, give[3] = {GIVE};
    const int staged = envi("STAGED", 1), wadv = envi("WADV", 0), wrel = envi("WREL", 2), wslack = envi("WSLACK", 0), wmax = envi("WMAX", 3);
    const char* depth = envs("DEPTH", "zzzzzzzzzzzzzzzzzzzzzzzzzzzzzzzzzzzzzzzzzzzz");
    int coarse_of[16];
    int n = 0, nsw = 0, swt[2] = {};
    int units[kTiles];
    auto unit = [&](int t) { return units[t]; };
    for (int g = 0, i0 = 0; gs[g]; i0 += gs[g], g++) {
        for (int i = 1; i <= gs[g]; i++, n++) {
            units[n] = i0 + i % gs[g];
            tl[n].pos = (units[n] * NPAT + pat) * (SHAPE ? 4 : 2);
            tl[n].flags = i < gs[g] ? F_P : F_SWAP | (g == 0 ? F_READY : 0);
            coarse_of[unit(n)] = n;
        }
        for (int i = 0; i < 4 * gs[g] && n < kTiles; i++, n++) {
            units[n] = i0 + i / 4;
            tl[n].pos = 0x8000 + (SHAPE ? ((units[n] * NPAT + pat) * 4 + (i & 3)) * kGroup : ((units[n] * NPAT + pat) * 2 + (i & 3) / 2) * kGroup + (i & 1) * 0x1000);
            tl[n].flags = F_FINE | (i >= 4 && (i & 3) == 0 ? F_P : 0) | (i & 1 ? F_Q1 : 0) | (i & 2 ? F_Q2 : 0);
            if (i == 4 * gs[g] - 1 && gs[g + 1]) {
                tl[n].flags |= staged ? F_SWAP | F_STAGED | (nsw ? F_SW1 : 0) : F_SWAP;
                if (staged) swt[nsw++] = n;
            }
        }
    }
    int nwo = 0;
    for (int need = -4; need < 6; need++)
        for (int g = 0; g < 3; g++) {
            const int c = need - give[g];
            if (c < 6 - NSTG || c > 5) continue;
            worder[nwo++] = g * 8 + c;
            for (int i = 0; i < nsw && !wslack; i++) {
                const int j = 6 * swt[i] + need + 4 - wadv;
                tl[j / 6].wcnt += 1 << (2 * (j % 6));
            }
        }
    int uses[kSlots], loads[kSlots], queue[512], head = 0, tail = 0, slot_of[6 * kTiles];
    for (int s = 0; s < kSlots; s++) uses[s] = s >= kSlotL, loads[s] = 0;
    auto take_p = [&](int t, int w, int s) { tl[t].p[w] = s * 8 + ((uses[s] + 1) & 1) * 2; uses[s]++; };
    bool taken[kSlots] = {};
    for (int w = 0; w < 3; w++)
        if (take[w] < 0 && (tl[0].flags & F_P)) take_p(0, w, kSlotW + 6 * w + 2), taken[kSlotW + 6 * w + 2] = true;
    for (int s = 0; s < kSlotL; s++) queue[tail++] = s;
    for (int s = kSlotW; s < kSlots; s++) if (!taken[s]) queue[tail++] = s;
    for (int s = kSlotL; s < kSlotW; s++) queue[tail++] = s;
    int r = 0, wk = 0, wi = 0;
    int rel[512];
    for (int i = 0; i < tail; i++) rel[i] = -1;
    auto get_slot = [&](int from) {
        for (; r < 6 * kTiles; r++) {
            for (int i = head; i < tail; i++)
                if (rel[i] >= from) {
                    const int s = queue[i];
                    for (; i > head; i--) queue[i] = queue[i - 1], rel[i] = rel[i - 1];
                    head++;
                    return s;
                }
            for (int i = tail; i < tail + 16; i++) rel[i] = r;
            bool to_p = false;
            for (int w = 0; w < 3; w++) {
                int x = r - take[w];
                if (x >= 0 && x % 6 == 0 && x / 6 < kTiles && (tl[x / 6].flags & (F_FINE | F_P)) == F_P) take_p(x / 6, w, slot_of[r]), to_p = true;
                if (x >= 0 && x % 6 == 0 && x / 6 < kTiles && (tl[x / 6].flags & F_FINE) && park[x / 6] != '0') {
                    const int s = slot_of[r];
                    out[x / 6][w] = s * 8 + ((uses[s] + 1) & 1) * 2 + (parked[s] & 1);
                    nth[x / 6][w] = ++uses[s], parked[s]++, to_p = true;
                }
                for (int t = 0; t < kTiles; t++)
                    if ((tl[t].flags & F_FINE) && park[t] != '0' && r == 6 * t + 4 + give[w] + 2 * digit(park[t])) queue[tail++] = out[t][w] >> 3;
            }
            if (!to_p) queue[tail++] = slot_of[r];
            for (int w = 0; w < 3; w++) {
                int x = r - give[w];
                if (x >= 0 && x % 6 == 0 && x / 6 < kTiles && (tl[x / 6].flags & (F_FINE | F_P)) == (F_FINE | F_P)) {
                    tl[x / 6].p[w] = tl[coarse_of[unit(x / 6)]].p[w];
                    queue[tail++] = tl[x / 6].p[w] >> 3;
                }
                x -= wrel;
                if (x >= 0 && x / 6 < kTiles && (tl[x / 6].flags & F_STAGED) && x % 6 >= 6 - NSTG) queue[tail++] = wslot[tl[x / 6].flags >> 7][w][x % 6] >> 3;
            }
        }
        return 0;
    };
    for (int c = 0; c < 6 * kTiles; c++) {
        const char dp = depth[c / 6];
        int s = get_slot(dp == 'z' ? -1 : c - 4 - (dp > '9' ? dp - 'a' + 10 : dp - '0'));
        slot_of[c] = s;
        tl[c / 6].chunk[c % 6] = s * 8 + ((uses[s] + 1) & 1) * 2 + (loads[s] & 1);
        if (c % 6 == 0 && c) tl[c / 6 - 1].chunk[6] = tl[c / 6].chunk[0];
        uses[s]++, loads[s]++;
        for (int k = wslack ? wmax : (tl[c / 6].wcnt >> (2 * (c % 6))) & 3; k; k--) {
            if (wslack) {
                if (wi == nsw || 6 * swt[wi] + (worder[wk] & 7) + give[worder[wk] >> 3] - r > wslack) break;
                tl[c / 6].wcnt += 1 << (2 * (c % 6));
            }
            s = get_slot(-1);
            (&wslot[wi][0][0])[worder[wk]] = s * 8 + ((uses[s] + 1) & 1) * 2;
            uses[s]++;
            if (++wk == 3 * NSTG) wk = 0, wi++;
        }
    }
    get_slot(6 * kTiles);
    fin[0] = (1u << kSlots) - 1, fin[1] = 0;
    for (int s = 0; s < kSlots; s++) fin[1] |= ((uses[s] + 1) & 1) << s;
    for (int t = 0, k = 1; t < kTiles; t++)
        if (!(tl[t].flags & F_FINE)) memcpy(out[t], tl[t].p, 3);
        else if (park[t] == '0') {
            for (int w = 0; w < 3; w++) out[t][w] = (kSlots + w) * 8 + 4 + (k & 1) * 2 + (~k & 1);
            k++;
        } else
            for (int w = 0; w < 3; w++) {
                if (uses[out[t][w] >> 3] > nth[t][w]) out[t][w] |= 4;
                else fin[0] &= ~(1u << (out[t][w] >> 3));
            }
    if (INLOOP) tl[0].flags |= F_READY;
    const char* free_run = envs("NOTOK", "710000000000000000000000000000000000000000071");
    for (int t = 0; t <= kTiles; t++)
        for (int w = 0; w < 3; w++)
            if ((free_run[t] - '0') >> w & 1) {
                tl[t].p[w] |= 1;
                if (w) tl[t].p[w - 1] |= 4;
                else if (t) tl[t - 1].p[2] |= 4;
            }
    for (int t = 0; t < kTiles; t++)
        for (int w = 0; w < 3; w++) po[t][w] = tl[t].p[w] + 256 * out[t][w];
}

typedef CUresult (*EncodeFn)(CUtensorMap*, CUtensorMapDataType, cuuint32_t, void*, const cuuint64_t*, const cuuint64_t*,
                             const cuuint32_t*, const cuuint32_t*, CUtensorMapInterleave, CUtensorMapSwizzle,
                             CUtensorMapL2promotion, CUtensorMapFloatOOBfill);

void encode_2d(EncodeFn enc, CUtensorMap* tm, const void* ptr, uint64_t rows, uint32_t box_rows, CUtensorMapL2promotion promo) {
    cuuint64_t dims[2] = {(cuuint64_t)kC, rows};
    cuuint64_t strides[1] = {(cuuint64_t)kC * 2};
    cuuint32_t box[2] = {64, box_rows};
    cuuint32_t es[2] = {1, 1};
    enc(tm, CU_TENSOR_MAP_DATA_TYPE_BFLOAT16, 2, const_cast<void*>(ptr), dims, strides, box, es, CU_TENSOR_MAP_INTERLEAVE_NONE,
        CU_TENSOR_MAP_SWIZZLE_128B, promo, CU_TENSOR_MAP_FLOAT_OOB_FILL_NONE);
}

}

extern "C" void kernel_launch(void* const* d_in, const int* in_sizes, int n_in, void* d_out, int out_size) {
    (void)in_sizes; (void)n_in; (void)out_size;
    static EncodeFn enc = nullptr;
    static Schedule sched;
    static Scratch* scr;
    if (!enc) {
        cudaGetSymbolAddress((void**)&scr, g_scratch);
        void* fn = nullptr;
        cudaDriverEntryPointQueryResult qr;
        cudaGetDriverEntryPoint("cuTensorMapEncodeTiled", &fn, cudaEnableDefault, &qr);
        enc = (EncodeFn)fn;
        cudaFuncSetAttribute(fpn_lateral_kernel, cudaFuncAttributeMaxDynamicSharedMemorySize, kSmemBytes);
        if (envi("CARVE", 0)) cudaFuncSetAttribute(fpn_lateral_kernel, cudaFuncAttributePreferredSharedMemoryCarveout, envi("CARVE", 0));
        cudaLaunchConfig_t cfg = {};
        cfg.gridDim = dim3(2);
        cfg.blockDim = dim3(512);
        cfg.dynamicSmemBytes = kSmemBytes;
        cudaLaunchAttribute at;
        at.id = cudaLaunchAttributeClusterDimension;
        at.val.clusterDim.x = 2; at.val.clusterDim.y = 1; at.val.clusterDim.z = 1;
        cfg.attrs = &at; cfg.numAttrs = 1;
        int ncl = 0;
        if (cudaOccupancyMaxActiveClusters(&ncl, fpn_lateral_kernel, &cfg) != cudaSuccess) { (void)cudaGetLastError(); ncl = 0; }
        const char* pn[4] = {"PATA", "PATB", "PATC", "PATD"};
        const char* pd[4] = {"45", "45", "36", "63"};
        sched.pgroup = envi("PGROUP", 0), sched.members = sched.pgroup ? kGroup : kClusters;
        for (int q = 0; q < NPAT; q++) {
            int gs[8] = {};
            const char* sa = envs(pn[q], pd[q]);
            for (int i = 0; sa[i]; i++) gs[i] = sa[i] - '0';
            build_schedule(q, sched.tile[q], sched.po, sched.fin, sched.wslot[q], sched.worder, gs);
        }
        {
            const char* gaps = envs("GAPS", "00000lmkonnlnomm000mkkkkk0jru000pklf0iIx0000");
            const char* lef = envs("LEF", "60000000000000000000000000000000026666666666");
            const uint8_t masks[7] = {0, 1, 9, 0x15, 0x1B, 0x1F, 0x3F};
            for (int t = 0; t < kTiles; t++) {
                const int d = digit(gaps[t]);
                sched.gap[t] = (d > 36 ? 3 * d - 72 : d) * envi("GUNIT", 75);
                if (gaps[t] != '0' || envi("GALL", 0)) sched.gap_to = t + 1;
                for (int c = 0; c < 6; c++) sched.tile[0][t].chunk[c] |= (masks[lef[t] - '0'] >> c & 1) * 4;
            }
            sched.gslack = envi("GSLACK", 0);
            const char* lead = envs("LEAD3", "00000000012153dbdpphgminhnmpnnoommgkifjdcefefbdbgeaa8888368cbba78aa88aaa95dc9deeebacaa69ac888878987997756666666666736677666786446245");
            sched.pf_from = envi("PFFROM", 30);
            int pos = sched.pf_from + envi("PF0", 0);
            sched.tgt[0] = pos;
            for (int e = 0; e < EV * kTiles; e++) {
                const int x = (e + 1) * (6 / EV) + digit(lead[e]);
                if (pos < x) pos = x;
                if (pos > 6 * kTiles) pos = 6 * kTiles;
                sched.tgt[e + 1] = pos;
            }
            sched.pw_ev[0] = envi("PW0", 0) * EV / 6 + 1, sched.pw_ev[1] = envi("PW1", 146) * EV / 6 + 1, sched.pw_div = envi("PWDIV", 8);
            sched.t_a = envi("TA", 0), sched.t_d = envi("TD", 290), sched.t_max = envi("TMAX", 0), sched.fsleep = envi("FSLEEP", 40);
        }
        sched.gate1 = envi("GATE1", 1), sched.psleep = envi("PSLEEP", 20);
        sched.pace_from = envi("PACE_FROM", 18), sched.pace_to = envi("PACE_TO", 44);
        const char* v5 = envs("VTA", "55555555555577799666665555322335366655555557");
        const char* vts[4] = {v5, envs("VTB", v5), envs("VTC", v5), envs("VTD", v5)};
        int total = 0;
        for (int q = 0; q < NPAT; q++) {
            int sum[kTiles + 1] = {};
            for (int t = sched.pace_from; t < sched.pace_to; t++) sum[t] = sum[t - 1] + vts[q][t] - '0';
            total = sum[sched.pace_to - 1];
            for (int t = sched.pace_from; t < sched.pace_to; t++) {
                sched.vt[q][t] = sum[t] * kVt / total;
                const int slack = digit(envs("SLK", "000000000jhgfhryijmrdee7cg94gjormeca5454cbbg")[t]) * 8;
                sched.need[q][t] = ncl >= kClusters ? 65536 - kVt * kClusters + sched.vt[q][t] * sched.members - slack * 5 * kVt / total * sched.members / 64 : -1;
            }
        }
    }
    CUtensorMap tm_fine, tm_coarse, tm_coarse2, tm_wlat, tm_wout, tm_out;
    const cuuint32_t ones[5] = {1, 1, 1, 1, 1};
    {
        cuuint64_t dims[5] = {(cuuint64_t)kC, 2, 4, 4, (cuuint64_t)kFinePix / 32};
        cuuint64_t strides[4] = {768, 2 * 768, 8 * 768, 32 * 768};
        cuuint32_t box[5] = {64, 2, 4, 4, 1};
        enc(&tm_fine, CU_TENSOR_MAP_DATA_TYPE_BFLOAT16, 5, d_in[0], dims, strides, box, ones, CU_TENSOR_MAP_INTERLEAVE_NONE,
            CU_TENSOR_MAP_SWIZZLE_128B, CU_TENSOR_MAP_L2_PROMOTION_L2_128B, CU_TENSOR_MAP_FLOAT_OOB_FILL_NONE);
    }
    {
        cuuint64_t dims[3] = {64, (cuuint64_t)kC, 6};
        cuuint64_t strides[2] = {768, 128};
        cuuint32_t box[3] = {64, 16, 6};
        cuuint32_t es[3] = {1, 1, 1};
        enc(&tm_wlat, CU_TENSOR_MAP_DATA_TYPE_BFLOAT16, 3, d_in[2], dims, strides, box, es, CU_TENSOR_MAP_INTERLEAVE_NONE,
            CU_TENSOR_MAP_SWIZZLE_128B, CU_TENSOR_MAP_L2_PROMOTION_L2_256B, CU_TENSOR_MAP_FLOAT_OOB_FILL_NONE);
    }
    encode_2d(enc, &tm_wout, d_in[3], kC, 192, CU_TENSOR_MAP_L2_PROMOTION_L2_256B);
    {
        cuuint64_t dims[4] = {(cuuint64_t)kC, 32, 2, (cuuint64_t)kFinePix / 32 - kRankF};
        cuuint64_t strides[3] = {768, kRankF * 32 * 768, 32 * 768};
        cuuint32_t box[4] = {64, 32, 2, 1};
        enc(&tm_out, CU_TENSOR_MAP_DATA_TYPE_BFLOAT16, 4, d_out, dims, strides, box, ones, CU_TENSOR_MAP_INTERLEAVE_NONE,
            CU_TENSOR_MAP_SWIZZLE_128B, CU_TENSOR_MAP_L2_PROMOTION_NONE, CU_TENSOR_MAP_FLOAT_OOB_FILL_NONE);
    }
    {
        cuuint64_t dims[5] = {(cuuint64_t)kC, 2, 4, kGroup * kSeg / 8, 35};
        cuuint64_t strides[4] = {4 * 768, 768, 8 * 768, kGroup * kSeg * 768};
        cuuint32_t box[5] = {64, 2, 4, kSeg / 8, 32 / kSeg};
        enc(&tm_coarse, CU_TENSOR_MAP_DATA_TYPE_BFLOAT16, 5, d_in[1], dims, strides, box, ones, CU_TENSOR_MAP_INTERLEAVE_NONE,
            CU_TENSOR_MAP_SWIZZLE_128B, CU_TENSOR_MAP_L2_PROMOTION_L2_128B, CU_TENSOR_MAP_FLOAT_OOB_FILL_NONE);
        dims[4] = 34;
        enc(&tm_coarse2, CU_TENSOR_MAP_DATA_TYPE_BFLOAT16, 5, d_in[1], dims, strides, box, ones, CU_TENSOR_MAP_INTERLEAVE_NONE,
            CU_TENSOR_MAP_SWIZZLE_128B, CU_TENSOR_MAP_L2_PROMOTION_L2_128B, CU_TENSOR_MAP_FLOAT_OOB_FILL_NONE);
    }
    fpn_lateral_kernel<<<2 * kClusters, 512, kSmemBytes>>>(scr, (const char*)d_in[0], (const char*)d_in[1], (const char*)d_in[2], (const char*)d_in[3],
                                                          tm_fine, tm_coarse, tm_coarse2, tm_wlat, tm_wout, tm_out, sched);
}
```

```cpp
#include <cuda_runtime.h>
#include <cuda_bf16.h>
#include <cuda.h>
#include <stdint.h>
#include <string.h>
#include <type_traits>
#include <stdlib.h>

#define TOKEN_K 3
#define TAKE -2, 0, 2
#define GIVE -4, -2, 0
#define L_POS 0
#define NSTG 6
#define EV 3
#define STPOL 0
#define NO_MMA 0
#define EARLY 1
#define EARLY_T 0
#define W_PRE 0
#define TOPPF 1
#define TLBW 1
#define W_MIX 0x1E
#define WR 1
#define CHAINS 1
#define ROT 0
#define PUBTMA 1
#define DEFER 2
#define INLOOP 1
#define WSPLIT 1
#define TPF_N 0
#define TPF_A 400
#define TPF_D 300
#define FIN 2
#define NPAT 1
#define SHAPE 1
#define OBUF 1
#define LD_EF 1
#define CURVE_REC(k, i) do {} while (0)

#define CREC0(c) do {} while (0)
namespace {

constexpr int kC = 384;
constexpr int kFinePix = 384 * 384;
constexpr int kCoarsePix = 192 * 192;
constexpr int kClusters = 66;
constexpr int kTiles = 44;
constexpr int kFull = 2304 - 34 * kClusters;
constexpr int kVt = 65536 / kClusters;
#define SLOTS (28 - 3 * OBUF)
constexpr int kSlots = SLOTS;
#define GT 1
#define ILV 0
constexpr int kColR = ILV ? 64 : 192, kColG = ILV ? 128 : 64;
constexpr int kChunk = 8192;
constexpr int kTileBytes = 6 * kChunk;
constexpr int kOffOut = kSlots * kChunk;
constexpr int kOffBar = kOffOut + 3 * OBUF * kChunk;
constexpr int kSmemBytes = kOffBar + 1024;
constexpr int kSlotL = kSlots + 3 * OBUF - 20;
constexpr int kSlotW = kSlots + 3 * OBUF - 18;
constexpr int kBarFull = 0, kBarEmpty = 8 * kSlots, kBarStaged = kBarEmpty + 8 * (kSlots + 3), kBarW = kBarStaged + 8 * (kSlots + 3), kBarL = kBarW + 24;
constexpr int kBarPiece = kBarL + 8, kBarReady = kBarPiece + 8;
constexpr int kBarSwap = kBarReady + 8;
constexpr int kBarReady2 = kBarSwap + 56;
constexpr int kStarted = kBarSwap + 192, kAllowed = kStarted + 4;
constexpr int kBarW2 = WSPLIT ? kStarted + 8 : kBarW;
constexpr int kPos0 = 4;
constexpr int kPieces = 24;

enum : uint32_t { F_FINE = 1, F_P = 2, F_Q1 = 4, F_SWAP = 8, F_READY = 16, F_Q2 = 32, F_STAGED = 64, F_SW1 = 128 };
struct alignas(16) Tile {
    uint8_t chunk[7];
    uint8_t flags;
    uint8_t p[3];
    uint8_t pw;
    uint16_t pos;
    uint16_t wcnt;
};
constexpr int kGroup = kClusters / NPAT;
struct Schedule {
    Tile tile[NPAT][kTiles + 1];
    uint16_t tgt[EV * kTiles + 2];
    alignas(8) uint8_t wslot[NPAT][2][3][8];
    uint8_t worder[24];
    uint16_t po[kTiles][4];
    uint32_t fin[2];
    uint16_t gap[48];
    int members, pgroup, gslack, gap_to, tstag;
    int pace_from, pace_to, gate1, psleep, pf_from, pw_ev[2], pw_div, t_a, t_d, t_max, fsleep;
    int need[NPAT][kTiles + 1];
    uint16_t vt[NPAT][kTiles + 1];
};
static int envi(const char*, int d) { return d; }
static const char* envs(const char*, const char* d) { return d; }

struct Scratch {
    uint4 wfrag[2][2][3][24][128];
    uint32_t ready, pad0[31];
    uint32_t done, pad1[31];
    uint32_t progress[4][32];
};
__device__ Scratch g_scratch;
#define g_wfrag scr->wfrag
#define g_ready scr->ready
#define g_done scr->done
#define g_progress scr->progress

__device__ __forceinline__ uint32_t smem_u32(const void* p) { return (uint32_t)__cvta_generic_to_shared(p); }

__device__ __forceinline__ void mbar_init(uint32_t bar, uint32_t count) {
    asm volatile("mbarrier.init.shared::cta.b64 [%0], %1;" ::"r"(bar), "r"(count) : "memory");
}
__device__ __forceinline__ void mbar_expect_tx(uint32_t bar, uint32_t bytes) {
    asm volatile("mbarrier.arrive.expect_tx.shared::cta.b64 _, [%0], %1;" ::"r"(bar), "r"(bytes) : "memory");
}
__device__ __forceinline__ void mbar_wait(uint32_t bar, uint32_t parity) {
    asm volatile(
        "{\n"
        ".reg .pred p;\n"
        ".reg .u32 n;\n"
        "mov.u32 n, 0;\n"
        "WAIT_LOOP:\n"
        "mbarrier.try_wait.parity.shared::cta.b64 p, [%0], %1;\n"
        "@p bra WAIT_DONE;\n"
        "add.u32 n, n, 1;\n"
        "setp.lt.u32 p, n, 0x400000;\n"
        "@p bra WAIT_LOOP;\n"
        "trap;\n"
        "WAIT_DONE:\n"
        "}\n" ::"r"(bar), "r"(parity) : "memory");
}
__device__ __forceinline__ void mbar_wait1(uint32_t bar, uint32_t parity) {
    uint32_t r;
    asm volatile("{\n.reg .pred p;\nmbarrier.try_wait.parity.shared::cta.b64 p, [%1], %2;\nselp.u32 %0, 1, 0, p;\n}\n" : "=r"(r) : "r"(bar), "r"(parity) : "memory");
    if (!r) mbar_wait(bar, parity);
}
__device__ __forceinline__ bool mbar_test(uint32_t bar, uint32_t parity) {
    uint32_t r;
    asm volatile("{\n.reg .pred p;\nmbarrier.test_wait.parity.shared::cta.b64 p, [%1], %2;\nselp.u32 %0, 1, 0, p;\n}\n" : "=r"(r) : "r"(bar), "r"(parity) : "memory");
    return r != 0;
}
__device__ __forceinline__ void mbar_arrive(uint32_t bar) {
    asm volatile("mbarrier.arrive.shared::cta.b64 _, [%0];" ::"r"(bar) : "memory");
}
template <int N>
__device__ __forceinline__ void mbar_arrive_cluster(uint32_t bar) {
    if (N == 1) asm volatile("mbarrier.arrive.shared::cluster.b64 _, [%0];" ::"r"(bar) : "memory");
    else asm volatile("mbarrier.arrive.shared::cluster.b64 _, [%0], %1;" ::"r"(bar), "n"(N) : "memory");
}
__device__ __forceinline__ void bulk_load(uint32_t dst, const void* src, uint32_t bar) {
    asm volatile("cp.async.bulk.shared::cluster.global.mbarrier::complete_tx::bytes [%0], [%1], %2, [%3];"
                 ::"r"(dst), "l"(src), "n"(kChunk), "r"(bar) : "memory");
}
__device__ __forceinline__ void tma_load_2d(uint32_t dst, const CUtensorMap* tm, int c0, int c1, uint32_t bar) {
    asm volatile("cp.async.bulk.tensor.2d.shared::cluster.global.mbarrier::complete_tx::bytes [%0], [%1, {%2, %3}], [%4];"
                 ::"r"(dst), "l"(tm), "r"(c0), "r"(c1), "r"(bar) : "memory");
}
__device__ __forceinline__ void tma_load_3d(uint32_t dst, const CUtensorMap* tm, int c1, uint32_t bar) {
    asm volatile("cp.async.bulk.tensor.3d.shared::cluster.global.mbarrier::complete_tx::bytes [%0], [%1, {%2, %3, %2}], [%4];"
                 ::"r"(dst), "l"(tm), "r"(0), "r"(c1), "r"(bar) : "memory");
}
template <bool HINT>
__device__ __forceinline__ void tma_load_5d_mc(uint32_t dst, const CUtensorMap* tm, int c0, int c3, int c4, uint32_t bar, uint64_t pol) {
    if (HINT) asm volatile("cp.async.bulk.tensor.5d.shared::cluster.global.mbarrier::complete_tx::bytes.multicast::cluster.L2::cache_hint [%0], [%1, {%2, %3, %3, %4, %5}], [%6], %7, %8;"
                 ::"r"(dst), "l"(tm), "r"(c0), "r"(0), "r"(c3), "r"(c4), "r"(bar), "h"((uint16_t)3), "l"(pol) : "memory");
    else asm volatile("cp.async.bulk.tensor.5d.shared::cluster.global.mbarrier::complete_tx::bytes.multicast::cluster [%0], [%1, {%2, %3, %3, %4, %5}], [%6], %7;"
                 ::"r"(dst), "l"(tm), "r"(c0), "r"(0), "r"(c3), "r"(c4), "r"(bar), "h"((uint16_t)3) : "memory");
}
__device__ __forceinline__ void tma_store_4d(const CUtensorMap* tm, uint32_t src, int c0, int c3, uint64_t pol) {
    if (STPOL) asm volatile("cp.async.bulk.tensor.4d.global.shared::cta.bulk_group.L2::cache_hint [%0, {%2, %3, %3, %4}], [%1], %5;"
                 ::"l"(tm), "r"(src), "r"(c0), "r"(0), "r"(c3), "l"(pol) : "memory");
    else asm volatile("cp.async.bulk.tensor.4d.global.shared::cta.bulk_group [%0, {%2, %3, %3, %4}], [%1];"
                 ::"l"(tm), "r"(src), "r"(c0), "r"(0), "r"(c3) : "memory");
}
__device__ __forceinline__ void prefetch_l2(const void* p) {
    asm volatile("prefetch.global.L2 [%0];" ::"l"(p) : "memory");
}
__device__ __forceinline__ void prefetch_tm(const CUtensorMap* tm) {
    asm volatile("prefetch.tensormap [%0];" ::"l"(tm) : "memory");
}
__device__ __forceinline__ uint32_t now_ns() {
    uint32_t t;
    asm volatile("mov.u32 %0, %globaltimer_lo;" : "=r"(t));
    return t;
}
__device__ __forceinline__ bool elect_one() {
    uint32_t p;
    asm volatile("{\n.reg .pred p;\nelect.sync _|p, 0xffffffff;\nselp.u32 %0, 1, 0, p;\n}\n" : "=r"(p));
    return p != 0;
}
#define CLUSTER_ARRIVE() asm volatile("barrier.cluster.arrive.relaxed.aligned;" ::: "memory")
#define CLUSTER_WAIT() asm volatile("barrier.cluster.wait.acquire.aligned;" ::: "memory")

#define WG_FENCE() asm volatile("wgmma.fence.sync.aligned;" ::: "memory")
#define WG_COMMIT() asm volatile("wgmma.commit_group.sync.aligned;" ::: "memory")
#define WG_WAIT(n) asm volatile("wgmma.wait_group.sync.aligned %0;" ::"n"(n) : "memory")

#define ACC32 "{%0,%1,%2,%3,%4,%5,%6,%7,%8,%9,%10,%11,%12,%13,%14,%15,%16,%17,%18,%19,%20,%21,%22,%23,%24,%25,%26,%27,%28,%29,%30,%31}"
#define ACC8(b) "+f"(d[b]), "+f"(d[b + 1]), "+f"(d[b + 2]), "+f"(d[b + 3]), "+f"(d[b + 4]), "+f"(d[b + 5]), "+f"(d[b + 6]), "+f"(d[b + 7])

#define DESC_HI "0x40000040"
template <int BOFF>
__device__ __forceinline__ void wgmma_rs(float (&d)[32], const uint32_t* a, uint32_t b_lo) {
    asm volatile("{\n.reg .b32 tb;\n.reg .b64 db;\nadd.u32 tb, %36, %37;\nmov.b64 db, {tb, " DESC_HI "};\n"
                 "wgmma.mma_async.sync.aligned.m64n64k16.f32.bf16.bf16 " ACC32 ", {%32,%33,%34,%35}, db, 1, 1, 1, 0;\n}\n"
                 : ACC8(0), ACC8(8), ACC8(16), ACC8(24)
                 : "r"(a[0]), "r"(a[1]), "r"(a[2]), "r"(a[3]), "r"(b_lo), "n"(BOFF));
}
__device__ __forceinline__ void wgmma_rs_first(float (&d)[32], const uint32_t* a, uint32_t b_lo, uint32_t accum) {
    asm volatile("{\n.reg .pred p;\n.reg .b64 db;\nsetp.ne.u32 p, %37, 0;\nmov.b64 db, {%36, " DESC_HI "};\n"
                 "wgmma.mma_async.sync.aligned.m64n64k16.f32.bf16.bf16 " ACC32 ", {%32,%33,%34,%35}, db, p, 1, 1, 0;\n}\n"
                 : ACC8(0), ACC8(8), ACC8(16), ACC8(24)
                 : "r"(a[0]), "r"(a[1]), "r"(a[2]), "r"(a[3]), "r"(b_lo), "r"(accum));
}
template <int ACCUM, int BOFF, int D>
__device__ __forceinline__ void wgmma_rs16(float (&d)[32], const uint32_t* a, uint32_t b_lo) {
    asm volatile("{\n.reg .b32 tb;\n.reg .b64 db;\nadd.u32 tb, %12, %13;\nmov.b64 db, {tb, " DESC_HI "};\n"
                 "wgmma.mma_async.sync.aligned.m64n16k16.f32.bf16.bf16 {%0,%1,%2,%3,%4,%5,%6,%7}, {%8,%9,%10,%11}, db, %14, 1, 1, 0;\n}\n"
                 : ACC8(D)
                 : "r"(a[0]), "r"(a[1]), "r"(a[2]), "r"(a[3]), "r"(b_lo), "n"(BOFF), "n"(ACCUM));
}
template <int S>
__device__ __forceinline__ void piece_steps(float (&d)[32], const uint32_t (&w)[96], uint32_t b_lo) {
    if constexpr (S < 24) {
        wgmma_rs16<(S >= CHAINS), (S >> 2) * 128 + (S & 3) * 2, S % CHAINS * 8>(d, &w[4 * S], b_lo);
        piece_steps<S + 1>(d, w, b_lo);
    }
}

__device__ __forceinline__ uint32_t pack_bf16(float lo, float hi) {
    uint32_t r;
    asm("cvt.rn.bf16x2.f32 %0, %1, %2;" : "=r"(r) : "f"(hi), "f"(lo));
    return r;
}

template <int C>
__device__ __forceinline__ void reload_w(uint32_t (&w)[96], const char* base, uint32_t tid16, uint32_t on) {
#define W4(i) "+r"(w[16 * C + 4 * i]), "+r"(w[16 * C + 4 * i + 1]), "+r"(w[16 * C + 4 * i + 2]), "+r"(w[16 * C + 4 * i + 3])
    asm volatile("{\n.reg .pred p;\n.reg .b64 a;\nsetp.ne.u32 p, %19, 0;\ncvt.u64.u32 a, %18;\nadd.u64 a, a, %16;\n"
                 "@p ld.global.cg.v4.u32 {%0,%1,%2,%3}, [a + %17];\n"
                 "@p ld.global.cg.v4.u32 {%4,%5,%6,%7}, [a + %17 + 2048];\n"
                 "@p ld.global.cg.v4.u32 {%8,%9,%10,%11}, [a + %17 + 4096];\n"
                 "@p ld.global.cg.v4.u32 {%12,%13,%14,%15}, [a + %17 + 6144];\n}\n"
                 : W4(0), W4(1), W4(2), W4(3)
                 : "l"(base), "n"(C * 8192), "r"(tid16), "r"(on) : "memory");
#undef W4
}

template <int C>
__device__ __forceinline__ uint32_t entry(uint2 e) { return C < 4 ? e.x >> (8 * C) : e.y >> (8 * (C - 4)); }

template <int C>
__device__ __forceinline__ bool issue_chunk(float (&acc)[32], const uint32_t (&w)[96], uint2 e, uint32_t bars, uint32_t b_lo0, bool ready) {
    if (!ready) mbar_wait(bars + kBarFull + (entry<C>(e) & 0xF8), entry<C>(e) & 1);
    const bool next = C < 5 && mbar_test(bars + kBarFull + (entry<C + 1>(e) & 0xF8), entry<C + 1>(e) & 1);
    const uint32_t b_lo = b_lo0 + (entry<C>(e) & 0xF8) * 64;
    if (!NO_MMA) {
        WG_FENCE();
        if (C == 0) wgmma_rs_first(acc, &w[0], b_lo, e.y & (F_FINE << 24));
        else wgmma_rs<0>(acc, &w[16 * C], b_lo);
        wgmma_rs<2>(acc, &w[16 * C + 4], b_lo);
        wgmma_rs<4>(acc, &w[16 * C + 8], b_lo);
        wgmma_rs<6>(acc, &w[16 * C + 12], b_lo);
        WG_COMMIT();
    }
    return next;
}
template <int C, int PENDING, int MODE>
__device__ __forceinline__ void retire_chunk(uint32_t (&w)[96], uint2 e, const uint8_t (*ws)[3][8], int wg, uint32_t sbase, uint32_t rel_bar, bool rel, const char* swap, uint32_t tid16) {
    if (!NO_MMA) WG_WAIT(PENDING);
    if (rel) mbar_arrive_cluster<1>(rel_bar + (entry<C>(e) & 0xF8));
    if (MODE == 1 && C < 6 - DEFER) reload_w<C>(w, swap, tid16, 1);
    if (MODE == 2 && C >= 6 - NSTG) {
        const uint32_t x = ws[e.y >> 31][wg][C];
        mbar_wait(sbase + kOffBar + kBarSwap + 64 * wg + 8 * C, e.y >> 31);
        const uint32_t a = sbase + (x & 0xF8) * 1024 + tid16;
#pragma unroll
        for (int q = 0; q < 4; q++)
            asm volatile("ld.shared.v4.u32 {%0,%1,%2,%3}, [%4];" : "=r"(w[16 * C + 4 * q]), "=r"(w[16 * C + 4 * q + 1]), "=r"(w[16 * C + 4 * q + 2]), "=r"(w[16 * C + 4 * q + 3])
                         : "r"(a + q * 2048) : "memory");
        asm volatile("bar.sync %0, 128;" ::"r"(4 + wg + ((w[16 * C] | w[16 * C + 4] | w[16 * C + 8] | w[16 * C + 12]) & x & 1)) : "memory");
        if (rel) mbar_arrive_cluster<3>(rel_bar + (x & 0xF8));
    }
}

__device__ __forceinline__ int pub_slot(int g) { return g == 0 ? kSlotL + 1 : g == 1 ? kSlotW + 11 : kSlotW + 14; }
__device__ __forceinline__ int fine_group(uint32_t pos, int ci) {
    const uint32_t q = (pos & 0xFFF) + ci;
    return SHAPE ? q + q / 12 * 12 : 2 * q + (q / 6 + ((pos >> 12) & 1)) * 12;
}
constexpr int kRankF = SHAPE ? 12 : 1, kRankC = SHAPE ? 2 : 1, kSeg = SHAPE ? 16 : 32;
template <int L0, int L1>
__device__ __forceinline__ void prefetch_tile(uint32_t pos, int ci, int rank, int lane, const char* fine, const char* coarse) {
    const bool f = pos & 0x8000;
    const uint32_t row = f ? (fine_group(pos, ci) + kRankF * rank) * 32 : (((pos & 0xFFF) + kRankC * rank) * kGroup + ci) * kSeg;
    const char* p = (f ? fine : coarse) + (size_t)row * 768 + lane * 128;
    const char* q = SHAPE && !f ? p + (kGroup - 1) * kSeg * 768 : p;
#pragma unroll
    for (int l = L0; l < L1; l++) prefetch_l2((l < 3 ? p : q) + l * 4096);
}

__global__ void __cluster_dims__(2, 1, 1) __launch_bounds__(512, 1)
fpn_lateral_kernel(Scratch* const scr, const char* __restrict__ fine, const char* __restrict__ coarse,
                   const char* __restrict__ wlat, const char* __restrict__ wout,
                   const __grid_constant__ CUtensorMap tm_fine, const __grid_constant__ CUtensorMap tm_coarse, const __grid_constant__ CUtensorMap tm_coarse2,
                   const __grid_constant__ CUtensorMap tm_wlat, const __grid_constant__ CUtensorMap tm_wout,
                   const __grid_constant__ CUtensorMap tm_out, const __grid_constant__ Schedule sched) {
    extern __shared__ __align__(1024) unsigned char smem_raw[];
    if (threadIdx.x == 0) CURVE_REC(0, 0);
    uint32_t t_start;
    asm volatile("mov.u32 %0, %clock;" : "=r"(t_start));
    const uint32_t sbase = smem_u32(smem_raw);
    const uint32_t bars = sbase + kOffBar;
    const int rot = !ROT ? 0 : blockIdx.x < 4 * kPieces ? blockIdx.x & 2 : 1;
    const int npc = !ROT ? (blockIdx.x < 2 * kPieces ? 3 : 0) : blockIdx.x < 4 * kPieces ? 2 - (rot >> 1) : 0;
    const int pj = blockIdx.x >> (1 + ROT);
    auto slice = [&](int g) { return g + rot >= 3 ? g + rot - 3 : g + rot; };
    if (threadIdx.x == EARLY_T) {
        mbar_init(bars + kBarW, 1);
        if (WSPLIT) mbar_init(bars + kBarW2, 1);
        mbar_init(bars + kBarL, 1);
        asm volatile("fence.proxy.async.shared::cta;" ::: "memory");
        mbar_expect_tx(bars + kBarW, kTileBytes >> WSPLIT);
        if (WSPLIT) mbar_expect_tx(bars + kBarW2, kTileBytes >> WSPLIT);
        for (int c = 0; c < 2; c++) tma_load_2d(sbase + (kSlotW + 3 * c) * kChunk, &tm_wout, (blockIdx.x & 1) * kColR + rot * kColG, c * 192, bars + (c ? kBarW2 : kBarW));
        prefetch_tm(&tm_coarse);
        if (npc) {
            mbar_expect_tx(bars + kBarL, 6 * 2048);
            tma_load_3d(sbase + kSlotL * kChunk, &tm_wlat, pj * 16, bars + kBarL);
        }
        asm volatile("fence.mbarrier_init.release.cluster;" ::: "memory");
        CURVE_REC(1, 47);
    }
    {
        constexpr int kWw = (36 * WR + 31) / 32;
        const uint32_t t = threadIdx.x - 32, b = blockIdx.x, c = (t >> 5) - kWw, l = ((b >> 1) % (64 / WR)) * (36 * WR) + t;
        const uint32_t row = ((kPos0 + kRankC * (b & 1) + ((t >> 4) & 1)) * kGroup + (b >> 1)) * kSeg + (t & 15);
        const char* p = t >= 32 * kWw ? coarse + row * 768 + c * 128 : (b & 1 ? wlat : wout) + l * 128;
        if (t < 36 * WR || c < TOPPF) prefetch_l2(p);
    }
    const int warp_id = __shfl_sync(0xffffffffu, (int)(threadIdx.x >> 5), 0);
    const int lane = threadIdx.x & 31;
    const int wg = warp_id >> 2;
    const int rank = blockIdx.x & 1;
    const int cid = blockIdx.x >> 1;
    const int pat = cid % NPAT, ci = cid / NPAT;
    const Tile* const tiles = sched.tile[pat];

    if (wg == 3) {
        asm volatile("setmaxnreg.dec.sync.aligned.u32 32;");
        const int j = warp_id & 3;
        const bool lead = elect_one();
        if (j == 3) {
            uint32_t c0;
            asm volatile("mov.u32 %0, %clock;" : "=r"(c0));
            if (lead) CURVE_REC(1, 46);
            if (lead) {
                mbar_init(bars + kBarW + 8, 1);
                mbar_init(bars + kBarW + 16, 1);
                if (WSPLIT) mbar_init(bars + kBarW2 + 8, 1), mbar_init(bars + kBarW2 + 16, 1);
                asm volatile("fence.mbarrier_init.release.cluster;" ::: "memory");
                asm volatile("fence.proxy.async.shared::cta;" ::: "memory");
            }
            __syncwarp();
            CLUSTER_ARRIVE();
            if (lead) {
                for (int g = 1; g < 3; g++) {
                    mbar_expect_tx(bars + kBarW + 8 * g, kTileBytes >> WSPLIT);
                    if (WSPLIT) mbar_expect_tx(bars + kBarW2 + 8 * g, kTileBytes >> WSPLIT);
                }
                for (int g = 2; g < 2 + W_PRE; g++) tma_load_2d(sbase + (kSlotW + 3 * g) * kChunk, &tm_wout, rank * kColR + slice(g >> 1) * kColG, (g & 1) * 192, bars + (g & 1 ? kBarW2 : kBarW) + 8 * (g >> 1));
            }
            __syncwarp();
            CLUSTER_WAIT();
            if (lead) {
                int g = 2 + W_PRE;
#pragma unroll 1
                for (int c = 0; c < 6; c++) {
                    mbar_expect_tx(bars + kBarFull + 8 * c, kChunk);
                    tma_load_5d_mc<false>(sbase + rank * 4096 + c * kChunk, &tm_coarse, c * 64, ci * (kSeg / 8), kPos0 + kRankC * rank, bars + kBarFull + 8 * c, 0);
                    CURVE_REC(1, 52 + c);
                    if ((W_MIX >> c & 1) && g < 6) {
                        tma_load_2d(sbase + (kSlotW + 3 * g) * kChunk, &tm_wout, rank * kColR + slice(g >> 1) * kColG, (g & 1) * 192, bars + (g & 1 ? kBarW2 : kBarW) + 8 * (g >> 1));
                        g++;
                    }
                }
#pragma unroll 1
                for (; g < 6; g++) {
                    tma_load_2d(sbase + (kSlotW + 3 * g) * kChunk, &tm_wout, rank * kColR + slice(g >> 1) * kColG, (g & 1) * 192, bars + (g & 1 ? kBarW2 : kBarW) + 8 * (g >> 1));
                    CURVE_REC(1, 47 + (g >> 1));
                }
            }
            __syncwarp();
            uint32_t cur = sched.pf_from, u = 0, pw = sched.pw_ev[0] == 1;
            const char* p = nullptr;
            bool ok = false;
#pragma unroll 1
            for (uint32_t n = 0; cur < 6 * kTiles; n++) {
                uint32_t v;
                asm volatile("ld.volatile.shared.u32 %0, [%1];" : "=r"(v) : "r"(bars + kStarted) : "memory");
                uint32_t tgt = sched.tgt[v];
                if (cur < sched.t_max) {
                    uint32_t c;
                    asm volatile("mov.u32 %0, %clock;" : "=r"(c));
                    if ((int)(c - c0) >= (int)(sched.t_a + cur * sched.t_d)) tgt = max(tgt, cur + 1);
                }
#pragma unroll 1
                for (; cur < tgt; cur++) {
                    if (u == 0) {
                        const uint32_t pos = tiles[cur / 6].pos;
                        const bool f = pos & 0x8000;
                        const uint32_t row = f ? (fine_group(pos, ci) + kRankF * rank) * 32 + lane : (((pos & 0xFFF) + kRankC * rank + (lane >> 4)) * kGroup + ci) * kSeg + (lane & 15);
                        p = (f ? fine : coarse) + (size_t)row * 768;
                        ok = row < (f ? kFinePix : kCoarsePix);
                    }
                    if (ok) prefetch_l2(p);
                    p += 128;
                    u = u == 5 ? 0 : u + 1;
                }
                if (pw < 2 && v >= sched.pw_ev[pw]) {
                    const char* q = (const char*)&g_wfrag[pw][rank][0][0][0] + lane * 128;
#pragma unroll 1
                    for (int l = ci % sched.pw_div; l < 36; l += sched.pw_div) prefetch_l2(q + l * 4096);
                    pw++;
                }
                if (n == 0x1000000) __trap();
                __nanosleep(sched.fsleep);
            }
        } else if (j == 2) {
            if (lead) CURVE_REC(1, 58);
            CLUSTER_ARRIVE();
            if (lead) {
                uint32_t v;
                asm volatile("ld.relaxed.gpu.global.u32 %0, [%1];" : "=r"(v) : "l"(&g_ready) : "memory");
            }
            if (lead) {
                CURVE_REC(1, 59);
                prefetch_tm(&tm_fine);
                prefetch_tm(&tm_coarse2);
                prefetch_tm(&tm_out);
            }
            __syncwarp();
            CLUSTER_WAIT();
            if (lead) {
                if (npc) {
                    mbar_wait(bars + kBarPiece, 0);
                    asm volatile("fence.proxy.async.shared::cta;" ::: "memory");
                    for (int i = 0; i < 2 * npc; i++)
                        asm volatile("cp.async.bulk.global.shared::cta.bulk_group [%0], [%1], 2048;"
                                     ::"l"(&g_wfrag[i & 1][rank][slice(i >> 1)][pj][0]), "r"(sbase + pub_slot(i >> 1) * kChunk + 4096 + (i & 1) * 2048) : "memory");
                    asm volatile("cp.async.bulk.commit_group;" ::: "memory");
                    asm volatile("cp.async.bulk.wait_group.read 0;" ::: "memory");
                    for (int i = 0; i < 2 * npc; i++) {
                        uint32_t b;
                        asm("mapa.shared::cluster.u32 %0, %1, %2;" : "=r"(b) : "r"(bars + kBarEmpty + 8 * pub_slot(i >> 1)), "r"(i & 1));
                        asm volatile("mbarrier.arrive.shared::cluster.b64 _, [%0], %1;" ::"r"(b), "r"(i < 2 ? 1 : 3) : "memory");
                    }
                    asm volatile("cp.async.bulk.wait_group 0;" ::: "memory");
                    asm volatile("red.relaxed.gpu.global.add.u32 [%0], 1;" ::"l"(&g_ready) : "memory");
                    CURVE_REC(2, 61);
                }
                uint32_t v, n = 0;
                for (;;) {
                    asm volatile("ld.acquire.gpu.global.u32 %0, [%1];" : "=r"(v) : "l"(&g_ready) : "memory");
                    if (v >= (2 * kPieces << ROT)) break;
                    if (++n == 0x100000) __trap();
                    __nanosleep(50);
                }
                CURVE_REC(2, 62);
                mbar_arrive(bars + kBarReady);
                asm volatile("fence.proxy.async.global;" ::: "memory");
                mbar_arrive(bars + kBarReady2);
                if (atomicAdd(&g_done, 1) == gridDim.x - 1) {
                    g_ready = 0;
                    g_done = 0;
                }
                asm volatile("st.volatile.shared.u32 [%0], %1;" ::"r"(bars + kAllowed), "r"(rank == 0 || sched.gate1 ? sched.pace_from : kTiles) : "memory");
                if (rank == 0 || sched.gate1) {
                    const uint16_t* vt = sched.vt[pat];
                    uint32_t* const ctr = g_progress[sched.pgroup * pat];
                    const int last = sched.pace_to - 1;
                    asm volatile("ld.relaxed.gpu.global.u32 %0, [%1];" : "=r"(v) : "l"(ctr) : "memory");
                    const uint32_t base = v & ~0xFFFFu;
                    if (blockIdx.x == 0) asm volatile("red.relaxed.gpu.global.add.u32 [%0], %1;" ::"l"(ctr), "r"(65536 - kVt * kClusters) : "memory");
                    int counted = rank == 0 ? sched.pace_from - 1 : last, allowed = sched.pace_from;
#pragma unroll 1
                    for (n = 0; n < 0x10000 && (allowed <= last || counted < last); n++) {
                        int started;
                        asm volatile("ld.volatile.shared.u32 %0, [%1];" : "=r"(started) : "r"(bars + kStarted) : "memory");
                        started = (started + EV - 1) / EV;
                        if (counted < last && counted < started) {
                            const int upto = min(started, last);
                            asm volatile("red.relaxed.gpu.global.add.u32 [%0], %1;" ::"l"(ctr), "r"(vt[upto] - vt[counted]) : "memory");
                            counted = upto;
                        }
                        if (allowed <= last && started + 1 >= allowed) {
                            asm volatile("ld.relaxed.gpu.global.u32 %0, [%1];" : "=r"(v) : "l"(ctr) : "memory");
                            while (allowed <= last && (int)(v - base) >= sched.need[pat][allowed]) allowed++;
                            asm volatile("st.volatile.shared.u32 [%0], %1;" ::"r"(bars + kAllowed), "r"(allowed > last ? kTiles : allowed) : "memory");
                        }
                        __nanosleep(sched.psleep);
                    }
                    asm volatile("st.volatile.shared.u32 [%0], %1;" ::"r"(bars + kAllowed), "r"(kTiles) : "memory");
                    if (counted < last) asm volatile("red.relaxed.gpu.global.add.u32 [%0], %1;" ::"l"(ctr), "r"(vt[last] - vt[counted]) : "memory");
                }
            }
        } else if (j == 1) {
            if (lead) CURVE_REC(3, 51);
            if (sbase & 1023) __trap();
            if (lead) {
                asm volatile("st.shared.u32 [%0], %1;" ::"r"(bars + kStarted), "r"(0) : "memory");
                asm volatile("st.shared.u32 [%0], %1;" ::"r"(bars + kAllowed), "r"(8) : "memory");
                if (kSlots > 24) {
                    mbar_init(bars + kBarFull + 8 * 24, 1);
                    mbar_init(bars + kBarEmpty + 8 * 24, 6);
                }
                mbar_init(bars + kBarPiece, max(4 * npc, 1));
                mbar_init(bars + kBarReady, 1);
                for (int i = 0; i < 3; i++) mbar_init(bars + kBarEmpty + 8 * (kSlots + i), 1);
                for (int i = 24; i < kSlots + 3; i++) mbar_init(bars + kBarStaged + 8 * i, 4);
                asm volatile("fence.acq_rel.cta;" ::: "memory");
                asm volatile("fence.mbarrier_init.release.cluster;" ::: "memory");
                CURVE_REC(3, 52);
            }
            __syncwarp();
            CLUSTER_ARRIVE();
            CLUSTER_WAIT();
            if (lead) {
                const uint32_t t0 = now_ns();
                uint32_t last[3] = {t0, t0, t0}, peer;
                asm("mapa.shared::cluster.u32 %0, %1, %2;" : "=r"(peer) : "r"(bars + kBarEmpty), "r"(rank ^ 1));
                auto release = [&](uint32_t o) {
                    const uint32_t s8 = o & 0xF8;
                    if (s8 >= 8 * kSlots) mbar_arrive(bars + kBarEmpty + s8);
                    else {
                        asm volatile("mbarrier.arrive.shared::cta.b64 _, [%0], 3;" ::"r"(bars + kBarEmpty + s8) : "memory");
                        mbar_arrive_cluster<3>(peer + s8);
                    }
                };
                uint64_t pol_normal = 0;
                if (STPOL) asm volatile("createpolicy.fractional.L2::evict_normal.b64 %0, 1.0;" : "=l"(pol_normal));
#pragma unroll 1
                for (int t = 0; t < kTiles; t++) {
                    const uint32_t pos = tiles[t].pos, gap = sched.gap[t];
                    if (!(pos & 0x8000)) continue;
                    const int row = fine_group(pos, ci);
                    uint32_t prev = 0;
                    if (tiles[t].pw) {
#pragma unroll 1
                        for (uint32_t n = 0, v = 0; n < 4096 && v < tiles[t].pw; n++) {
                            __nanosleep(20);
                            asm volatile("ld.volatile.shared.u32 %0, [%1];" : "=r"(v) : "r"(bars + kStarted) : "memory");
                        }
                        const uint32_t c = now_ns();
                        last[0] = c, last[1] = c + sched.tstag, last[2] = c + 2 * sched.tstag;
                    }
#pragma unroll
                    for (int g = 0; g < 3; g++) {
                        const uint32_t o = sched.po[t][g] >> 8, s8 = o & 0xF8;
                        mbar_wait1(bars + kBarStaged + s8, o & 1);
                        if (g == 2) CURVE_REC(1, t);
                        if (t < sched.gap_to) {
                            uint32_t c;
                            last[g] += gap;
#pragma unroll 1
                            for (int n = 0; n < 4096; n++) {
                                c = now_ns();
                                if ((int)(c - last[g]) >= 0) break;
                                __nanosleep(20);
                            }
                            if ((int)(c - last[g]) > sched.gslack) last[g] = c - sched.gslack;
                        }
                        asm volatile("fence.proxy.async.shared::cta;" ::: "memory");
                        tma_store_4d(&tm_out, sbase + s8 * 1024, rank * kColR + slice(g) * kColG, row, pol_normal);
                        asm volatile("cp.async.bulk.commit_group;" ::: "memory");
                        if (prev & 4) {
                            asm volatile("cp.async.bulk.wait_group.read 1;" ::: "memory");
                            release(prev);
                        }
                        prev = o;
                    }
                    if (prev & 4) {
                        asm volatile("cp.async.bulk.wait_group.read 0;" ::: "memory");
                        release(prev);
                    }
                    CURVE_REC(3, t);
                }
                asm volatile("cp.async.bulk.wait_group.read 0;" ::: "memory");
            }
        } else {
            if (lead) CURVE_REC(1, 50);
            CLUSTER_ARRIVE();
            uint4 e = *(const uint4*)&tiles[1];
            asm volatile("" : "+r"(e.x), "+r"(e.y), "+r"(e.w));
            CLUSTER_WAIT();
            if (lead) CURVE_REC(1, 51);
            if (lead) {
                uint32_t dst0 = sbase + rank * 4096, bar0 = bars;
                asm volatile("" : "+r"(dst0), "+r"(bar0));
                uint32_t wk = 0, wi = 0;
                int allowed = 0;
                uint64_t pol_first, pol_normal;
                asm volatile("createpolicy.fractional.L2::evict_first.b64 %0, 1.0;" : "=l"(pol_first));
                asm volatile("createpolicy.fractional.L2::evict_normal.b64 %0, 1.0;" : "=l"(pol_normal));
#pragma unroll 1
                for (int t = EARLY ? 1 : 0; t < kTiles; t++) {
                    if (t > 1) e = *(const uint4*)&tiles[t];
                    const bool f = e.w & 0x8000;
                    const CUtensorMap* tm = f ? &tm_fine : ci < kFull ? &tm_coarse : &tm_coarse2;
                    const int c3 = f ? 0 : ci * (kSeg / 8), c4 = f ? fine_group(e.w, ci) + kRankF * rank : (e.w & 0xFFF) + kRankC * rank;
                    for (uint32_t n = 0; t >= allowed; n++) {
                        asm volatile("ld.volatile.shared.u32 %0, [%1];" : "=r"(allowed) : "r"(bar0 + kAllowed) : "memory");
                        if (n == 0x4000000) __trap();
                        if (n) __nanosleep(20);
                    }
                    if (t) CURVE_REC(0, t);
#pragma unroll
                    for (int c = 0; c < 6; c++) {
                        if (c % (6 / EV) == 0) asm volatile("st.volatile.shared.u32 [%0], %1;" ::"r"(bar0 + kStarted), "r"(EV * t + 1 + c / (6 / EV)) : "memory");
                        const uint32_t x = c < 4 ? e.x >> (8 * c) : e.y >> (8 * (c - 4)), s8 = x & 0xF8;
                        mbar_wait1(bar0 + kBarEmpty + s8, (x >> 1) & 1);
                        mbar_expect_tx(bar0 + kBarFull + s8, kChunk);
                        tma_load_5d_mc<LD_EF>(dst0 + s8 * 1024, tm, c * 64, c3, c4, bar0 + kBarFull + s8, x & 4 ? pol_first : pol_normal);
#pragma unroll 1
                        for (uint32_t n = (e.w >> (16 + 2 * c)) & 3; n; n--) {
                            if (wk == 0) mbar_wait(bar0 + kBarReady2, 0);
                            const uint32_t o = sched.worder[wk], y = (&sched.wslot[pat][wi][0][0])[o];
                            mbar_wait1(bar0 + kBarEmpty + (y & 0xF8), (y >> 1) & 1);
                            mbar_expect_tx(bar0 + kBarSwap + 8 * o, kChunk);
                            bulk_load(sbase + (y & 0xF8) * 1024, (const char*)&g_wfrag[0][rank][0][0][0] + (6 * slice(o >> 3) + (o & 7)) * kChunk, bar0 + kBarSwap + 8 * o);
                            if (++wk == 3 * NSTG) wk = 0, wi++;
                        }
                    }
                }
            }
        }
        __syncwarp();
    } else {
        if (elect_one()) {
            for (int i = 2 * warp_id; i < 2 * warp_id + 2; i++) {
                mbar_init(bars + kBarSwap + 8 * i, 1);
                if (i >= kSlots) continue;
                mbar_init(bars + kBarFull + 8 * i, 1);
                mbar_init(bars + kBarEmpty + 8 * i, 6);
                mbar_init(bars + kBarStaged + 8 * i, 4);
            }
            asm volatile("fence.mbarrier_init.release.cluster;" ::: "memory");
        }
        __syncwarp();
        CLUSTER_ARRIVE();
        asm volatile("setmaxnreg.inc.sync.aligned.u32 160;");
        const int tid = threadIdx.x & 127;
        const int warp = tid >> 5;
        const bool rel = tid < 2;
        uint32_t rel_bar;
        asm("mapa.shared::cluster.u32 %0, %1, %2;" : "=r"(rel_bar) : "r"(bars + kBarEmpty), "r"(tid & 1));
        const uint32_t b_lo0 = ((sbase & 0x3FFFF) >> 4) | 0x10000u;
        const uint32_t frag_off = ((lane >> 4) * 8 + (lane & 7)) * 128 + (((2 * warp + ((lane >> 3) & 1)) ^ (lane & 7)) << 4);
        uint32_t st_addr = sbase + frag_off, tid16 = tid * 16;
        asm volatile("" : "+r"(st_addr), "+r"(tid16));
        uint4* const wf = &g_wfrag[0][rank][slice(wg)][pj][tid];
        constexpr int kSet = 2 * 3 * 24 * 128;

        float acc[32];
        uint32_t w[96], p[16];

        auto load_w = [&]() {
        mbar_wait(bars + kBarW + 8 * wg, 0);
        if (tid == 0) CURVE_REC(3, 48 + wg);
        const uint32_t w_addr = sbase + (kSlotW + 6 * wg) * kChunk + frag_off;
#pragma unroll
        for (int s = 0; s < 24; s++) {
            if (WSPLIT && s == 12) mbar_wait(bars + kBarW2 + 8 * wg, 0);
            asm volatile("ldmatrix.sync.aligned.m8n8.x4.trans.shared.b16 {%0,%1,%2,%3}, [%4];"
                         : "=r"(w[4 * s]), "=r"(w[4 * s + 1]), "=r"(w[4 * s + 2]), "=r"(w[4 * s + 3]) : "r"(w_addr + s * 2048) : "memory");
        }
        if (wg < npc) {
            asm volatile("ldmatrix.sync.aligned.m8n8.x4.trans.shared.b16 {%0,%1,%2,%3}, [%4];"
                         : "=r"(p[0]), "=r"(p[1]), "=r"(p[2]), "=r"(p[3]) : "r"(w_addr + pj * 2048) : "memory");
            if (!PUBTMA) wf[0] = make_uint4(p[0], p[1], p[2], p[3]);
        }
        asm volatile("bar.sync %0, 128;" ::"r"(4 + wg) : "memory");
        {
            const uint32_t m = (wg == 2 ? 0x3F : 0xFFF) & ~(PUBTMA && wg && wg < npc ? 3u << 2 * (pub_slot(wg) - kSlotW - 6 * wg) : 0u);
            asm volatile("{\n.reg .pred p;\nsetp.ne.u32 p, %1, 0;\n@p mbarrier.arrive.shared::cluster.b64 _, [%0], 3;\n}\n"
                         ::"r"(rel_bar + 8 * (kSlotW + 6 * wg + (tid >> 1))), "r"(tid < 12 ? m >> tid & 1 : 0) : "memory");
        }
        if (threadIdx.x == 0) CURVE_REC(2, 59);
        if (wg < npc) {
            mbar_wait(bars + kBarL, 0);
            if (threadIdx.x == 0) CURVE_REC(3, 61);
            WG_FENCE();
            piece_steps<0>(acc, w, b_lo0 + kSlotL * 512);
            WG_COMMIT();
            WG_WAIT(0);
#pragma unroll
            for (int i = 0; i < 8; i++) {
                asm volatile("" : "+f"(acc[i]), "+f"(acc[8 + i]), "+f"(acc[16 + i]), "+f"(acc[24 + i]));
                if (CHAINS == 2) acc[i] += acc[8 + i];
                if (CHAINS == 4) acc[i] = (acc[i] + acc[8 + i]) + (acc[16 + i] + acc[24 + i]);
            }
            const uint32_t a = sbase + pub_slot(wg) * kChunk + 4096 + tid16;
            asm volatile("st.shared.v4.u32 [%0], {%1,%2,%3,%4};" ::"r"(a), "r"(p[0]), "r"(p[1]), "r"(p[2]), "r"(p[3]) : "memory");
            asm volatile("st.shared.v4.u32 [%0], {%1,%2,%3,%4};" ::"r"(a + 2048), "r"(pack_bf16(acc[0], acc[1])), "r"(pack_bf16(acc[2], acc[3])),
                         "r"(pack_bf16(acc[4], acc[5])), "r"(pack_bf16(acc[6], acc[7])) : "memory");
            __syncwarp();
            if (threadIdx.x == 0) CURVE_REC(3, 62);
            if (lane == 0) mbar_arrive(bars + kBarPiece);
        }
        if (tid < (PUBTMA && wg == 0 && npc ? 2 : 4)) mbar_arrive_cluster<1>(rel_bar + 8 * (kSlotL + (tid >> 1)));
        if (threadIdx.x == 256) CURVE_REC(2, 60);
        };
        if (tid == 0) CURVE_REC(3, 46);
        CLUSTER_WAIT();
        if (tid == 0) CURVE_REC(3, 47);
#pragma unroll
        for (int i = 0; i < 16; i++) p[i] = 0;

        const int tok_in = 1 + wg, tok_out = wg == 2 ? 1 : wg + 2;
#pragma unroll 1
        for (int t = 0; t < kTiles; t++) {
            const uint2 e = *(const uint2*)&tiles[t];
            const uint32_t fl = e.y >> 24, pe = sched.po[t][wg];
            const uint32_t p_addr = sbase + (pe & 0xF8) * 1024 + tid16;
            if ((~fl & (F_FINE | F_P)) == 0) {
#pragma unroll
                for (int q = 0; q < 4; q++)
                    asm volatile("ld.shared.v4.u32 {%0,%1,%2,%3}, [%4];" : "=r"(p[4 * q]), "=r"(p[4 * q + 1]), "=r"(p[4 * q + 2]), "=r"(p[4 * q + 3])
                                 : "r"(p_addr + q * 2048) : "memory");
            }
            const char* swap = (const char*)&g_wfrag[1][rank][slice(wg)][0][0];
            auto init = [&](auto quarter) {
                constexpr int Q = decltype(quarter)::value;
#pragma unroll
                for (int i = 0; i < 8; i++)
                    asm volatile("shl.b32 %0, %4, 16;\nshl.b32 %1, %4, 16;\nand.b32 %2, %4, 0xffff0000;\nand.b32 %3, %4, 0xffff0000;"
                                 : "=f"(acc[4 * i]), "=f"(acc[4 * i + 1]), "=f"(acc[4 * i + 2]), "=f"(acc[4 * i + 3]) : "r"(p[4 * Q + (i & 3)]));
            };
            if (fl & F_FINE) {
                if (fl & F_Q2) {
                    if (fl & F_Q1) init(std::integral_constant<int, 3>());
                    else init(std::integral_constant<int, 2>());
                } else {
                    if (fl & F_Q1) init(std::integral_constant<int, 1>());
                    else {
                        if (DEFER >= 3) reload_w<3>(w, swap, tid16, ~fl & F_P);
                        if (DEFER >= 2) reload_w<4>(w, swap, tid16, ~fl & F_P);
                        if (DEFER >= 1) reload_w<5>(w, swap, tid16, ~fl & F_P);
                        init(std::integral_constant<int, 0>());
                    }
                }
            }
            if (fl & F_READY) {
                if (INLOOP && t == 0) load_w();
                else mbar_wait(bars + kBarReady, 0);
            }
            mbar_wait(bars + kBarFull + (e.x & 0xF8), e.x & 1);
            asm volatile("{\n.reg .pred p;\nsetp.eq.u32 p, %1, 0;\n@p bar.sync %0, 256;\n}\n" ::"r"(tok_in), "r"(pe & 1) : "memory");
            auto body = [&](auto mode) {
                constexpr int M = decltype(mode)::value;
                if (M == 1 && DEFER) asm volatile("{\n.reg .pred p;\nsetp.ne.u32 p, %0, 0;\n@p trap;\n}\n" ::"r"(w[95] & e.y & 0x40000));
                bool rdy = issue_chunk<0>(acc, w, e, bars, b_lo0, true);
                CREC0(0);
                rdy = issue_chunk<1>(acc, w, e, bars, b_lo0, rdy);
                CREC0(1);
                if (TOKEN_K == 2) asm volatile("{\n.reg .pred p;\nsetp.eq.u32 p, %1, 0;\n@p bar.arrive %0, 256;\n}\n" ::"r"(tok_out), "r"(pe & 4) : "memory");
                retire_chunk<0, 1, M>(w, e, sched.wslot[pat], wg, sbase, rel_bar, rel, swap, tid16);
                if (M == 0 && rel && (~fl & (F_FINE | F_P)) == 0) mbar_arrive_cluster<3>(rel_bar + (pe & 0xF8));
                rdy = issue_chunk<2>(acc, w, e, bars, b_lo0, rdy);
                CREC0(2);
                if (TOKEN_K == 3) asm volatile("{\n.reg .pred p;\nsetp.eq.u32 p, %1, 0;\n@p bar.arrive %0, 256;\n}\n" ::"r"(tok_out), "r"(pe & 4) : "memory");
                retire_chunk<1, 1, M>(w, e, sched.wslot[pat], wg, sbase, rel_bar, rel, swap, tid16);
                rdy = issue_chunk<3>(acc, w, e, bars, b_lo0, rdy);
                CREC0(3);
                retire_chunk<2, 1, M>(w, e, sched.wslot[pat], wg, sbase, rel_bar, rel, swap, tid16);
                rdy = issue_chunk<4>(acc, w, e, bars, b_lo0, rdy);
                CREC0(4);
                retire_chunk<3, 1, M>(w, e, sched.wslot[pat], wg, sbase, rel_bar, rel, swap, tid16);
                rdy = issue_chunk<5>(acc, w, e, bars, b_lo0, rdy);
                CREC0(5);
                retire_chunk<4, 1, M>(w, e, sched.wslot[pat], wg, sbase, rel_bar, rel, swap, tid16);
                if (M != 1) mbar_wait(bars + kBarEmpty + (pe >> 11) * 8, (pe >> 9) & 1);
                retire_chunk<5, 0, M>(w, e, sched.wslot[pat], wg, sbase, rel_bar, rel, swap, tid16);
            };
            if (!(fl & F_SWAP)) body(std::integral_constant<int, 0>());
            else if (fl & F_STAGED) body(std::integral_constant<int, 2>());
            else body(std::integral_constant<int, 1>());
            if (fl & F_FINE) {
#pragma unroll
                for (int q = 0; q < 4; q++)
                    asm volatile("stmatrix.sync.aligned.m8n8.x4.trans.shared.b16 [%0], {%1,%2,%3,%4};" ::"r"(st_addr + (pe >> 11) * kChunk + q * 2048),
                                 "r"(pack_bf16(acc[8 * q], acc[8 * q + 1])), "r"(pack_bf16(acc[8 * q + 2], acc[8 * q + 3])),
                                 "r"(pack_bf16(acc[8 * q + 4], acc[8 * q + 5])), "r"(pack_bf16(acc[8 * q + 6], acc[8 * q + 7])) : "memory");
                __syncwarp();
                asm volatile("{\n.reg .pred p;\nelect.sync _|p, 0xffffffff;\n@p mbarrier.arrive.shared::cta.b64 _, [%0];\n}\n" ::"r"(bars + kBarStaged + (pe >> 11) * 8) : "memory");
            } else {
#pragma unroll
                for (int q = 0; q < 4; q++) {
                    p[4 * q] = pack_bf16(acc[8 * q], acc[8 * q + 2]);
                    p[4 * q + 1] = pack_bf16(acc[8 * q + 1], acc[8 * q + 3]);
                    p[4 * q + 2] = pack_bf16(acc[8 * q + 4], acc[8 * q + 6]);
                    p[4 * q + 3] = pack_bf16(acc[8 * q + 5], acc[8 * q + 7]);
                    if (fl & F_P)
                        asm volatile("st.shared.v4.u32 [%0], {%1,%2,%3,%4};" ::"r"(p_addr + q * 2048),
                                     "r"(p[4 * q]), "r"(p[4 * q + 1]), "r"(p[4 * q + 2]), "r"(p[4 * q + 3]) : "memory");
                }
            }
        }
        if (warp_id == 11 && (sched.fin[0] >> lane & 1)) mbar_wait(bars + kBarEmpty + 8 * lane, sched.fin[1] >> lane & 1);
        __syncwarp();
    }
    CLUSTER_ARRIVE();
    CLUSTER_WAIT();
    if (threadIdx.x == 0) CURVE_REC(0, 63);
}

int digit(char ch) { return ch >= 'a' ? ch - 'a' + 10 : ch >= 'A' ? ch - 'A' + 36 : ch - '0'; }
void build_schedule(int pat, Tile* tl, uint16_t (*po)[4], uint32_t* fin, uint8_t (*wslot)[3][8], uint8_t* worder, const int* gs) {
    const char* park = envs("OUT", "000000000000000000000000000000000000000zzzzz");
    uint8_t out[kTiles][3] = {};
    int parked[kSlots] = {}, nth[kTiles][3];
    const int take[3] = {TAKE}, give[3] = {GIVE};
    const int staged = envi("STAGED", 1), wadv = envi("WADV", 0), wrel = envi("WREL", 1), wslack = envi("WSLACK", 0), wmax = envi("WMAX", 3);
    const char* depth = envs("DEPTH", "zzzzzzzzzzzzzzzzzzzzzzzzzzzzzzzzzzzzzzzzzzzz");
    int coarse_of[16];
    int n = 0, nsw = 0, swt[2] = {};
    int units[kTiles];
    auto unit = [&](int t) { return units[t]; };
    for (int g = 0, i0 = 0; gs[g]; i0 += gs[g], g++) {
        for (int i = 1; i <= gs[g]; i++, n++) {
            units[n] = i0 + i % gs[g];
            tl[n].pos = (units[n] * NPAT + pat) * (SHAPE ? 4 : 2);
            tl[n].flags = i < gs[g] ? F_P : F_SWAP | (g == 0 ? F_READY : 0);
            coarse_of[unit(n)] = n;
        }
        for (int i = 0; i < 4 * gs[g] && n < kTiles; i++, n++) {
            units[n] = i0 + i / 4;
            tl[n].pos = 0x8000 + (SHAPE ? ((units[n] * NPAT + pat) * 4 + (i & 3)) * kGroup : ((units[n] * NPAT + pat) * 2 + (i & 3) / 2) * kGroup + (i & 1) * 0x1000);
            tl[n].flags = F_FINE | (i >= 4 && (i & 3) == 0 ? F_P : 0) | (i & 1 ? F_Q1 : 0) | (i & 2 ? F_Q2 : 0);
            if (i == 4 * gs[g] - 1 && gs[g + 1]) {
                tl[n].flags |= staged ? F_SWAP | F_STAGED | (nsw ? F_SW1 : 0) : F_SWAP;
                if (staged) swt[nsw++] = n;
            }
        }
    }
    int nwo = 0;
    for (int need = -4; need < 6; need++)
        for (int g = 0; g < 3; g++) {
            const int c = need - give[g];
            if (c < 6 - NSTG || c > 5) continue;
            worder[nwo++] = g * 8 + c;
            for (int i = 0; i < nsw && !wslack; i++) {
                const int j = 6 * swt[i] + need + 4 - wadv;
                tl[j / 6].wcnt += 1 << (2 * (j % 6));
            }
        }
    int uses[kSlots], loads[kSlots], queue[512], head = 0, tail = 0, slot_of[6 * kTiles];
    for (int s = 0; s < kSlots; s++) uses[s] = s >= kSlotL, loads[s] = 0;
    auto take_p = [&](int t, int w, int s) { tl[t].p[w] = s * 8 + ((uses[s] + 1) & 1) * 2; uses[s]++; };
    bool taken[kSlots] = {};
    for (int w = 0; w < 3; w++)
        if (take[w] < 0 && (tl[0].flags & F_P)) take_p(0, w, kSlotW + 6 * w + 2), taken[kSlotW + 6 * w + 2] = true;
    for (int s = 0; s < kSlotL; s++) queue[tail++] = s;
    for (int s = kSlotW; s < kSlots; s++) if (!taken[s]) queue[tail++] = s;
    for (int s = kSlotL; s < kSlotW; s++) queue[tail++] = s;
    int r = 0, wk = 0, wi = 0;
    int rel[512];
    for (int i = 0; i < tail; i++) rel[i] = -1;
    auto get_slot = [&](int from) {
        for (; r < 6 * kTiles; r++) {
            for (int i = head; i < tail; i++)
                if (rel[i] >= from) {
                    const int s = queue[i];
                    for (; i > head; i--) queue[i] = queue[i - 1], rel[i] = rel[i - 1];
                    head++;
                    return s;
                }
            for (int i = tail; i < tail + 16; i++) rel[i] = r;
            bool to_p = false;
            for (int w = 0; w < 3; w++) {
                int x = r - take[w];
                if (x >= 0 && x % 6 == 0 && x / 6 < kTiles && (tl[x / 6].flags & (F_FINE | F_P)) == F_P) take_p(x / 6, w, slot_of[r]), to_p = true;
                if (x >= 0 && x % 6 == 0 && x / 6 < kTiles && (tl[x / 6].flags & F_FINE) && park[x / 6] != '0') {
                    const int s = slot_of[r];
                    out[x / 6][w] = s * 8 + ((uses[s] + 1) & 1) * 2 + (parked[s] & 1);
                    nth[x / 6][w] = ++uses[s], parked[s]++, to_p = true;
                }
                for (int t = 0; t < kTiles; t++)
                    if ((tl[t].flags & F_FINE) && park[t] != '0' && r == 6 * t + 4 + give[w] + 2 * digit(park[t])) queue[tail++] = out[t][w] >> 3;
            }
            if (!to_p) queue[tail++] = slot_of[r];
            for (int w = 0; w < 3; w++) {
                int x = r - give[w];
                if (x >= 0 && x % 6 == 0 && x / 6 < kTiles && (tl[x / 6].flags & (F_FINE | F_P)) == (F_FINE | F_P)) {
                    tl[x / 6].p[w] = tl[coarse_of[unit(x / 6)]].p[w];
                    queue[tail++] = tl[x / 6].p[w] >> 3;
                }
                x -= wrel;
                if (x >= 0 && x / 6 < kTiles && (tl[x / 6].flags & F_STAGED) && x % 6 >= 6 - NSTG) queue[tail++] = wslot[tl[x / 6].flags >> 7][w][x % 6] >> 3;
            }
        }
        return 0;
    };
    for (int c = 0; c < 6 * kTiles; c++) {
        const char dp = depth[c / 6];
        int s = get_slot(dp == 'z' ? -1 : c - 4 - (dp > '9' ? dp - 'a' + 10 : dp - '0'));
        slot_of[c] = s;
        tl[c / 6].chunk[c % 6] = s * 8 + ((uses[s] + 1) & 1) * 2 + (loads[s] & 1);
        if (c % 6 == 0 && c) tl[c / 6 - 1].chunk[6] = tl[c / 6].chunk[0];
        uses[s]++, loads[s]++;
        for (int k = wslack ? wmax : (tl[c / 6].wcnt >> (2 * (c % 6))) & 3; k; k--) {
            if (wslack) {
                if (wi == nsw || 6 * swt[wi] + (worder[wk] & 7) + give[worder[wk] >> 3] - r > wslack) break;
                tl[c / 6].wcnt += 1 << (2 * (c % 6));
            }
            s = get_slot(-1);
            (&wslot[wi][0][0])[worder[wk]] = s * 8 + ((uses[s] + 1) & 1) * 2;
            uses[s]++;
            if (++wk == 3 * NSTG) wk = 0, wi++;
        }
    }
    get_slot(6 * kTiles);
    fin[0] = (1u << kSlots) - 1, fin[1] = 0;
    for (int s = 0; s < kSlots; s++) fin[1] |= ((uses[s] + 1) & 1) << s;
    for (int t = 0, k = 1; t < kTiles; t++)
        if (!(tl[t].flags & F_FINE)) memcpy(out[t], tl[t].p, 3);
        else if (park[t] == '0') {
            for (int w = 0; w < 3; w++) out[t][w] = (kSlots + w) * 8 + 4 + (k & 1) * 2 + (~k & 1);
            k++;
        } else
            for (int w = 0; w < 3; w++) {
                if (uses[out[t][w] >> 3] > nth[t][w]) out[t][w] |= 4;
                else fin[0] &= ~(1u << (out[t][w] >> 3));
            }
    if (INLOOP) tl[0].flags |= F_READY;
    const char* free_run = envs("NOTOK", "710000000000000000000000000000000000000000071");
    for (int t = 0; t <= kTiles; t++)
        for (int w = 0; w < 3; w++)
            if ((free_run[t] - '0') >> w & 1) {
                tl[t].p[w] |= 1;
                if (w) tl[t].p[w - 1] |= 4;
                else if (t) tl[t - 1].p[2] |= 4;
            }
    for (int t = 0; t < kTiles; t++)
        for (int w = 0; w < 3; w++) po[t][w] = tl[t].p[w] + 256 * out[t][w];
}

typedef CUresult (*EncodeFn)(CUtensorMap*, CUtensorMapDataType, cuuint32_t, void*, const cuuint64_t*, const cuuint64_t*,
                             const cuuint32_t*, const cuuint32_t*, CUtensorMapInterleave, CUtensorMapSwizzle,
                             CUtensorMapL2promotion, CUtensorMapFloatOOBfill);

void encode_2d(EncodeFn enc, CUtensorMap* tm, const void* ptr, uint64_t rows, uint32_t box_rows, CUtensorMapL2promotion promo) {
    cuuint64_t dims[2] = {(cuuint64_t)kC, rows};
    cuuint64_t strides[1] = {(cuuint64_t)kC * 2};
    cuuint32_t box[2] = {64, box_rows};
    cuuint32_t es[2] = {1, 1};
    enc(tm, CU_TENSOR_MAP_DATA_TYPE_BFLOAT16, 2, const_cast<void*>(ptr), dims, strides, box, es, CU_TENSOR_MAP_INTERLEAVE_NONE,
        CU_TENSOR_MAP_SWIZZLE_128B, promo, CU_TENSOR_MAP_FLOAT_OOB_FILL_NONE);
}

}

extern "C" void kernel_launch(void* const* d_in, const int* in_sizes, int n_in, void* d_out, int out_size) {
    (void)in_sizes; (void)n_in; (void)out_size;
    static EncodeFn enc = nullptr;
    static Schedule sched;
    static Scratch* scr;
    if (!enc) {
        cudaGetSymbolAddress((void**)&scr, g_scratch);
        void* fn = nullptr;
        cudaDriverEntryPointQueryResult qr;
        cudaGetDriverEntryPoint("cuTensorMapEncodeTiled", &fn, cudaEnableDefault, &qr);
        enc = (EncodeFn)fn;
        cudaFuncSetAttribute(fpn_lateral_kernel, cudaFuncAttributeMaxDynamicSharedMemorySize, kSmemBytes);
        if (envi("CARVE", 0)) cudaFuncSetAttribute(fpn_lateral_kernel, cudaFuncAttributePreferredSharedMemoryCarveout, envi("CARVE", 0));
        cudaLaunchConfig_t cfg = {};
        cfg.gridDim = dim3(2);
        cfg.blockDim = dim3(512);
        cfg.dynamicSmemBytes = kSmemBytes;
        cudaLaunchAttribute at;
        at.id = cudaLaunchAttributeClusterDimension;
        at.val.clusterDim.x = 2; at.val.clusterDim.y = 1; at.val.clusterDim.z = 1;
        cfg.attrs = &at; cfg.numAttrs = 1;
        int ncl = 0;
        if (cudaOccupancyMaxActiveClusters(&ncl, fpn_lateral_kernel, &cfg) != cudaSuccess) { (void)cudaGetLastError(); ncl = 0; }
        const char* pn[4] = {"PATA", "PATB", "PATC", "PATD"};
        const char* pd[4] = {"45", "45", "36", "63"};
        sched.pgroup = envi("PGROUP", 0), sched.members = sched.pgroup ? kGroup : kClusters;
        for (int q = 0; q < NPAT; q++) {
            int gs[8] = {};
            const char* sa = envs(pn[q], pd[q]);
            for (int i = 0; sa[i]; i++) gs[i] = sa[i] - '0';
            build_schedule(q, sched.tile[q], sched.po, sched.fin, sched.wslot[q], sched.worder, gs);
        }
        {
            const char* gaps = envs("GAPS", "00000lmkonnlnomm000qocckkk0su010p11h06I60000");
            const char* lef = envs("LEF", "60000000000000000000000000000000026666666666");
            const uint8_t masks[7] = {0, 1, 9, 0x15, 0x1B, 0x1F, 0x3F};
            for (int t = 0; t < kTiles; t++) {
                const int tr = digit(envs("TRIG", "000000000000000000000000000000a00770060e0000")[t]);
                sched.tile[0][t].pw = tr ? min(EV * t + tr, EV * kTiles) : 0;
                const int d = digit(gaps[t]);
                sched.gap[t] = (d > 36 ? 3 * d - 72 : d) * envi("GUNIT", 75);
                if (gaps[t] != '0' || envi("GALL", 0)) sched.gap_to = t + 1;
                for (int c = 0; c < 6; c++) sched.tile[0][t].chunk[c] |= (masks[lef[t] - '0'] >> c & 1) * 4;
            }
            sched.tstag = envi("TSTAG", 0), sched.gslack = envi("GSLACK", 0);
            const char* lead = envs("LEAD3", "00000000012153ddfnndcminhnmpnnoommgkifjdcefefbd9ecaa8888368cbba78aa88aaa95dc9deebbacaa689ba88847876886756667776666736677666797557955");
            sched.pf_from = envi("PFFROM", 30);
            int pos = sched.pf_from + envi("PF0", 0);
            sched.tgt[0] = pos;
            for (int e = 0; e < EV * kTiles; e++) {
                const int x = (e + 1) * (6 / EV) + digit(lead[e]);
                if (pos < x) pos = x;
                if (pos > 6 * kTiles) pos = 6 * kTiles;
                sched.tgt[e + 1] = pos;
            }
            sched.pw_ev[0] = envi("PW0", 0) * EV / 6 + 1, sched.pw_ev[1] = envi("PW1", 146) * EV / 6 + 1, sched.pw_div = envi("PWDIV", 4);
            sched.t_a = envi("TA", 0), sched.t_d = envi("TD", 290), sched.t_max = envi("TMAX", 0), sched.fsleep = envi("FSLEEP", 80);
        }
        sched.gate1 = envi("GATE1", 1), sched.psleep = envi("PSLEEP", 100);
        sched.pace_from = envi("PACE_FROM", 18), sched.pace_to = envi("PACE_TO", 44);
        const char* v5 = envs("VTA", "55555555555577799664465555332335166655555557");
        const char* vts[4] = {v5, envs("VTB", v5), envs("VTC", v5), envs("VTD", v5)};
        int total = 0;
        for (int q = 0; q < NPAT; q++) {
            int sum[kTiles + 1] = {};
            for (int t = sched.pace_from; t < sched.pace_to; t++) sum[t] = sum[t - 1] + vts[q][t] - '0';
            total = sum[sched.pace_to - 1];
            for (int t = sched.pace_from; t < sched.pace_to; t++) {
                sched.vt[q][t] = sum[t] * kVt / total;
                const int slack = digit(envs("SLK", "000000000jhkjlvyifipjge7eg94gjgijddb6444babl")[t]) * 8;
                sched.need[q][t] = ncl >= kClusters ? 65536 - kVt * kClusters + sched.vt[q][t] * sched.members - slack * 5 * kVt / total * sched.members / 64 : -1;
            }
        }
    }
    CUtensorMap tm_fine, tm_coarse, tm_coarse2, tm_wlat, tm_wout, tm_out;
    const cuuint32_t ones[5] = {1, 1, 1, 1, 1};
    {
        cuuint64_t dims[5] = {(cuuint64_t)kC, 2, 4, 4, (cuuint64_t)kFinePix / 32};
        cuuint64_t strides[4] = {768, 2 * 768, 8 * 768, 32 * 768};
        cuuint32_t box[5] = {64, 2, 4, 4, 1};
        enc(&tm_fine, CU_TENSOR_MAP_DATA_TYPE_BFLOAT16, 5, d_in[0], dims, strides, box, ones, CU_TENSOR_MAP_INTERLEAVE_NONE,
            CU_TENSOR_MAP_SWIZZLE_128B, CU_TENSOR_MAP_L2_PROMOTION_L2_128B, CU_TENSOR_MAP_FLOAT_OOB_FILL_NONE);
    }
    {
        cuuint64_t dims[3] = {64, (cuuint64_t)kC, 6};
        cuuint64_t strides[2] = {768, 128};
        cuuint32_t box[3] = {64, 16, 6};
        cuuint32_t es[3] = {1, 1, 1};
        enc(&tm_wlat, CU_TENSOR_MAP_DATA_TYPE_BFLOAT16, 3, d_in[2], dims, strides, box, es, CU_TENSOR_MAP_INTERLEAVE_NONE,
            CU_TENSOR_MAP_SWIZZLE_128B, CU_TENSOR_MAP_L2_PROMOTION_L2_256B, CU_TENSOR_MAP_FLOAT_OOB_FILL_NONE);
    }
    encode_2d(enc, &tm_wout, d_in[3], kC, 192, CU_TENSOR_MAP_L2_PROMOTION_L2_256B);
    {
        cuuint64_t dims[4] = {(cuuint64_t)kC, 32, 2, (cuuint64_t)kFinePix / 32 - kRankF};
        cuuint64_t strides[3] = {768, kRankF * 32 * 768, 32 * 768};
        cuuint32_t box[4] = {64, 32, 2, 1};
        enc(&tm_out, CU_TENSOR_MAP_DATA_TYPE_BFLOAT16, 4, d_out, dims, strides, box, ones, CU_TENSOR_MAP_INTERLEAVE_NONE,
            CU_TENSOR_MAP_SWIZZLE_128B, CU_TENSOR_MAP_L2_PROMOTION_NONE, CU_TENSOR_MAP_FLOAT_OOB_FILL_NONE);
    }
    {
        cuuint64_t dims[5] = {(cuuint64_t)kC, 2, 4, kGroup * kSeg / 8, 35};
        cuuint64_t strides[4] = {4 * 768, 768, 8 * 768, kGroup * kSeg * 768};
        cuuint32_t box[5] = {64, 2, 4, kSeg / 8, 32 / kSeg};
        enc(&tm_coarse, CU_TENSOR_MAP_DATA_TYPE_BFLOAT16, 5, d_in[1], dims, strides, box, ones, CU_TENSOR_MAP_INTERLEAVE_NONE,
            CU_TENSOR_MAP_SWIZZLE_128B, CU_TENSOR_MAP_L2_PROMOTION_L2_128B, CU_TENSOR_MAP_FLOAT_OOB_FILL_NONE);
        dims[4] = 34;
        enc(&tm_coarse2, CU_TENSOR_MAP_DATA_TYPE_BFLOAT16, 5, d_in[1], dims, strides, box, ones, CU_TENSOR_MAP_INTERLEAVE_NONE,
            CU_TENSOR_MAP_SWIZZLE_128B, CU_TENSOR_MAP_L2_PROMOTION_L2_128B, CU_TENSOR_MAP_FLOAT_OOB_FILL_NONE);
    }
    fpn_lateral_kernel<<<2 * kClusters, 512, kSmemBytes>>>(scr, (const char*)d_in[0], (const char*)d_in[1], (const char*)d_in[2], (const char*)d_in[3],
                                                          tm_fine, tm_coarse, tm_coarse2, tm_wlat, tm_wout, tm_out, sched);
}
```

```cpp
#include <cuda_runtime.h>
#include <cuda_bf16.h>
#include <cuda.h>
#include <stdint.h>
#include <string.h>
#include <type_traits>
#include <stdlib.h>

#define TOKEN_K 3
#define TAKE -2, 0, 2
#define GIVE -4, -2, 0
#define L_POS 0
#define NSTG 6
#define EV 3
#define STPOL 0
#define NO_MMA 0
#define EARLY 1
#define EARLY_T 0
#define W_PRE 0
#define TOPPF 1
#define TLBW 1
#define W_MIX 0x1E
#define WR 1
#define CHAINS 1
#define ROT 0
#define PUBTMA 1
#define DEFER 2
#define INLOOP 1
#define WSPLIT 1
#define TPF_N 0
#define TPF_A 400
#define TPF_D 300
#define FIN 2
#define ENDBAR 1
#define NPAT 1
#define SHAPE 1
#define OBUF 1
#define LD_EF 1
#define CURVE_REC(k, i) do {} while (0)

#define CREC0(c) do {} while (0)
namespace {

constexpr int kC = 384;
constexpr int kFinePix = 384 * 384;
constexpr int kCoarsePix = 192 * 192;
constexpr int kClusters = 66;
constexpr int kTiles = 44;
constexpr int kFull = 2304 - 34 * kClusters;
constexpr int kVt = 65536 / kClusters;
#define SLOTS (28 - 3 * OBUF)
constexpr int kSlots = SLOTS;
#define GT 1
#define ILV 0
constexpr int kColR = ILV ? 64 : 192, kColG = ILV ? 128 : 64;
constexpr int kChunk = 8192;
constexpr int kTileBytes = 6 * kChunk;
constexpr int kOffOut = kSlots * kChunk;
constexpr int kOffBar = kOffOut + 3 * OBUF * kChunk;
constexpr int kSmemBytes = kOffBar + 1024;
constexpr int kSlotL = kSlots + 3 * OBUF - 20;
constexpr int kSlotW = kSlots + 3 * OBUF - 18;
constexpr int kBarFull = 0, kBarEmpty = 8 * kSlots, kBarStaged = kBarEmpty + 8 * (kSlots + 3), kBarW = kBarStaged + 8 * (kSlots + 3), kBarL = kBarW + 24;
constexpr int kBarPiece = kBarL + 8, kBarReady = kBarPiece + 8;
constexpr int kBarSwap = kBarReady + 8;
constexpr int kBarReady2 = kBarSwap + 56;
constexpr int kStarted = kBarSwap + 192, kAllowed = kStarted + 4;
constexpr int kBarW2 = WSPLIT ? kStarted + 8 : kBarW;
constexpr int kPos0 = 4;
constexpr int kPieces = 24;

enum : uint32_t { F_FINE = 1, F_P = 2, F_Q1 = 4, F_SWAP = 8, F_READY = 16, F_Q2 = 32, F_STAGED = 64, F_SW1 = 128 };
struct alignas(16) Tile {
    uint8_t chunk[7];
    uint8_t flags;
    uint8_t p[3];
    uint8_t pw;
    uint16_t pos;
    uint16_t wcnt;
};
constexpr int kGroup = kClusters / NPAT;
struct Schedule {
    Tile tile[NPAT][kTiles + 1];
    uint16_t tgt[EV * kTiles + 2];
    alignas(8) uint8_t wslot[NPAT][2][3][8];
    uint8_t worder[24];
    uint16_t po[kTiles][4];
    uint32_t fin[2];
    uint16_t gap[48];
    int members, pgroup, gslack, gap_to, tstag;
    int pace_from, pace_to, gate1, psleep, pf_from, pw_ev[2], pw_div, t_a, t_d, t_max, fsleep;
    int need[NPAT][kTiles + 1];
    uint16_t vt[NPAT][kTiles + 1];
};
static int envi(const char*, int d) { return d; }
static const char* envs(const char*, const char* d) { return d; }

struct Scratch {
    uint4 wfrag[2][2][3][24][128];
    uint32_t ready, pad0[31];
    uint32_t done, pad1[31];
    uint32_t progress[4][32];
};
__device__ Scratch g_scratch;
#define g_wfrag scr->wfrag
#define g_ready scr->ready
#define g_done scr->done
#define g_progress scr->progress

__device__ __forceinline__ uint32_t smem_u32(const void* p) { return (uint32_t)__cvta_generic_to_shared(p); }

__device__ __forceinline__ void mbar_init(uint32_t bar, uint32_t count) {
    asm volatile("mbarrier.init.shared::cta.b64 [%0], %1;" ::"r"(bar), "r"(count) : "memory");
}
__device__ __forceinline__ void mbar_expect_tx(uint32_t bar, uint32_t bytes) {
    asm volatile("mbarrier.arrive.expect_tx.shared::cta.b64 _, [%0], %1;" ::"r"(bar), "r"(bytes) : "memory");
}
__device__ __forceinline__ void mbar_wait(uint32_t bar, uint32_t parity) {
    asm volatile(
        "{\n"
        ".reg .pred p;\n"
        ".reg .u32 n;\n"
        "mov.u32 n, 0;\n"
        "WAIT_LOOP:\n"
        "mbarrier.try_wait.parity.shared::cta.b64 p, [%0], %1;\n"
        "@p bra WAIT_DONE;\n"
        "add.u32 n, n, 1;\n"
        "setp.lt.u32 p, n, 0x400000;\n"
        "@p bra WAIT_LOOP;\n"
        "trap;\n"
        "WAIT_DONE:\n"
        "}\n" ::"r"(bar), "r"(parity) : "memory");
}
__device__ __forceinline__ void mbar_wait1(uint32_t bar, uint32_t parity) {
    uint32_t r;
    asm volatile("{\n.reg .pred p;\nmbarrier.try_wait.parity.shared::cta.b64 p, [%1], %2;\nselp.u32 %0, 1, 0, p;\n}\n" : "=r"(r) : "r"(bar), "r"(parity) : "memory");
    if (!r) mbar_wait(bar, parity);
}
__device__ __forceinline__ bool mbar_test(uint32_t bar, uint32_t parity) {
    uint32_t r;
    asm volatile("{\n.reg .pred p;\nmbarrier.test_wait.parity.shared::cta.b64 p, [%1], %2;\nselp.u32 %0, 1, 0, p;\n}\n" : "=r"(r) : "r"(bar), "r"(parity) : "memory");
    return r != 0;
}
__device__ __forceinline__ void mbar_arrive(uint32_t bar) {
    asm volatile("mbarrier.arrive.shared::cta.b64 _, [%0];" ::"r"(bar) : "memory");
}
template <int N>
__device__ __forceinline__ void mbar_arrive_cluster(uint32_t bar) {
    if (N == 1) asm volatile("mbarrier.arrive.shared::cluster.b64 _, [%0];" ::"r"(bar) : "memory");
    else asm volatile("mbarrier.arrive.shared::cluster.b64 _, [%0], %1;" ::"r"(bar), "n"(N) : "memory");
}
__device__ __forceinline__ void bulk_load(uint32_t dst, const void* src, uint32_t bar) {
    asm volatile("cp.async.bulk.shared::cluster.global.mbarrier::complete_tx::bytes [%0], [%1], %2, [%3];"
                 ::"r"(dst), "l"(src), "n"(kChunk), "r"(bar) : "memory");
}
__device__ __forceinline__ void tma_load_2d(uint32_t dst, const CUtensorMap* tm, int c0, int c1, uint32_t bar) {
    asm volatile("cp.async.bulk.tensor.2d.shared::cluster.global.mbarrier::complete_tx::bytes [%0], [%1, {%2, %3}], [%4];"
                 ::"r"(dst), "l"(tm), "r"(c0), "r"(c1), "r"(bar) : "memory");
}
__device__ __forceinline__ void tma_load_3d(uint32_t dst, const CUtensorMap* tm, int c1, uint32_t bar) {
    asm volatile("cp.async.bulk.tensor.3d.shared::cluster.global.mbarrier::complete_tx::bytes [%0], [%1, {%2, %3, %2}], [%4];"
                 ::"r"(dst), "l"(tm), "r"(0), "r"(c1), "r"(bar) : "memory");
}
template <bool HINT>
__device__ __forceinline__ void tma_load_5d_mc(uint32_t dst, const CUtensorMap* tm, int c0, int c3, int c4, uint32_t bar, uint64_t pol) {
    if (HINT) asm volatile("cp.async.bulk.tensor.5d.shared::cluster.global.mbarrier::complete_tx::bytes.multicast::cluster.L2::cache_hint [%0], [%1, {%2, %3, %3, %4, %5}], [%6], %7, %8;"
                 ::"r"(dst), "l"(tm), "r"(c0), "r"(0), "r"(c3), "r"(c4), "r"(bar), "h"((uint16_t)3), "l"(pol) : "memory");
    else asm volatile("cp.async.bulk.tensor.5d.shared::cluster.global.mbarrier::complete_tx::bytes.multicast::cluster [%0], [%1, {%2, %3, %3, %4, %5}], [%6], %7;"
                 ::"r"(dst), "l"(tm), "r"(c0), "r"(0), "r"(c3), "r"(c4), "r"(bar), "h"((uint16_t)3) : "memory");
}
__device__ __forceinline__ void tma_store_4d(const CUtensorMap* tm, uint32_t src, int c0, int c3, uint64_t pol) {
    if (STPOL) asm volatile("cp.async.bulk.tensor.4d.global.shared::cta.bulk_group.L2::cache_hint [%0, {%2, %3, %3, %4}], [%1], %5;"
                 ::"l"(tm), "r"(src), "r"(c0), "r"(0), "r"(c3), "l"(pol) : "memory");
    else asm volatile("cp.async.bulk.tensor.4d.global.shared::cta.bulk_group [%0, {%2, %3, %3, %4}], [%1];"
                 ::"l"(tm), "r"(src), "r"(c0), "r"(0), "r"(c3) : "memory");
}
__device__ __forceinline__ void prefetch_l2(const void* p) {
    asm volatile("prefetch.global.L2 [%0];" ::"l"(p) : "memory");
}
__device__ __forceinline__ void prefetch_tm(const CUtensorMap* tm) {
    asm volatile("prefetch.tensormap [%0];" ::"l"(tm) : "memory");
}
__device__ __forceinline__ uint32_t now_ns() {
    uint32_t t;
    asm volatile("mov.u32 %0, %globaltimer_lo;" : "=r"(t));
    return t;
}
__device__ __forceinline__ bool elect_one() {
    uint32_t p;
    asm volatile("{\n.reg .pred p;\nelect.sync _|p, 0xffffffff;\nselp.u32 %0, 1, 0, p;\n}\n" : "=r"(p));
    return p != 0;
}
#define CLUSTER_ARRIVE() asm volatile("barrier.cluster.arrive.relaxed.aligned;" ::: "memory")
#define CLUSTER_WAIT() asm volatile("barrier.cluster.wait.acquire.aligned;" ::: "memory")

#define WG_FENCE() asm volatile("wgmma.fence.sync.aligned;" ::: "memory")
#define WG_COMMIT() asm volatile("wgmma.commit_group.sync.aligned;" ::: "memory")
#define WG_WAIT(n) asm volatile("wgmma.wait_group.sync.aligned %0;" ::"n"(n) : "memory")

#define ACC32 "{%0,%1,%2,%3,%4,%5,%6,%7,%8,%9,%10,%11,%12,%13,%14,%15,%16,%17,%18,%19,%20,%21,%22,%23,%24,%25,%26,%27,%28,%29,%30,%31}"
#define ACC8(b) "+f"(d[b]), "+f"(d[b + 1]), "+f"(d[b + 2]), "+f"(d[b + 3]), "+f"(d[b + 4]), "+f"(d[b + 5]), "+f"(d[b + 6]), "+f"(d[b + 7])

#define DESC_HI "0x40000040"
template <int BOFF>
__device__ __forceinline__ void wgmma_rs(float (&d)[32], const uint32_t* a, uint32_t b_lo) {
    asm volatile("{\n.reg .b32 tb;\n.reg .b64 db;\nadd.u32 tb, %36, %37;\nmov.b64 db, {tb, " DESC_HI "};\n"
                 "wgmma.mma_async.sync.aligned.m64n64k16.f32.bf16.bf16 " ACC32 ", {%32,%33,%34,%35}, db, 1, 1, 1, 0;\n}\n"
                 : ACC8(0), ACC8(8), ACC8(16), ACC8(24)
                 : "r"(a[0]), "r"(a[1]), "r"(a[2]), "r"(a[3]), "r"(b_lo), "n"(BOFF));
}
__device__ __forceinline__ void wgmma_rs_first(float (&d)[32], const uint32_t* a, uint32_t b_lo, uint32_t accum) {
    asm volatile("{\n.reg .pred p;\n.reg .b64 db;\nsetp.ne.u32 p, %37, 0;\nmov.b64 db, {%36, " DESC_HI "};\n"
                 "wgmma.mma_async.sync.aligned.m64n64k16.f32.bf16.bf16 " ACC32 ", {%32,%33,%34,%35}, db, p, 1, 1, 0;\n}\n"
                 : ACC8(0), ACC8(8), ACC8(16), ACC8(24)
                 : "r"(a[0]), "r"(a[1]), "r"(a[2]), "r"(a[3]), "r"(b_lo), "r"(accum));
}
template <int ACCUM, int BOFF, int D>
__device__ __forceinline__ void wgmma_rs16(float (&d)[32], const uint32_t* a, uint32_t b_lo) {
    asm volatile("{\n.reg .b32 tb;\n.reg .b64 db;\nadd.u32 tb, %12, %13;\nmov.b64 db, {tb, " DESC_HI "};\n"
                 "wgmma.mma_async.sync.aligned.m64n16k16.f32.bf16.bf16 {%0,%1,%2,%3,%4,%5,%6,%7}, {%8,%9,%10,%11}, db, %14, 1, 1, 0;\n}\n"
                 : ACC8(D)
                 : "r"(a[0]), "r"(a[1]), "r"(a[2]), "r"(a[3]), "r"(b_lo), "n"(BOFF), "n"(ACCUM));
}
template <int S>
__device__ __forceinline__ void piece_steps(float (&d)[32], const uint32_t (&w)[96], uint32_t b_lo) {
    if constexpr (S < 24) {
        wgmma_rs16<(S >= CHAINS), (S >> 2) * 128 + (S & 3) * 2, S % CHAINS * 8>(d, &w[4 * S], b_lo);
        piece_steps<S + 1>(d, w, b_lo);
    }
}

__device__ __forceinline__ uint32_t pack_bf16(float lo, float hi) {
    uint32_t r;
    asm("cvt.rn.bf16x2.f32 %0, %1, %2;" : "=r"(r) : "f"(hi), "f"(lo));
    return r;
}

template <int C>
__device__ __forceinline__ void reload_w(uint32_t (&w)[96], const char* base, uint32_t tid16, uint32_t on) {
#define W4(i) "+r"(w[16 * C + 4 * i]), "+r"(w[16 * C + 4 * i + 1]), "+r"(w[16 * C + 4 * i + 2]), "+r"(w[16 * C + 4 * i + 3])
    asm volatile("{\n.reg .pred p;\n.reg .b64 a;\nsetp.ne.u32 p, %19, 0;\ncvt.u64.u32 a, %18;\nadd.u64 a, a, %16;\n"
                 "@p ld.global.cg.v4.u32 {%0,%1,%2,%3}, [a + %17];\n"
                 "@p ld.global.cg.v4.u32 {%4,%5,%6,%7}, [a + %17 + 2048];\n"
                 "@p ld.global.cg.v4.u32 {%8,%9,%10,%11}, [a + %17 + 4096];\n"
                 "@p ld.global.cg.v4.u32 {%12,%13,%14,%15}, [a + %17 + 6144];\n}\n"
                 : W4(0), W4(1), W4(2), W4(3)
                 : "l"(base), "n"(C * 8192), "r"(tid16), "r"(on) : "memory");
#undef W4
}

template <int C>
__device__ __forceinline__ uint32_t entry(uint2 e) { return C < 4 ? e.x >> (8 * C) : e.y >> (8 * (C - 4)); }

template <int C>
__device__ __forceinline__ bool issue_chunk(float (&acc)[32], const uint32_t (&w)[96], uint2 e, uint32_t bars, uint32_t b_lo0, bool ready) {
    if (!ready) mbar_wait(bars + kBarFull + (entry<C>(e) & 0xF8), entry<C>(e) & 1);
    const bool next = C < 5 && mbar_test(bars + kBarFull + (entry<C + 1>(e) & 0xF8), entry<C + 1>(e) & 1);
    const uint32_t b_lo = b_lo0 + (entry<C>(e) & 0xF8) * 64;
    if (!NO_MMA) {
        WG_FENCE();
        if (C == 0) wgmma_rs_first(acc, &w[0], b_lo, e.y & (F_FINE << 24));
        else wgmma_rs<0>(acc, &w[16 * C], b_lo);
        wgmma_rs<2>(acc, &w[16 * C + 4], b_lo);
        wgmma_rs<4>(acc, &w[16 * C + 8], b_lo);
        wgmma_rs<6>(acc, &w[16 * C + 12], b_lo);
        WG_COMMIT();
    }
    return next;
}
template <int C, int PENDING, int MODE>
__device__ __forceinline__ void retire_chunk(uint32_t (&w)[96], uint2 e, const uint8_t (*ws)[3][8], int wg, uint32_t sbase, uint32_t rel_bar, bool rel, const char* swap, uint32_t tid16) {
    if (!NO_MMA) WG_WAIT(PENDING);
    if (rel) mbar_arrive_cluster<1>(rel_bar + (entry<C>(e) & 0xF8));
    if (MODE == 1 && C < 6 - DEFER) reload_w<C>(w, swap, tid16, 1);
    if (MODE == 2 && C >= 6 - NSTG) {
        const uint32_t x = ws[e.y >> 31][wg][C];
        mbar_wait(sbase + kOffBar + kBarSwap + 64 * wg + 8 * C, e.y >> 31);
        const uint32_t a = sbase + (x & 0xF8) * 1024 + tid16;
#pragma unroll
        for (int q = 0; q < 4; q++)
            asm volatile("ld.shared.v4.u32 {%0,%1,%2,%3}, [%4];" : "=r"(w[16 * C + 4 * q]), "=r"(w[16 * C + 4 * q + 1]), "=r"(w[16 * C + 4 * q + 2]), "=r"(w[16 * C + 4 * q + 3])
                         : "r"(a + q * 2048) : "memory");
        asm volatile("bar.sync %0, 128;" ::"r"(4 + wg + ((w[16 * C] | w[16 * C + 4] | w[16 * C + 8] | w[16 * C + 12]) & x & 1)) : "memory");
        if (rel) mbar_arrive_cluster<3>(rel_bar + (x & 0xF8));
    }
}

__device__ __forceinline__ int pub_slot(int g) { return g == 0 ? kSlotL + 1 : g == 1 ? kSlotW + 11 : kSlotW + 14; }
__device__ __forceinline__ int fine_group(uint32_t pos, int ci) {
    const uint32_t q = (pos & 0xFFF) + ci;
    return SHAPE ? q + q / 12 * 12 : 2 * q + (q / 6 + ((pos >> 12) & 1)) * 12;
}
constexpr int kRankF = SHAPE ? 12 : 1, kRankC = SHAPE ? 2 : 1, kSeg = SHAPE ? 16 : 32;
template <int L0, int L1>
__device__ __forceinline__ void prefetch_tile(uint32_t pos, int ci, int rank, int lane, const char* fine, const char* coarse) {
    const bool f = pos & 0x8000;
    const uint32_t row = f ? (fine_group(pos, ci) + kRankF * rank) * 32 : (((pos & 0xFFF) + kRankC * rank) * kGroup + ci) * kSeg;
    const char* p = (f ? fine : coarse) + (size_t)row * 768 + lane * 128;
    const char* q = SHAPE && !f ? p + (kGroup - 1) * kSeg * 768 : p;
#pragma unroll
    for (int l = L0; l < L1; l++) prefetch_l2((l < 3 ? p : q) + l * 4096);
}

__global__ void __cluster_dims__(2, 1, 1) __launch_bounds__(512, 1)
fpn_lateral_kernel(Scratch* const scr, const char* __restrict__ fine, const char* __restrict__ coarse,
                   const char* __restrict__ wlat, const char* __restrict__ wout,
                   const __grid_constant__ CUtensorMap tm_fine, const __grid_constant__ CUtensorMap tm_coarse, const __grid_constant__ CUtensorMap tm_coarse2,
                   const __grid_constant__ CUtensorMap tm_wlat, const __grid_constant__ CUtensorMap tm_wout,
                   const __grid_constant__ CUtensorMap tm_out, const __grid_constant__ Schedule sched) {
    extern __shared__ __align__(1024) unsigned char smem_raw[];
    if (threadIdx.x == 0) CURVE_REC(0, 0);
    uint32_t t_start;
    asm volatile("mov.u32 %0, %clock;" : "=r"(t_start));
    const uint32_t sbase = smem_u32(smem_raw);
    const uint32_t bars = sbase + kOffBar;
    const int rot = !ROT ? 0 : blockIdx.x < 4 * kPieces ? blockIdx.x & 2 : 1;
    const int npc = !ROT ? (blockIdx.x < 2 * kPieces ? 3 : 0) : blockIdx.x < 4 * kPieces ? 2 - (rot >> 1) : 0;
    const int pj = blockIdx.x >> (1 + ROT);
    auto slice = [&](int g) { return g + rot >= 3 ? g + rot - 3 : g + rot; };
    if (threadIdx.x == EARLY_T) {
        mbar_init(bars + kBarW, 1);
        if (WSPLIT) mbar_init(bars + kBarW2, 1);
        mbar_init(bars + kBarL, 1);
        asm volatile("fence.proxy.async.shared::cta;" ::: "memory");
        mbar_expect_tx(bars + kBarW, kTileBytes >> WSPLIT);
        if (WSPLIT) mbar_expect_tx(bars + kBarW2, kTileBytes >> WSPLIT);
        for (int c = 0; c < 2; c++) tma_load_2d(sbase + (kSlotW + 3 * c) * kChunk, &tm_wout, (blockIdx.x & 1) * kColR + rot * kColG, c * 192, bars + (c ? kBarW2 : kBarW));
        prefetch_tm(&tm_coarse);
        if (npc) {
            mbar_expect_tx(bars + kBarL, 6 * 2048);
            tma_load_3d(sbase + kSlotL * kChunk, &tm_wlat, pj * 16, bars + kBarL);
        }
        asm volatile("fence.mbarrier_init.release.cluster;" ::: "memory");
        CURVE_REC(1, 47);
    }
    {
        constexpr int kWw = (36 * WR + 31) / 32;
        const uint32_t t = threadIdx.x - 32, b = blockIdx.x, c = (t >> 5) - kWw, l = ((b >> 1) % (64 / WR)) * (36 * WR) + t;
        const uint32_t row = ((kPos0 + kRankC * (b & 1) + ((t >> 4) & 1)) * kGroup + (b >> 1)) * kSeg + (t & 15);
        const char* p = t >= 32 * kWw ? coarse + row * 768 + c * 128 : (b & 1 ? wlat : wout) + l * 128;
        if (t < 36 * WR || c < TOPPF) prefetch_l2(p);
    }
    const int warp_id = __shfl_sync(0xffffffffu, (int)(threadIdx.x >> 5), 0);
    const int lane = threadIdx.x & 31;
    const int wg = warp_id >> 2;
    const int rank = blockIdx.x & 1;
    const int cid = blockIdx.x >> 1;
    const int pat = cid % NPAT, ci = cid / NPAT;
    const Tile* const tiles = sched.tile[pat];

    if (wg == 3) {
        asm volatile("setmaxnreg.dec.sync.aligned.u32 32;");
        const int j = warp_id & 3;
        const bool lead = elect_one();
        if (j == 3) {
            uint32_t c0;
            asm volatile("mov.u32 %0, %clock;" : "=r"(c0));
            if (lead) CURVE_REC(1, 46);
            if (lead) {
                mbar_init(bars + kBarW + 8, 1);
                mbar_init(bars + kBarW + 16, 1);
                if (WSPLIT) mbar_init(bars + kBarW2 + 8, 1), mbar_init(bars + kBarW2 + 16, 1);
                asm volatile("fence.mbarrier_init.release.cluster;" ::: "memory");
                asm volatile("fence.proxy.async.shared::cta;" ::: "memory");
            }
            __syncwarp();
            CLUSTER_ARRIVE();
            if (lead) {
                for (int g = 1; g < 3; g++) {
                    mbar_expect_tx(bars + kBarW + 8 * g, kTileBytes >> WSPLIT);
                    if (WSPLIT) mbar_expect_tx(bars + kBarW2 + 8 * g, kTileBytes >> WSPLIT);
                }
                for (int g = 2; g < 2 + W_PRE; g++) tma_load_2d(sbase + (kSlotW + 3 * g) * kChunk, &tm_wout, rank * kColR + slice(g >> 1) * kColG, (g & 1) * 192, bars + (g & 1 ? kBarW2 : kBarW) + 8 * (g >> 1));
            }
            __syncwarp();
            CLUSTER_WAIT();
            if (lead) {
                int g = 2 + W_PRE;
#pragma unroll 1
                for (int c = 0; c < 6; c++) {
                    mbar_expect_tx(bars + kBarFull + 8 * c, kChunk);
                    tma_load_5d_mc<false>(sbase + rank * 4096 + c * kChunk, &tm_coarse, c * 64, ci * (kSeg / 8), kPos0 + kRankC * rank, bars + kBarFull + 8 * c, 0);
                    CURVE_REC(1, 52 + c);
                    if ((W_MIX >> c & 1) && g < 6) {
                        tma_load_2d(sbase + (kSlotW + 3 * g) * kChunk, &tm_wout, rank * kColR + slice(g >> 1) * kColG, (g & 1) * 192, bars + (g & 1 ? kBarW2 : kBarW) + 8 * (g >> 1));
                        g++;
                    }
                }
#pragma unroll 1
                for (; g < 6; g++) {
                    tma_load_2d(sbase + (kSlotW + 3 * g) * kChunk, &tm_wout, rank * kColR + slice(g >> 1) * kColG, (g & 1) * 192, bars + (g & 1 ? kBarW2 : kBarW) + 8 * (g >> 1));
                    CURVE_REC(1, 47 + (g >> 1));
                }
            }
            __syncwarp();
            uint32_t cur = sched.pf_from, u = 0, pw = sched.pw_ev[0] == 1;
            const char* p = nullptr;
            bool ok = false;
#pragma unroll 1
            for (uint32_t n = 0; cur < 6 * kTiles; n++) {
                uint32_t v;
                asm volatile("ld.volatile.shared.u32 %0, [%1];" : "=r"(v) : "r"(bars + kStarted) : "memory");
                uint32_t tgt = sched.tgt[v];
                if (cur < sched.t_max) {
                    uint32_t c;
                    asm volatile("mov.u32 %0, %clock;" : "=r"(c));
                    if ((int)(c - c0) >= (int)(sched.t_a + cur * sched.t_d)) tgt = max(tgt, cur + 1);
                }
#pragma unroll 1
                for (; cur < tgt; cur++) {
                    if (u == 0) {
                        const uint32_t pos = tiles[cur / 6].pos;
                        const bool f = pos & 0x8000;
                        const uint32_t row = f ? (fine_group(pos, ci) + kRankF * rank) * 32 + lane : (((pos & 0xFFF) + kRankC * rank + (lane >> 4)) * kGroup + ci) * kSeg + (lane & 15);
                        p = (f ? fine : coarse) + (size_t)row * 768;
                        ok = row < (f ? kFinePix : kCoarsePix);
                    }
                    if (ok) prefetch_l2(p);
                    p += 128;
                    u = u == 5 ? 0 : u + 1;
                }
                if (pw < 2 && v >= sched.pw_ev[pw]) {
                    const char* q = (const char*)&g_wfrag[pw][rank][0][0][0] + lane * 128;
#pragma unroll 1
                    for (int l = ci % sched.pw_div; l < 36; l += sched.pw_div) prefetch_l2(q + l * 4096);
                    pw++;
                }
                if (n == 0x1000000) __trap();
                __nanosleep(sched.fsleep);
            }
        } else if (j == 2) {
            if (lead) CURVE_REC(1, 58);
            CLUSTER_ARRIVE();
            if (lead) {
                uint32_t v;
                asm volatile("ld.relaxed.gpu.global.u32 %0, [%1];" : "=r"(v) : "l"(&g_ready) : "memory");
            }
            if (lead) {
                CURVE_REC(1, 59);
                prefetch_tm(&tm_fine);
                prefetch_tm(&tm_coarse2);
                prefetch_tm(&tm_out);
            }
            __syncwarp();
            CLUSTER_WAIT();
            if (lead) {
                if (npc) {
                    mbar_wait(bars + kBarPiece, 0);
                    asm volatile("fence.proxy.async.shared::cta;" ::: "memory");
                    for (int i = 0; i < 2 * npc; i++)
                        asm volatile("cp.async.bulk.global.shared::cta.bulk_group [%0], [%1], 2048;"
                                     ::"l"(&g_wfrag[i & 1][rank][slice(i >> 1)][pj][0]), "r"(sbase + pub_slot(i >> 1) * kChunk + 4096 + (i & 1) * 2048) : "memory");
                    asm volatile("cp.async.bulk.commit_group;" ::: "memory");
                    asm volatile("cp.async.bulk.wait_group.read 0;" ::: "memory");
                    for (int i = 0; i < 2 * npc; i++) {
                        uint32_t b;
                        asm("mapa.shared::cluster.u32 %0, %1, %2;" : "=r"(b) : "r"(bars + kBarEmpty + 8 * pub_slot(i >> 1)), "r"(i & 1));
                        asm volatile("mbarrier.arrive.shared::cluster.b64 _, [%0], %1;" ::"r"(b), "r"(i < 2 ? 1 : 3) : "memory");
                    }
                    asm volatile("cp.async.bulk.wait_group 0;" ::: "memory");
                    asm volatile("red.relaxed.gpu.global.add.u32 [%0], 1;" ::"l"(&g_ready) : "memory");
                    CURVE_REC(2, 61);
                }
                uint32_t v, n = 0;
                for (;;) {
                    asm volatile("ld.acquire.gpu.global.u32 %0, [%1];" : "=r"(v) : "l"(&g_ready) : "memory");
                    if (v >= (2 * kPieces << ROT)) break;
                    if (++n == 0x100000) __trap();
                    __nanosleep(50);
                }
                CURVE_REC(2, 62);
                mbar_arrive(bars + kBarReady);
                asm volatile("fence.proxy.async.global;" ::: "memory");
                mbar_arrive(bars + kBarReady2);
                if (atomicAdd(&g_done, 1) == gridDim.x - 1) {
                    g_ready = 0;
                    g_done = 0;
                }
                asm volatile("st.volatile.shared.u32 [%0], %1;" ::"r"(bars + kAllowed), "r"(rank == 0 || sched.gate1 ? sched.pace_from : kTiles) : "memory");
                if (rank == 0 || sched.gate1) {
                    const uint16_t* vt = sched.vt[pat];
                    uint32_t* const ctr = g_progress[sched.pgroup * pat];
                    const int last = sched.pace_to - 1;
                    asm volatile("ld.relaxed.gpu.global.u32 %0, [%1];" : "=r"(v) : "l"(ctr) : "memory");
                    const uint32_t base = v & ~0xFFFFu;
                    if (blockIdx.x == 0) asm volatile("red.relaxed.gpu.global.add.u32 [%0], %1;" ::"l"(ctr), "r"(65536 - kVt * kClusters) : "memory");
                    int counted = rank == 0 ? sched.pace_from - 1 : last, allowed = sched.pace_from;
#pragma unroll 1
                    for (n = 0; n < 0x10000 && (allowed <= last || counted < last); n++) {
                        int started;
                        asm volatile("ld.volatile.shared.u32 %0, [%1];" : "=r"(started) : "r"(bars + kStarted) : "memory");
                        started = (started + EV - 1) / EV;
                        if (counted < last && counted < started) {
                            const int upto = min(started, last);
                            asm volatile("red.relaxed.gpu.global.add.u32 [%0], %1;" ::"l"(ctr), "r"(vt[upto] - vt[counted]) : "memory");
                            counted = upto;
                        }
                        if (allowed <= last && started + 1 >= allowed) {
                            asm volatile("ld.relaxed.gpu.global.u32 %0, [%1];" : "=r"(v) : "l"(ctr) : "memory");
                            while (allowed <= last && (int)(v - base) >= sched.need[pat][allowed]) allowed++;
                            asm volatile("st.volatile.shared.u32 [%0], %1;" ::"r"(bars + kAllowed), "r"(allowed > last ? kTiles : allowed) : "memory");
                        }
                        __nanosleep(sched.psleep);
                    }
                    asm volatile("st.volatile.shared.u32 [%0], %1;" ::"r"(bars + kAllowed), "r"(kTiles) : "memory");
                    if (counted < last) asm volatile("red.relaxed.gpu.global.add.u32 [%0], %1;" ::"l"(ctr), "r"(vt[last] - vt[counted]) : "memory");
                }
            }
        } else if (j == 1) {
            if (lead) CURVE_REC(3, 51);
            if (sbase & 1023) __trap();
            if (lead) {
                asm volatile("st.shared.u32 [%0], %1;" ::"r"(bars + kStarted), "r"(0) : "memory");
                asm volatile("st.shared.u32 [%0], %1;" ::"r"(bars + kAllowed), "r"(8) : "memory");
                if (kSlots > 24) {
                    mbar_init(bars + kBarFull + 8 * 24, 1);
                    mbar_init(bars + kBarEmpty + 8 * 24, 6);
                }
                mbar_init(bars + kBarPiece, max(4 * npc, 1));
                mbar_init(bars + kBarReady, 1);
                for (int i = 0; i < 3; i++) mbar_init(bars + kBarEmpty + 8 * (kSlots + i), 1);
                for (int i = 24; i < kSlots + 3; i++) mbar_init(bars + kBarStaged + 8 * i, 4);
                asm volatile("fence.acq_rel.cta;" ::: "memory");
                asm volatile("fence.mbarrier_init.release.cluster;" ::: "memory");
                CURVE_REC(3, 52);
            }
            __syncwarp();
            CLUSTER_ARRIVE();
            CLUSTER_WAIT();
            if (lead) {
                const uint32_t t0 = now_ns();
                uint32_t last[3] = {t0, t0, t0}, peer;
                asm("mapa.shared::cluster.u32 %0, %1, %2;" : "=r"(peer) : "r"(bars + kBarEmpty), "r"(rank ^ 1));
                auto release = [&](uint32_t o) {
                    const uint32_t s8 = o & 0xF8;
                    if (s8 >= 8 * kSlots) mbar_arrive(bars + kBarEmpty + s8);
                    else {
                        asm volatile("mbarrier.arrive.shared::cta.b64 _, [%0], 3;" ::"r"(bars + kBarEmpty + s8) : "memory");
                        mbar_arrive_cluster<3>(peer + s8);
                    }
                };
                uint64_t pol_normal = 0;
                if (STPOL) asm volatile("createpolicy.fractional.L2::evict_normal.b64 %0, 1.0;" : "=l"(pol_normal));
#pragma unroll 1
                for (int t = 0; t < kTiles; t++) {
                    const uint32_t pos = tiles[t].pos, gap = sched.gap[t];
                    if (!(pos & 0x8000)) continue;
                    const int row = fine_group(pos, ci);
                    uint32_t prev = 0;
                    if (tiles[t].pw) {
#pragma unroll 1
                        for (uint32_t n = 0, v = 0; n < 4096 && v < tiles[t].pw; n++) {
                            __nanosleep(20);
                            asm volatile("ld.volatile.shared.u32 %0, [%1];" : "=r"(v) : "r"(bars + kStarted) : "memory");
                        }
                        const uint32_t c = now_ns();
                        last[0] = c, last[1] = c + sched.tstag, last[2] = c + 2 * sched.tstag;
                    }
#pragma unroll
                    for (int g = 0; g < 3; g++) {
                        const uint32_t o = sched.po[t][g] >> 8, s8 = o & 0xF8;
                        mbar_wait1(bars + kBarStaged + s8, o & 1);
                        if (g == 2) CURVE_REC(1, t);
                        if (t < sched.gap_to) {
                            uint32_t c;
                            last[g] += gap;
#pragma unroll 1
                            for (int n = 0; n < 4096; n++) {
                                c = now_ns();
                                if ((int)(c - last[g]) >= 0) break;
                                __nanosleep(20);
                            }
                            if ((int)(c - last[g]) > sched.gslack) last[g] = c - sched.gslack;
                        }
                        asm volatile("fence.proxy.async.shared::cta;" ::: "memory");
                        tma_store_4d(&tm_out, sbase + s8 * 1024, rank * kColR + slice(g) * kColG, row, pol_normal);
                        asm volatile("cp.async.bulk.commit_group;" ::: "memory");
                        if (prev & 4) {
                            asm volatile("cp.async.bulk.wait_group.read 1;" ::: "memory");
                            release(prev);
                        }
                        prev = o;
                    }
                    if (prev & 4) {
                        asm volatile("cp.async.bulk.wait_group.read 0;" ::: "memory");
                        release(prev);
                    }
                    CURVE_REC(3, t);
                }
                asm volatile("cp.async.bulk.wait_group.read 0;" ::: "memory");
            }
        } else {
            if (lead) CURVE_REC(1, 50);
            CLUSTER_ARRIVE();
            uint4 e = *(const uint4*)&tiles[1];
            asm volatile("" : "+r"(e.x), "+r"(e.y), "+r"(e.w));
            CLUSTER_WAIT();
            if (lead) CURVE_REC(1, 51);
            if (lead) {
                uint32_t dst0 = sbase + rank * 4096, bar0 = bars;
                asm volatile("" : "+r"(dst0), "+r"(bar0));
                uint32_t wk = 0, wi = 0;
                int allowed = 0;
                uint64_t pol_first, pol_normal;
                asm volatile("createpolicy.fractional.L2::evict_first.b64 %0, 1.0;" : "=l"(pol_first));
                asm volatile("createpolicy.fractional.L2::evict_normal.b64 %0, 1.0;" : "=l"(pol_normal));
#pragma unroll 1
                for (int t = EARLY ? 1 : 0; t < kTiles; t++) {
                    if (t > 1) e = *(const uint4*)&tiles[t];
                    const bool f = e.w & 0x8000;
                    const CUtensorMap* tm = f ? &tm_fine : ci < kFull ? &tm_coarse : &tm_coarse2;
                    const int c3 = f ? 0 : ci * (kSeg / 8), c4 = f ? fine_group(e.w, ci) + kRankF * rank : (e.w & 0xFFF) + kRankC * rank;
                    for (uint32_t n = 0; t >= allowed; n++) {
                        asm volatile("ld.volatile.shared.u32 %0, [%1];" : "=r"(allowed) : "r"(bar0 + kAllowed) : "memory");
                        if (n == 0x4000000) __trap();
                        if (n) __nanosleep(20);
                    }
                    if (t) CURVE_REC(0, t);
#pragma unroll
                    for (int c = 0; c < 6; c++) {
                        if (c % (6 / EV) == 0) asm volatile("st.volatile.shared.u32 [%0], %1;" ::"r"(bar0 + kStarted), "r"(EV * t + 1 + c / (6 / EV)) : "memory");
                        const uint32_t x = c < 4 ? e.x >> (8 * c) : e.y >> (8 * (c - 4)), s8 = x & 0xF8;
                        mbar_wait1(bar0 + kBarEmpty + s8, (x >> 1) & 1);
                        mbar_expect_tx(bar0 + kBarFull + s8, kChunk);
                        tma_load_5d_mc<LD_EF>(dst0 + s8 * 1024, tm, c * 64, c3, c4, bar0 + kBarFull + s8, x & 4 ? pol_first : pol_normal);
#pragma unroll 1
                        for (uint32_t n = (e.w >> (16 + 2 * c)) & 3; n; n--) {
                            if (wk == 0) mbar_wait(bar0 + kBarReady2, 0);
                            const uint32_t o = sched.worder[wk], y = (&sched.wslot[pat][wi][0][0])[o];
                            mbar_wait1(bar0 + kBarEmpty + (y & 0xF8), (y >> 1) & 1);
                            mbar_expect_tx(bar0 + kBarSwap + 8 * o, kChunk);
                            bulk_load(sbase + (y & 0xF8) * 1024, (const char*)&g_wfrag[0][rank][0][0][0] + (6 * slice(o >> 3) + (o & 7)) * kChunk, bar0 + kBarSwap + 8 * o);
                            if (++wk == 3 * NSTG) wk = 0, wi++;
                        }
                    }
                }
            }
        }
        __syncwarp();
    } else {
        if (elect_one()) {
            for (int i = 2 * warp_id; i < 2 * warp_id + 2; i++) {
                mbar_init(bars + kBarSwap + 8 * i, 1);
                if (i >= kSlots) continue;
                mbar_init(bars + kBarFull + 8 * i, 1);
                mbar_init(bars + kBarEmpty + 8 * i, 6);
                mbar_init(bars + kBarStaged + 8 * i, 4);
            }
            asm volatile("fence.mbarrier_init.release.cluster;" ::: "memory");
        }
        __syncwarp();
        CLUSTER_ARRIVE();
        asm volatile("setmaxnreg.inc.sync.aligned.u32 160;");
        const int tid = threadIdx.x & 127;
        const int warp = tid >> 5;
        const bool rel = tid < 2;
        uint32_t rel_bar;
        asm("mapa.shared::cluster.u32 %0, %1, %2;" : "=r"(rel_bar) : "r"(bars + kBarEmpty), "r"(tid & 1));
        const uint32_t b_lo0 = ((sbase & 0x3FFFF) >> 4) | 0x10000u;
        const uint32_t frag_off = ((lane >> 4) * 8 + (lane & 7)) * 128 + (((2 * warp + ((lane >> 3) & 1)) ^ (lane & 7)) << 4);
        uint32_t st_addr = sbase + frag_off, tid16 = tid * 16;
        asm volatile("" : "+r"(st_addr), "+r"(tid16));
        uint4* const wf = &g_wfrag[0][rank][slice(wg)][pj][tid];
        constexpr int kSet = 2 * 3 * 24 * 128;

        float acc[32];
        uint32_t w[96], p[16];

        auto load_w = [&]() {
        mbar_wait(bars + kBarW + 8 * wg, 0);
        if (tid == 0) CURVE_REC(3, 48 + wg);
        const uint32_t w_addr = sbase + (kSlotW + 6 * wg) * kChunk + frag_off;
#pragma unroll
        for (int s = 0; s < 24; s++) {
            if (WSPLIT && s == 12) mbar_wait(bars + kBarW2 + 8 * wg, 0);
            asm volatile("ldmatrix.sync.aligned.m8n8.x4.trans.shared.b16 {%0,%1,%2,%3}, [%4];"
                         : "=r"(w[4 * s]), "=r"(w[4 * s + 1]), "=r"(w[4 * s + 2]), "=r"(w[4 * s + 3]) : "r"(w_addr + s * 2048) : "memory");
        }
        if (wg < npc) {
            asm volatile("ldmatrix.sync.aligned.m8n8.x4.trans.shared.b16 {%0,%1,%2,%3}, [%4];"
                         : "=r"(p[0]), "=r"(p[1]), "=r"(p[2]), "=r"(p[3]) : "r"(w_addr + pj * 2048) : "memory");
            if (!PUBTMA) wf[0] = make_uint4(p[0], p[1], p[2], p[3]);
        }
        asm volatile("bar.sync %0, 128;" ::"r"(4 + wg) : "memory");
        {
            const uint32_t m = (wg == 2 ? 0x3F : 0xFFF) & ~(PUBTMA && wg && wg < npc ? 3u << 2 * (pub_slot(wg) - kSlotW - 6 * wg) : 0u);
            asm volatile("{\n.reg .pred p;\nsetp.ne.u32 p, %1, 0;\n@p mbarrier.arrive.shared::cluster.b64 _, [%0], 3;\n}\n"
                         ::"r"(rel_bar + 8 * (kSlotW + 6 * wg + (tid >> 1))), "r"(tid < 12 ? m >> tid & 1 : 0) : "memory");
        }
        if (threadIdx.x == 0) CURVE_REC(2, 59);
        if (wg < npc) {
            mbar_wait(bars + kBarL, 0);
            if (threadIdx.x == 0) CURVE_REC(3, 61);
            WG_FENCE();
            piece_steps<0>(acc, w, b_lo0 + kSlotL * 512);
            WG_COMMIT();
            WG_WAIT(0);
#pragma unroll
            for (int i = 0; i < 8; i++) {
                asm volatile("" : "+f"(acc[i]), "+f"(acc[8 + i]), "+f"(acc[16 + i]), "+f"(acc[24 + i]));
                if (CHAINS == 2) acc[i] += acc[8 + i];
                if (CHAINS == 4) acc[i] = (acc[i] + acc[8 + i]) + (acc[16 + i] + acc[24 + i]);
            }
            const uint32_t a = sbase + pub_slot(wg) * kChunk + 4096 + tid16;
            asm volatile("st.shared.v4.u32 [%0], {%1,%2,%3,%4};" ::"r"(a), "r"(p[0]), "r"(p[1]), "r"(p[2]), "r"(p[3]) : "memory");
            asm volatile("st.shared.v4.u32 [%0], {%1,%2,%3,%4};" ::"r"(a + 2048), "r"(pack_bf16(acc[0], acc[1])), "r"(pack_bf16(acc[2], acc[3])),
                         "r"(pack_bf16(acc[4], acc[5])), "r"(pack_bf16(acc[6], acc[7])) : "memory");
            __syncwarp();
            if (threadIdx.x == 0) CURVE_REC(3, 62);
            if (lane == 0) mbar_arrive(bars + kBarPiece);
        }
        if (tid < (PUBTMA && wg == 0 && npc ? 2 : 4)) mbar_arrive_cluster<1>(rel_bar + 8 * (kSlotL + (tid >> 1)));
        if (threadIdx.x == 256) CURVE_REC(2, 60);
        };
        if (tid == 0) CURVE_REC(3, 46);
        CLUSTER_WAIT();
        if (tid == 0) CURVE_REC(3, 47);
#pragma unroll
        for (int i = 0; i < 16; i++) p[i] = 0;

        const int tok_in = 1 + wg, tok_out = wg == 2 ? 1 : wg + 2;
#pragma unroll 1
        for (int t = 0; t < kTiles; t++) {
            const uint2 e = *(const uint2*)&tiles[t];
            const uint32_t fl = e.y >> 24, pe = sched.po[t][wg];
            const uint32_t p_addr = sbase + (pe & 0xF8) * 1024 + tid16;
            if ((~fl & (F_FINE | F_P)) == 0) {
#pragma unroll
                for (int q = 0; q < 4; q++)
                    asm volatile("ld.shared.v4.u32 {%0,%1,%2,%3}, [%4];" : "=r"(p[4 * q]), "=r"(p[4 * q + 1]), "=r"(p[4 * q + 2]), "=r"(p[4 * q + 3])
                                 : "r"(p_addr + q * 2048) : "memory");
            }
            const char* swap = (const char*)&g_wfrag[1][rank][slice(wg)][0][0];
            auto init = [&](auto quarter) {
                constexpr int Q = decltype(quarter)::value;
#pragma unroll
                for (int i = 0; i < 8; i++)
                    asm volatile("shl.b32 %0, %4, 16;\nshl.b32 %1, %4, 16;\nand.b32 %2, %4, 0xffff0000;\nand.b32 %3, %4, 0xffff0000;"
                                 : "=f"(acc[4 * i]), "=f"(acc[4 * i + 1]), "=f"(acc[4 * i + 2]), "=f"(acc[4 * i + 3]) : "r"(p[4 * Q + (i & 3)]));
            };
            if (fl & F_FINE) {
                if (fl & F_Q2) {
                    if (fl & F_Q1) init(std::integral_constant<int, 3>());
                    else init(std::integral_constant<int, 2>());
                } else {
                    if (fl & F_Q1) init(std::integral_constant<int, 1>());
                    else {
                        if (DEFER >= 3) reload_w<3>(w, swap, tid16, ~fl & F_P);
                        if (DEFER >= 2) reload_w<4>(w, swap, tid16, ~fl & F_P);
                        if (DEFER >= 1) reload_w<5>(w, swap, tid16, ~fl & F_P);
                        init(std::integral_constant<int, 0>());
                    }
                }
            }
            if (fl & F_READY) {
                if (INLOOP && t == 0) load_w();
                else mbar_wait(bars + kBarReady, 0);
            }
            mbar_wait(bars + kBarFull + (e.x & 0xF8), e.x & 1);
            asm volatile("{\n.reg .pred p;\nsetp.eq.u32 p, %1, 0;\n@p bar.sync %0, 256;\n}\n" ::"r"(tok_in), "r"(pe & 1) : "memory");
            auto body = [&](auto mode) {
                constexpr int M = decltype(mode)::value;
                if (M == 1 && DEFER) asm volatile("{\n.reg .pred p;\nsetp.ne.u32 p, %0, 0;\n@p trap;\n}\n" ::"r"(w[95] & e.y & 0x40000));
                bool rdy = issue_chunk<0>(acc, w, e, bars, b_lo0, true);
                CREC0(0);
                rdy = issue_chunk<1>(acc, w, e, bars, b_lo0, rdy);
                CREC0(1);
                if (TOKEN_K == 2) asm volatile("{\n.reg .pred p;\nsetp.eq.u32 p, %1, 0;\n@p bar.arrive %0, 256;\n}\n" ::"r"(tok_out), "r"(pe & 4) : "memory");
                retire_chunk<0, 1, M>(w, e, sched.wslot[pat], wg, sbase, rel_bar, rel, swap, tid16);
                if (M == 0 && rel && (~fl & (F_FINE | F_P)) == 0) mbar_arrive_cluster<3>(rel_bar + (pe & 0xF8));
                rdy = issue_chunk<2>(acc, w, e, bars, b_lo0, rdy);
                CREC0(2);
                if (TOKEN_K == 3) asm volatile("{\n.reg .pred p;\nsetp.eq.u32 p, %1, 0;\n@p bar.arrive %0, 256;\n}\n" ::"r"(tok_out), "r"(pe & 4) : "memory");
                retire_chunk<1, 1, M>(w, e, sched.wslot[pat], wg, sbase, rel_bar, rel, swap, tid16);
                rdy = issue_chunk<3>(acc, w, e, bars, b_lo0, rdy);
                CREC0(3);
                retire_chunk<2, 1, M>(w, e, sched.wslot[pat], wg, sbase, rel_bar, rel, swap, tid16);
                rdy = issue_chunk<4>(acc, w, e, bars, b_lo0, rdy);
                CREC0(4);
                retire_chunk<3, 1, M>(w, e, sched.wslot[pat], wg, sbase, rel_bar, rel, swap, tid16);
                rdy = issue_chunk<5>(acc, w, e, bars, b_lo0, rdy);
                CREC0(5);
                retire_chunk<4, 1, M>(w, e, sched.wslot[pat], wg, sbase, rel_bar, rel, swap, tid16);
                if (M != 1) mbar_wait(bars + kBarEmpty + (pe >> 11) * 8, (pe >> 9) & 1);
                retire_chunk<5, 0, M>(w, e, sched.wslot[pat], wg, sbase, rel_bar, rel, swap, tid16);
            };
            if (!(fl & F_SWAP)) body(std::integral_constant<int, 0>());
            else if (fl & F_STAGED) body(std::integral_constant<int, 2>());
            else body(std::integral_constant<int, 1>());
            if (fl & F_FINE) {
#pragma unroll
                for (int q = 0; q < 4; q++)
                    asm volatile("stmatrix.sync.aligned.m8n8.x4.trans.shared.b16 [%0], {%1,%2,%3,%4};" ::"r"(st_addr + (pe >> 11) * kChunk + q * 2048),
                                 "r"(pack_bf16(acc[8 * q], acc[8 * q + 1])), "r"(pack_bf16(acc[8 * q + 2], acc[8 * q + 3])),
                                 "r"(pack_bf16(acc[8 * q + 4], acc[8 * q + 5])), "r"(pack_bf16(acc[8 * q + 6], acc[8 * q + 7])) : "memory");
                __syncwarp();
                asm volatile("{\n.reg .pred p;\nelect.sync _|p, 0xffffffff;\n@p mbarrier.arrive.shared::cta.b64 _, [%0];\n}\n" ::"r"(bars + kBarStaged + (pe >> 11) * 8) : "memory");
            } else {
#pragma unroll
                for (int q = 0; q < 4; q++) {
                    p[4 * q] = pack_bf16(acc[8 * q], acc[8 * q + 2]);
                    p[4 * q + 1] = pack_bf16(acc[8 * q + 1], acc[8 * q + 3]);
                    p[4 * q + 2] = pack_bf16(acc[8 * q + 4], acc[8 * q + 6]);
                    p[4 * q + 3] = pack_bf16(acc[8 * q + 5], acc[8 * q + 7]);
                    if (fl & F_P)
                        asm volatile("st.shared.v4.u32 [%0], {%1,%2,%3,%4};" ::"r"(p_addr + q * 2048),
                                     "r"(p[4 * q]), "r"(p[4 * q + 1]), "r"(p[4 * q + 2]), "r"(p[4 * q + 3]) : "memory");
                }
            }
        }
        if (warp_id == 11 && (sched.fin[0] >> lane & 1)) mbar_wait(bars + kBarEmpty + 8 * lane, sched.fin[1] >> lane & 1);
        __syncwarp();
    }
    CLUSTER_ARRIVE();
    CLUSTER_WAIT();
    if (threadIdx.x == 0) CURVE_REC(0, 63);
}

int digit(char ch) { return ch >= 'a' ? ch - 'a' + 10 : ch >= 'A' ? ch - 'A' + 36 : ch - '0'; }
void build_schedule(int pat, Tile* tl, uint16_t (*po)[4], uint32_t* fin, uint8_t (*wslot)[3][8], uint8_t* worder, const int* gs) {
    const char* park = envs("OUT", "00000000000000000000000000000000040000zzzzzz");
    uint8_t out[kTiles][3] = {};
    int parked[kSlots] = {}, nth[kTiles][3];
    const int take[3] = {TAKE}, give[3] = {GIVE};
    const int staged = envi("STAGED", 1), wadv = envi("WADV", 0), wrel = envi("WREL", 1), wslack = envi("WSLACK", 0), wmax = envi("WMAX", 3);
    const char* depth = envs("DEPTH", "zzzzzzzzzzzzzhzzzzzhhdzzzzzzzfggdccbec99gzee");
    int coarse_of[16];
    int n = 0, nsw = 0, swt[2] = {};
    int units[kTiles];
    auto unit = [&](int t) { return units[t]; };
    for (int g = 0, i0 = 0; gs[g]; i0 += gs[g], g++) {
        for (int i = 1; i <= gs[g]; i++, n++) {
            units[n] = i0 + i % gs[g];
            tl[n].pos = (units[n] * NPAT + pat) * (SHAPE ? 4 : 2);
            tl[n].flags = i < gs[g] ? F_P : F_SWAP | (g == 0 ? F_READY : 0);
            coarse_of[unit(n)] = n;
        }
        for (int i = 0; i < 4 * gs[g] && n < kTiles; i++, n++) {
            units[n] = i0 + i / 4;
            tl[n].pos = 0x8000 + (SHAPE ? ((units[n] * NPAT + pat) * 4 + (i & 3)) * kGroup : ((units[n] * NPAT + pat) * 2 + (i & 3) / 2) * kGroup + (i & 1) * 0x1000);
            tl[n].flags = F_FINE | (i >= 4 && (i & 3) == 0 ? F_P : 0) | (i & 1 ? F_Q1 : 0) | (i & 2 ? F_Q2 : 0);
            if (i == 4 * gs[g] - 1 && gs[g + 1]) {
                tl[n].flags |= staged ? F_SWAP | F_STAGED | (nsw ? F_SW1 : 0) : F_SWAP;
                if (staged) swt[nsw++] = n;
            }
        }
    }
    int nwo = 0;
    for (int need = -4; need < 6; need++)
        for (int g = 0; g < 3; g++) {
            const int c = need - give[g];
            if (c < 6 - NSTG || c > 5) continue;
            worder[nwo++] = g * 8 + c;
            for (int i = 0; i < nsw && !wslack; i++) {
                const int j = 6 * swt[i] + need + 4 - wadv;
                tl[j / 6].wcnt += 1 << (2 * (j % 6));
            }
        }
    int uses[kSlots], loads[kSlots], queue[512], head = 0, tail = 0, slot_of[6 * kTiles];
    for (int s = 0; s < kSlots; s++) uses[s] = s >= kSlotL, loads[s] = 0;
    auto take_p = [&](int t, int w, int s) { tl[t].p[w] = s * 8 + ((uses[s] + 1) & 1) * 2; uses[s]++; };
    bool taken[kSlots] = {};
    for (int w = 0; w < 3; w++)
        if (take[w] < 0 && (tl[0].flags & F_P)) take_p(0, w, kSlotW + 6 * w + 2), taken[kSlotW + 6 * w + 2] = true;
    for (int s = 0; s < kSlotL; s++) queue[tail++] = s;
    for (int s = kSlotW; s < kSlots; s++) if (!taken[s]) queue[tail++] = s;
    for (int s = kSlotL; s < kSlotW; s++) queue[tail++] = s;
    int r = 0, wk = 0, wi = 0;
    int rel[512];
    for (int i = 0; i < tail; i++) rel[i] = -1;
    auto get_slot = [&](int from) {
        for (; r < 6 * kTiles; r++) {
            for (int i = head; i < tail; i++)
                if (rel[i] >= from) {
                    const int s = queue[i];
                    for (; i > head; i--) queue[i] = queue[i - 1], rel[i] = rel[i - 1];
                    head++;
                    return s;
                }
            for (int i = tail; i < tail + 16; i++) rel[i] = r;
            bool to_p = false;
            for (int w = 0; w < 3; w++) {
                int x = r - take[w];
                if (x >= 0 && x % 6 == 0 && x / 6 < kTiles && (tl[x / 6].flags & (F_FINE | F_P)) == F_P) take_p(x / 6, w, slot_of[r]), to_p = true;
                if (x >= 0 && x % 6 == 0 && x / 6 < kTiles && (tl[x / 6].flags & F_FINE) && park[x / 6] != '0') {
                    if (head == tail) to_p = true;
                    const int s = to_p ? slot_of[r] : queue[head++];
                    out[x / 6][w] = s * 8 + ((uses[s] + 1) & 1) * 2 + (parked[s] & 1);
                    nth[x / 6][w] = ++uses[s], parked[s]++;
                }
                for (int t = 0; t < kTiles; t++)
                    if ((tl[t].flags & F_FINE) && park[t] != '0' && r == 6 * t + 4 + give[w] + 2 * digit(park[t])) queue[tail++] = out[t][w] >> 3;
            }
            if (!to_p) queue[tail++] = slot_of[r];
            for (int w = 0; w < 3; w++) {
                int x = r - give[w];
                if (x >= 0 && x % 6 == 0 && x / 6 < kTiles && (tl[x / 6].flags & (F_FINE | F_P)) == (F_FINE | F_P)) {
                    tl[x / 6].p[w] = tl[coarse_of[unit(x / 6)]].p[w];
                    queue[tail++] = tl[x / 6].p[w] >> 3;
                }
                x -= wrel;
                if (x >= 0 && x / 6 < kTiles && (tl[x / 6].flags & F_STAGED) && x % 6 >= 6 - NSTG) queue[tail++] = wslot[tl[x / 6].flags >> 7][w][x % 6] >> 3;
            }
        }
        return 0;
    };
    for (int c = 0; c < 6 * kTiles; c++) {
        const char dp = depth[c / 6];
        int s = get_slot(dp == 'z' ? -1 : c - 4 - (dp > '9' ? dp - 'a' + 10 : dp - '0'));
        slot_of[c] = s;
        tl[c / 6].chunk[c % 6] = s * 8 + ((uses[s] + 1) & 1) * 2 + (loads[s] & 1);
        if (c % 6 == 0 && c) tl[c / 6 - 1].chunk[6] = tl[c / 6].chunk[0];
        uses[s]++, loads[s]++;
        for (int k = wslack ? wmax : (tl[c / 6].wcnt >> (2 * (c % 6))) & 3; k; k--) {
            if (wslack) {
                if (wi == nsw || 6 * swt[wi] + (worder[wk] & 7) + give[worder[wk] >> 3] - r > wslack) break;
                tl[c / 6].wcnt += 1 << (2 * (c % 6));
            }
            s = get_slot(-1);
            (&wslot[wi][0][0])[worder[wk]] = s * 8 + ((uses[s] + 1) & 1) * 2;
            uses[s]++;
            if (++wk == 3 * NSTG) wk = 0, wi++;
        }
    }
    get_slot(6 * kTiles);
    fin[0] = (1u << kSlots) - 1, fin[1] = 0;
    for (int s = 0; s < kSlots; s++) fin[1] |= ((uses[s] + 1) & 1) << s;
    for (int t = 0, k = 1; t < kTiles; t++)
        if (!(tl[t].flags & F_FINE)) memcpy(out[t], tl[t].p, 3);
        else if (park[t] == '0') {
            for (int w = 0; w < 3; w++) out[t][w] = (kSlots + w) * 8 + (strchr(park + t + 1, '0') ? 4 : 0) + (k & 1) * 2 + (~k & 1);
            k++;
        } else
            for (int w = 0; w < 3; w++) {
                if (uses[out[t][w] >> 3] > nth[t][w]) out[t][w] |= 4;
                else fin[0] &= ~(1u << (out[t][w] >> 3));
            }
    if (INLOOP) tl[0].flags |= F_READY;
    const char* free_run = envs("NOTOK", "710000000000000000000000000000000000000000071");
    for (int t = 0; t <= kTiles; t++)
        for (int w = 0; w < 3; w++)
            if ((free_run[t] - '0') >> w & 1) {
                tl[t].p[w] |= 1;
                if (w) tl[t].p[w - 1] |= 4;
                else if (t) tl[t - 1].p[2] |= 4;
            }
    for (int t = 0; t < kTiles; t++)
        for (int w = 0; w < 3; w++) po[t][w] = tl[t].p[w] + 256 * out[t][w];
}

typedef CUresult (*EncodeFn)(CUtensorMap*, CUtensorMapDataType, cuuint32_t, void*, const cuuint64_t*, const cuuint64_t*,
                             const cuuint32_t*, const cuuint32_t*, CUtensorMapInterleave, CUtensorMapSwizzle,
                             CUtensorMapL2promotion, CUtensorMapFloatOOBfill);

void encode_2d(EncodeFn enc, CUtensorMap* tm, const void* ptr, uint64_t rows, uint32_t box_rows, CUtensorMapL2promotion promo) {
    cuuint64_t dims[2] = {(cuuint64_t)kC, rows};
    cuuint64_t strides[1] = {(cuuint64_t)kC * 2};
    cuuint32_t box[2] = {64, box_rows};
    cuuint32_t es[2] = {1, 1};
    enc(tm, CU_TENSOR_MAP_DATA_TYPE_BFLOAT16, 2, const_cast<void*>(ptr), dims, strides, box, es, CU_TENSOR_MAP_INTERLEAVE_NONE,
        CU_TENSOR_MAP_SWIZZLE_128B, promo, CU_TENSOR_MAP_FLOAT_OOB_FILL_NONE);
}

}

extern "C" void kernel_launch(void* const* d_in, const int* in_sizes, int n_in, void* d_out, int out_size) {
    (void)in_sizes; (void)n_in; (void)out_size;
    static EncodeFn enc = nullptr;
    static Schedule sched;
    static Scratch* scr;
    if (!enc) {
        cudaGetSymbolAddress((void**)&scr, g_scratch);
        void* fn = nullptr;
        cudaDriverEntryPointQueryResult qr;
        cudaGetDriverEntryPoint("cuTensorMapEncodeTiled", &fn, cudaEnableDefault, &qr);
        enc = (EncodeFn)fn;
        cudaFuncSetAttribute(fpn_lateral_kernel, cudaFuncAttributeMaxDynamicSharedMemorySize, kSmemBytes);
        if (envi("CARVE", 0)) cudaFuncSetAttribute(fpn_lateral_kernel, cudaFuncAttributePreferredSharedMemoryCarveout, envi("CARVE", 0));
        cudaLaunchConfig_t cfg = {};
        cfg.gridDim = dim3(2);
        cfg.blockDim = dim3(512);
        cfg.dynamicSmemBytes = kSmemBytes;
        cudaLaunchAttribute at;
        at.id = cudaLaunchAttributeClusterDimension;
        at.val.clusterDim.x = 2; at.val.clusterDim.y = 1; at.val.clusterDim.z = 1;
        cfg.attrs = &at; cfg.numAttrs = 1;
        int ncl = 0;
        if (cudaOccupancyMaxActiveClusters(&ncl, fpn_lateral_kernel, &cfg) != cudaSuccess) { (void)cudaGetLastError(); ncl = 0; }
        const char* pn[4] = {"PATA", "PATB", "PATC", "PATD"};
        const char* pd[4] = {"45", "45", "36", "63"};
        sched.pgroup = envi("PGROUP", 0), sched.members = sched.pgroup ? kGroup : kClusters;
        for (int q = 0; q < NPAT; q++) {
            int gs[8] = {};
            const char* sa = envs(pn[q], pd[q]);
            for (int i = 0; sa[i]; i++) gs[i] = sa[i] - '0';
            build_schedule(q, sched.tile[q], sched.po, sched.fin, sched.wslot[q], sched.worder, gs);
        }
        {
            const char* gaps = envs("GAPS", "00000lmjonnlnomm0011occkkk0rv000m21107100000");
            const char* lef = envs("LEF", "60000000000000000000000000000000026666666666");
            const uint8_t masks[7] = {0, 1, 9, 0x15, 0x1B, 0x1F, 0x3F};
            for (int t = 0; t < kTiles; t++) {
                const int tr = digit(envs("TRIG", "0000000000000000007d0000000000a007a99gd00000")[t]);
                sched.tile[0][t].pw = tr ? min(EV * t + tr, EV * kTiles) : 0;
                const int d = digit(gaps[t]);
                sched.gap[t] = (d > 36 ? 3 * d - 72 : d) * envi("GUNIT", 75);
                if (gaps[t] != '0' || envi("GALL", 0)) sched.gap_to = t + 1;
                for (int c = 0; c < 6; c++) sched.tile[0][t].chunk[c] |= (masks[lef[t] - '0'] >> c & 1) * 4;
            }
            sched.tstag = envi("TSTAG", 0), sched.gslack = envi("GSLACK", 0);
            const char* lead = envs("LEAD3", "00044000013267hhfnnbakglfnmpnnoommgkifjdcefefbb7ca888888368cbba78aa8799994cb8cddaa9b99579ba88847447986756687776474444440444597chgf77");
            sched.pf_from = envi("PFFROM", 24);
            int pos = sched.pf_from + envi("PF0", 0);
            sched.tgt[0] = pos;
            for (int e = 0; e < EV * kTiles; e++) {
                const int x = (e + 1) * (6 / EV) + digit(lead[e]);
                if (pos < x) pos = x;
                if (pos > 6 * kTiles) pos = 6 * kTiles;
                sched.tgt[e + 1] = pos;
            }
            sched.pw_ev[0] = envi("PW0", 0) * EV / 6 + 1, sched.pw_ev[1] = envi("PW1", 144) * EV / 6 + 1, sched.pw_div = envi("PWDIV", 4);
            sched.t_a = envi("TA", 0), sched.t_d = envi("TD", 290), sched.t_max = envi("TMAX", 0), sched.fsleep = envi("FSLEEP", 0);
        }
        sched.gate1 = envi("GATE1", 1), sched.psleep = envi("PSLEEP", 50);
        sched.pace_from = envi("PACE_FROM", 18), sched.pace_to = envi("PACE_TO", 44);
        const char* v5 = envs("VTA", "55555555555577799664465555332435176767666669");
        const char* vts[4] = {v5, envs("VTB", v5), envs("VTC", v5), envs("VTD", v5)};
        int total = 0;
        for (int q = 0; q < NPAT; q++) {
            int sum[kTiles + 1] = {};
            for (int t = sched.pace_from; t < sched.pace_to; t++) sum[t] = sum[t - 1] + vts[q][t] - '0';
            total = sum[sched.pace_to - 1];
            for (int t = sched.pace_from; t < sched.pace_to; t++) {
                sched.vt[q][t] = sum[t] * kVt / total;
                const int slack = digit(envs("SLK", "000000000jlonpzzmihskfe7eg73ffcae59f5caedd7x")[t]) * 8;
                sched.need[q][t] = ncl >= kClusters ? 65536 - kVt * kClusters + sched.vt[q][t] * sched.members - slack * 5 * kVt / total * sched.members / 64 : -1;
            }
        }
    }
    CUtensorMap tm_fine, tm_coarse, tm_coarse2, tm_wlat, tm_wout, tm_out;
    const cuuint32_t ones[5] = {1, 1, 1, 1, 1};
    {
        cuuint64_t dims[5] = {(cuuint64_t)kC, 2, 4, 4, (cuuint64_t)kFinePix / 32};
        cuuint64_t strides[4] = {768, 2 * 768, 8 * 768, 32 * 768};
        cuuint32_t box[5] = {64, 2, 4, 4, 1};
        enc(&tm_fine, CU_TENSOR_MAP_DATA_TYPE_BFLOAT16, 5, d_in[0], dims, strides, box, ones, CU_TENSOR_MAP_INTERLEAVE_NONE,
            CU_TENSOR_MAP_SWIZZLE_128B, CU_TENSOR_MAP_L2_PROMOTION_L2_128B, CU_TENSOR_MAP_FLOAT_OOB_FILL_NONE);
    }
    {
        cuuint64_t dims[3] = {64, (cuuint64_t)kC, 6};
        cuuint64_t strides[2] = {768, 128};
        cuuint32_t box[3] = {64, 16, 6};
        cuuint32_t es[3] = {1, 1, 1};
        enc(&tm_wlat, CU_TENSOR_MAP_DATA_TYPE_BFLOAT16, 3, d_in[2], dims, strides, box, es, CU_TENSOR_MAP_INTERLEAVE_NONE,
            CU_TENSOR_MAP_SWIZZLE_128B, CU_TENSOR_MAP_L2_PROMOTION_L2_256B, CU_TENSOR_MAP_FLOAT_OOB_FILL_NONE);
    }
    encode_2d(enc, &tm_wout, d_in[3], kC, 192, CU_TENSOR_MAP_L2_PROMOTION_L2_256B);
    {
        cuuint64_t dims[4] = {(cuuint64_t)kC, 32, 2, (cuuint64_t)kFinePix / 32 - kRankF};
        cuuint64_t strides[3] = {768, kRankF * 32 * 768, 32 * 768};
        cuuint32_t box[4] = {64, 32, 2, 1};
        enc(&tm_out, CU_TENSOR_MAP_DATA_TYPE_BFLOAT16, 4, d_out, dims, strides, box, ones, CU_TENSOR_MAP_INTERLEAVE_NONE,
            CU_TENSOR_MAP_SWIZZLE_128B, CU_TENSOR_MAP_L2_PROMOTION_NONE, CU_TENSOR_MAP_FLOAT_OOB_FILL_NONE);
    }
    {
        cuuint64_t dims[5] = {(cuuint64_t)kC, 2, 4, kGroup * kSeg / 8, 35};
        cuuint64_t strides[4] = {4 * 768, 768, 8 * 768, kGroup * kSeg * 768};
        cuuint32_t box[5] = {64, 2, 4, kSeg / 8, 32 / kSeg};
        enc(&tm_coarse, CU_TENSOR_MAP_DATA_TYPE_BFLOAT16, 5, d_in[1], dims, strides, box, ones, CU_TENSOR_MAP_INTERLEAVE_NONE,
            CU_TENSOR_MAP_SWIZZLE_128B, CU_TENSOR_MAP_L2_PROMOTION_L2_128B, CU_TENSOR_MAP_FLOAT_OOB_FILL_NONE);
        dims[4] = 34;
        enc(&tm_coarse2, CU_TENSOR_MAP_DATA_TYPE_BFLOAT16, 5, d_in[1], dims, strides, box, ones, CU_TENSOR_MAP_INTERLEAVE_NONE,
            CU_TENSOR_MAP_SWIZZLE_128B, CU_TENSOR_MAP_L2_PROMOTION_L2_128B, CU_TENSOR_MAP_FLOAT_OOB_FILL_NONE);
    }
    fpn_lateral_kernel<<<2 * kClusters, 512, kSmemBytes>>>(scr, (const char*)d_in[0], (const char*)d_in[1], (const char*)d_in[2], (const char*)d_in[3],
                                                          tm_fine, tm_coarse, tm_coarse2, tm_wlat, tm_wout, tm_out, sched);
}
```

```cpp
#include <cuda_runtime.h>
#include <cuda_bf16.h>
#include <cuda.h>
#include <stdint.h>
#include <string.h>
#include <type_traits>
#include <stdlib.h>

#define TOKEN_K 3
#define TAKE -2, 0, 2
#define GIVE -4, -2, 0
#define L_POS 0
#define NSTG 6
#define EV 3
#define STPOL 0
#define NO_MMA 0
#define EARLY 1
#define EARLY_T 0
#define W_PRE 0
#define TOPPF 1
#define TLBW 1
#define W_MIX 0x1E
#define WR 1
#define CHAINS 1
#define ROT 0
#define PUBTMA 1
#define DEFER 2
#define INLOOP 1
#define WSPLIT 1
#define TPF_N 0
#define TPF_A 400
#define TPF_D 300
#define FIN 2
#define ENDBAR 1
#define NPAT 1
#define SHAPE 1
#define OBUF 1
#define LD_EF 1
#define CURVE_REC(k, i) do {} while (0)

#define CREC0(c) do {} while (0)
namespace {

constexpr int kC = 384;
constexpr int kFinePix = 384 * 384;
constexpr int kCoarsePix = 192 * 192;
constexpr int kClusters = 66;
constexpr int kTiles = 44;
constexpr int kFull = 2304 - 34 * kClusters;
constexpr int kVt = 65536 / kClusters;
#define SLOTS (28 - 3 * OBUF)
constexpr int kSlots = SLOTS;
#define GT 1
#define ILV 0
constexpr int kColR = ILV ? 64 : 192, kColG = ILV ? 128 : 64;
constexpr int kChunk = 8192;
constexpr int kTileBytes = 6 * kChunk;
constexpr int kOffOut = kSlots * kChunk;
constexpr int kOffBar = kOffOut + 3 * OBUF * kChunk;
constexpr int kSmemBytes = kOffBar + 1024;
constexpr int kSlotL = kSlots + 3 * OBUF - 20;
constexpr int kSlotW = kSlots + 3 * OBUF - 18;
constexpr int kBarFull = 0, kBarEmpty = 8 * kSlots, kBarStaged = kBarEmpty + 8 * (kSlots + 3), kBarW = kBarStaged + 8 * (kSlots + 3), kBarL = kBarW + 24;
constexpr int kBarPiece = kBarL + 8, kBarReady = kBarPiece + 8;
constexpr int kBarSwap = kBarReady + 8;
constexpr int kBarReady2 = kBarSwap + 56;
constexpr int kStarted = kBarSwap + 192, kAllowed = kStarted + 4;
constexpr int kBarW2 = WSPLIT ? kStarted + 8 : kBarW;
constexpr int kPos0 = 4;
constexpr int kPieces = 24;

enum : uint32_t { F_FINE = 1, F_P = 2, F_Q1 = 4, F_SWAP = 8, F_READY = 16, F_Q2 = 32, F_STAGED = 64, F_SW1 = 128 };
struct alignas(16) Tile {
    uint8_t chunk[7];
    uint8_t flags;
    uint8_t p[3];
    uint8_t pw;
    uint16_t pos;
    uint16_t wcnt;
};
constexpr int kGroup = kClusters / NPAT;
struct Schedule {
    Tile tile[NPAT][kTiles + 1];
    uint16_t tgt[EV * kTiles + 2];
    alignas(8) uint8_t wslot[NPAT][2][3][8];
    uint8_t worder[24];
    uint16_t po[kTiles][4];
    uint32_t fin[2];
    uint16_t stag[48];
    uint16_t gap[48];
    int members, pgroup, gslack, gap_to;
    int pace_from, pace_to, gate1, psleep, pf_from, pw_ev[2], pw_div, t_a, t_d, t_max, fsleep;
    int need[NPAT][kTiles + 1];
    uint16_t vt[NPAT][kTiles + 1];
};
static int envi(const char*, int d) { return d; }
static const char* envs(const char*, const char* d) { return d; }

struct Scratch {
    uint4 wfrag[2][2][3][24][128];
    uint32_t ready, pad0[31];
    uint32_t done, pad1[31];
    uint32_t progress[4][32];
};
__device__ Scratch g_scratch;
#define g_wfrag scr->wfrag
#define g_ready scr->ready
#define g_done scr->done
#define g_progress scr->progress

__device__ __forceinline__ uint32_t smem_u32(const void* p) { return (uint32_t)__cvta_generic_to_shared(p); }

__device__ __forceinline__ void mbar_init(uint32_t bar, uint32_t count) {
    asm volatile("mbarrier.init.shared::cta.b64 [%0], %1;" ::"r"(bar), "r"(count) : "memory");
}
__device__ __forceinline__ void mbar_expect_tx(uint32_t bar, uint32_t bytes) {
    asm volatile("mbarrier.arrive.expect_tx.shared::cta.b64 _, [%0], %1;" ::"r"(bar), "r"(bytes) : "memory");
}
__device__ __forceinline__ void mbar_wait(uint32_t bar, uint32_t parity) {
    asm volatile(
        "{\n"
        ".reg .pred p;\n"
        ".reg .u32 n;\n"
        "mov.u32 n, 0;\n"
        "WAIT_LOOP:\n"
        "mbarrier.try_wait.parity.shared::cta.b64 p, [%0], %1;\n"
        "@p bra WAIT_DONE;\n"
        "add.u32 n, n, 1;\n"
        "setp.lt.u32 p, n, 0x400000;\n"
        "@p bra WAIT_LOOP;\n"
        "trap;\n"
        "WAIT_DONE:\n"
        "}\n" ::"r"(bar), "r"(parity) : "memory");
}
__device__ __forceinline__ void mbar_wait1(uint32_t bar, uint32_t parity) {
    uint32_t r;
    asm volatile("{\n.reg .pred p;\nmbarrier.try_wait.parity.shared::cta.b64 p, [%1], %2;\nselp.u32 %0, 1, 0, p;\n}\n" : "=r"(r) : "r"(bar), "r"(parity) : "memory");
    if (!r) mbar_wait(bar, parity);
}
__device__ __forceinline__ bool mbar_test(uint32_t bar, uint32_t parity) {
    uint32_t r;
    asm volatile("{\n.reg .pred p;\nmbarrier.test_wait.parity.shared::cta.b64 p, [%1], %2;\nselp.u32 %0, 1, 0, p;\n}\n" : "=r"(r) : "r"(bar), "r"(parity) : "memory");
    return r != 0;
}
__device__ __forceinline__ void mbar_arrive(uint32_t bar) {
    asm volatile("mbarrier.arrive.shared::cta.b64 _, [%0];" ::"r"(bar) : "memory");
}
template <int N>
__device__ __forceinline__ void mbar_arrive_cluster(uint32_t bar) {
    if (N == 1) asm volatile("mbarrier.arrive.shared::cluster.b64 _, [%0];" ::"r"(bar) : "memory");
    else asm volatile("mbarrier.arrive.shared::cluster.b64 _, [%0], %1;" ::"r"(bar), "n"(N) : "memory");
}
__device__ __forceinline__ void bulk_load(uint32_t dst, const void* src, uint32_t bar) {
    asm volatile("cp.async.bulk.shared::cluster.global.mbarrier::complete_tx::bytes [%0], [%1], %2, [%3];"
                 ::"r"(dst), "l"(src), "n"(kChunk), "r"(bar) : "memory");
}
__device__ __forceinline__ void tma_load_2d(uint32_t dst, const CUtensorMap* tm, int c0, int c1, uint32_t bar) {
    asm volatile("cp.async.bulk.tensor.2d.shared::cluster.global.mbarrier::complete_tx::bytes [%0], [%1, {%2, %3}], [%4];"
                 ::"r"(dst), "l"(tm), "r"(c0), "r"(c1), "r"(bar) : "memory");
}
__device__ __forceinline__ void tma_load_3d(uint32_t dst, const CUtensorMap* tm, int c1, uint32_t bar) {
    asm volatile("cp.async.bulk.tensor.3d.shared::cluster.global.mbarrier::complete_tx::bytes [%0], [%1, {%2, %3, %2}], [%4];"
                 ::"r"(dst), "l"(tm), "r"(0), "r"(c1), "r"(bar) : "memory");
}
template <bool HINT>
__device__ __forceinline__ void tma_load_5d_mc(uint32_t dst, const CUtensorMap* tm, int c0, int c3, int c4, uint32_t bar, uint64_t pol) {
    if (HINT) asm volatile("cp.async.bulk.tensor.5d.shared::cluster.global.mbarrier::complete_tx::bytes.multicast::cluster.L2::cache_hint [%0], [%1, {%2, %3, %3, %4, %5}], [%6], %7, %8;"
                 ::"r"(dst), "l"(tm), "r"(c0), "r"(0), "r"(c3), "r"(c4), "r"(bar), "h"((uint16_t)3), "l"(pol) : "memory");
    else asm volatile("cp.async.bulk.tensor.5d.shared::cluster.global.mbarrier::complete_tx::bytes.multicast::cluster [%0], [%1, {%2, %3, %3, %4, %5}], [%6], %7;"
                 ::"r"(dst), "l"(tm), "r"(c0), "r"(0), "r"(c3), "r"(c4), "r"(bar), "h"((uint16_t)3) : "memory");
}
__device__ __forceinline__ void tma_store_4d(const CUtensorMap* tm, uint32_t src, int c0, int c3, uint64_t pol) {
    if (STPOL) asm volatile("cp.async.bulk.tensor.4d.global.shared::cta.bulk_group.L2::cache_hint [%0, {%2, %3, %3, %4}], [%1], %5;"
                 ::"l"(tm), "r"(src), "r"(c0), "r"(0), "r"(c3), "l"(pol) : "memory");
    else asm volatile("cp.async.bulk.tensor.4d.global.shared::cta.bulk_group [%0, {%2, %3, %3, %4}], [%1];"
                 ::"l"(tm), "r"(src), "r"(c0), "r"(0), "r"(c3) : "memory");
}
__device__ __forceinline__ void prefetch_l2(const void* p) {
    asm volatile("prefetch.global.L2 [%0];" ::"l"(p) : "memory");
}
__device__ __forceinline__ void prefetch_tm(const CUtensorMap* tm) {
    asm volatile("prefetch.tensormap [%0];" ::"l"(tm) : "memory");
}
__device__ __forceinline__ uint32_t now_ns() {
    uint32_t t;
    asm volatile("mov.u32 %0, %globaltimer_lo;" : "=r"(t));
    return t;
}
__device__ __forceinline__ bool elect_one() {
    uint32_t p;
    asm volatile("{\n.reg .pred p;\nelect.sync _|p, 0xffffffff;\nselp.u32 %0, 1, 0, p;\n}\n" : "=r"(p));
    return p != 0;
}
#define CLUSTER_ARRIVE() asm volatile("barrier.cluster.arrive.relaxed.aligned;" ::: "memory")
#define CLUSTER_WAIT() asm volatile("barrier.cluster.wait.acquire.aligned;" ::: "memory")

#define WG_FENCE() asm volatile("wgmma.fence.sync.aligned;" ::: "memory")
#define WG_COMMIT() asm volatile("wgmma.commit_group.sync.aligned;" ::: "memory")
#define WG_WAIT(n) asm volatile("wgmma.wait_group.sync.aligned %0;" ::"n"(n) : "memory")

#define ACC32 "{%0,%1,%2,%3,%4,%5,%6,%7,%8,%9,%10,%11,%12,%13,%14,%15,%16,%17,%18,%19,%20,%21,%22,%23,%24,%25,%26,%27,%28,%29,%30,%31}"
#define ACC8(b) "+f"(d[b]), "+f"(d[b + 1]), "+f"(d[b + 2]), "+f"(d[b + 3]), "+f"(d[b + 4]), "+f"(d[b + 5]), "+f"(d[b + 6]), "+f"(d[b + 7])

#define DESC_HI "0x40000040"
template <int BOFF>
__device__ __forceinline__ void wgmma_rs(float (&d)[32], const uint32_t* a, uint32_t b_lo) {
    asm volatile("{\n.reg .b32 tb;\n.reg .b64 db;\nadd.u32 tb, %36, %37;\nmov.b64 db, {tb, " DESC_HI "};\n"
                 "wgmma.mma_async.sync.aligned.m64n64k16.f32.bf16.bf16 " ACC32 ", {%32,%33,%34,%35}, db, 1, 1, 1, 0;\n}\n"
                 : ACC8(0), ACC8(8), ACC8(16), ACC8(24)
                 : "r"(a[0]), "r"(a[1]), "r"(a[2]), "r"(a[3]), "r"(b_lo), "n"(BOFF));
}
__device__ __forceinline__ void wgmma_rs_first(float (&d)[32], const uint32_t* a, uint32_t b_lo, uint32_t accum) {
    asm volatile("{\n.reg .pred p;\n.reg .b64 db;\nsetp.ne.u32 p, %37, 0;\nmov.b64 db, {%36, " DESC_HI "};\n"
                 "wgmma.mma_async.sync.aligned.m64n64k16.f32.bf16.bf16 " ACC32 ", {%32,%33,%34,%35}, db, p, 1, 1, 0;\n}\n"
                 : ACC8(0), ACC8(8), ACC8(16), ACC8(24)
                 : "r"(a[0]), "r"(a[1]), "r"(a[2]), "r"(a[3]), "r"(b_lo), "r"(accum));
}
template <int ACCUM, int BOFF, int D>
__device__ __forceinline__ void wgmma_rs16(float (&d)[32], const uint32_t* a, uint32_t b_lo) {
    asm volatile("{\n.reg .b32 tb;\n.reg .b64 db;\nadd.u32 tb, %12, %13;\nmov.b64 db, {tb, " DESC_HI "};\n"
                 "wgmma.mma_async.sync.aligned.m64n16k16.f32.bf16.bf16 {%0,%1,%2,%3,%4,%5,%6,%7}, {%8,%9,%10,%11}, db, %14, 1, 1, 0;\n}\n"
                 : ACC8(D)
                 : "r"(a[0]), "r"(a[1]), "r"(a[2]), "r"(a[3]), "r"(b_lo), "n"(BOFF), "n"(ACCUM));
}
template <int S>
__device__ __forceinline__ void piece_steps(float (&d)[32], const uint32_t (&w)[96], uint32_t b_lo) {
    if constexpr (S < 24) {
        wgmma_rs16<(S >= CHAINS), (S >> 2) * 128 + (S & 3) * 2, S % CHAINS * 8>(d, &w[4 * S], b_lo);
        piece_steps<S + 1>(d, w, b_lo);
    }
}

__device__ __forceinline__ uint32_t pack_bf16(float lo, float hi) {
    uint32_t r;
    asm("cvt.rn.bf16x2.f32 %0, %1, %2;" : "=r"(r) : "f"(hi), "f"(lo));
    return r;
}

template <int C>
__device__ __forceinline__ void reload_w(uint32_t (&w)[96], const char* base, uint32_t tid16, uint32_t on) {
#define W4(i) "+r"(w[16 * C + 4 * i]), "+r"(w[16 * C + 4 * i + 1]), "+r"(w[16 * C + 4 * i + 2]), "+r"(w[16 * C + 4 * i + 3])
    asm volatile("{\n.reg .pred p;\n.reg .b64 a;\nsetp.ne.u32 p, %19, 0;\ncvt.u64.u32 a, %18;\nadd.u64 a, a, %16;\n"
                 "@p ld.global.cg.v4.u32 {%0,%1,%2,%3}, [a + %17];\n"
                 "@p ld.global.cg.v4.u32 {%4,%5,%6,%7}, [a + %17 + 2048];\n"
                 "@p ld.global.cg.v4.u32 {%8,%9,%10,%11}, [a + %17 + 4096];\n"
                 "@p ld.global.cg.v4.u32 {%12,%13,%14,%15}, [a + %17 + 6144];\n}\n"
                 : W4(0), W4(1), W4(2), W4(3)
                 : "l"(base), "n"(C * 8192), "r"(tid16), "r"(on) : "memory");
#undef W4
}

template <int C>
__device__ __forceinline__ uint32_t entry(uint2 e) { return C < 4 ? e.x >> (8 * C) : e.y >> (8 * (C - 4)); }

template <int C>
__device__ __forceinline__ bool issue_chunk(float (&acc)[32], const uint32_t (&w)[96], uint2 e, uint32_t bars, uint32_t b_lo0, bool ready) {
    if (!ready) mbar_wait(bars + kBarFull + (entry<C>(e) & 0xF8), entry<C>(e) & 1);
    const bool next = C < 5 && mbar_test(bars + kBarFull + (entry<C + 1>(e) & 0xF8), entry<C + 1>(e) & 1);
    const uint32_t b_lo = b_lo0 + (entry<C>(e) & 0xF8) * 64;
    if (!NO_MMA) {
        WG_FENCE();
        if (C == 0) wgmma_rs_first(acc, &w[0], b_lo, e.y & (F_FINE << 24));
        else wgmma_rs<0>(acc, &w[16 * C], b_lo);
        wgmma_rs<2>(acc, &w[16 * C + 4], b_lo);
        wgmma_rs<4>(acc, &w[16 * C + 8], b_lo);
        wgmma_rs<6>(acc, &w[16 * C + 12], b_lo);
        WG_COMMIT();
    }
    return next;
}
template <int C, int PENDING, int MODE>
__device__ __forceinline__ void retire_chunk(uint32_t (&w)[96], uint2 e, const uint8_t (*ws)[3][8], int wg, uint32_t sbase, uint32_t rel_bar, bool rel, const char* swap, uint32_t tid16) {
    if (!NO_MMA) WG_WAIT(PENDING);
    if (rel) mbar_arrive_cluster<1>(rel_bar + (entry<C>(e) & 0xF8));
    if (MODE == 1 && C < 6 - DEFER) reload_w<C>(w, swap, tid16, 1);
    if (MODE == 2 && C >= 6 - NSTG) {
        const uint32_t x = ws[e.y >> 31][wg][C];
        mbar_wait(sbase + kOffBar + kBarSwap + 64 * wg + 8 * C, e.y >> 31);
        const uint32_t a = sbase + (x & 0xF8) * 1024 + tid16;
#pragma unroll
        for (int q = 0; q < 4; q++)
            asm volatile("ld.shared.v4.u32 {%0,%1,%2,%3}, [%4];" : "=r"(w[16 * C + 4 * q]), "=r"(w[16 * C + 4 * q + 1]), "=r"(w[16 * C + 4 * q + 2]), "=r"(w[16 * C + 4 * q + 3])
                         : "r"(a + q * 2048) : "memory");
        asm volatile("bar.sync %0, 128;" ::"r"(4 + wg + ((w[16 * C] | w[16 * C + 4] | w[16 * C + 8] | w[16 * C + 12]) & x & 1)) : "memory");
        if (rel) mbar_arrive_cluster<3>(rel_bar + (x & 0xF8));
    }
}

__device__ __forceinline__ int pub_slot(int g) { return g == 0 ? kSlotL + 1 : g == 1 ? kSlotW + 11 : kSlotW + 14; }
__device__ __forceinline__ int fine_group(uint32_t pos, int ci) {
    const uint32_t q = (pos & 0xFFF) + ci;
    return SHAPE ? q + q / 12 * 12 : 2 * q + (q / 6 + ((pos >> 12) & 1)) * 12;
}
constexpr int kRankF = SHAPE ? 12 : 1, kRankC = SHAPE ? 2 : 1, kSeg = SHAPE ? 16 : 32;
template <int L0, int L1>
__device__ __forceinline__ void prefetch_tile(uint32_t pos, int ci, int rank, int lane, const char* fine, const char* coarse) {
    const bool f = pos & 0x8000;
    const uint32_t row = f ? (fine_group(pos, ci) + kRankF * rank) * 32 : (((pos & 0xFFF) + kRankC * rank) * kGroup + ci) * kSeg;
    const char* p = (f ? fine : coarse) + (size_t)row * 768 + lane * 128;
    const char* q = SHAPE && !f ? p + (kGroup - 1) * kSeg * 768 : p;
#pragma unroll
    for (int l = L0; l < L1; l++) prefetch_l2((l < 3 ? p : q) + l * 4096);
}

__global__ void __cluster_dims__(2, 1, 1) __launch_bounds__(512, 1)
fpn_lateral_kernel(Scratch* const scr, const char* __restrict__ fine, const char* __restrict__ coarse,
                   const char* __restrict__ wlat, const char* __restrict__ wout,
                   const __grid_constant__ CUtensorMap tm_fine, const __grid_constant__ CUtensorMap tm_coarse, const __grid_constant__ CUtensorMap tm_coarse2,
                   const __grid_constant__ CUtensorMap tm_wlat, const __grid_constant__ CUtensorMap tm_wout,
                   const __grid_constant__ CUtensorMap tm_out, const __grid_constant__ Schedule sched) {
    extern __shared__ __align__(1024) unsigned char smem_raw[];
    if (threadIdx.x == 0) CURVE_REC(0, 0);
    uint32_t t_start;
    asm volatile("mov.u32 %0, %clock;" : "=r"(t_start));
    const uint32_t sbase = smem_u32(smem_raw);
    const uint32_t bars = sbase + kOffBar;
    const int rot = !ROT ? 0 : blockIdx.x < 4 * kPieces ? blockIdx.x & 2 : 1;
    const int npc = !ROT ? (blockIdx.x < 2 * kPieces ? 3 : 0) : blockIdx.x < 4 * kPieces ? 2 - (rot >> 1) : 0;
    const int pj = blockIdx.x >> (1 + ROT);
    auto slice = [&](int g) { return g + rot >= 3 ? g + rot - 3 : g + rot; };
    if (threadIdx.x == EARLY_T) {
        mbar_init(bars + kBarW, 1);
        if (WSPLIT) mbar_init(bars + kBarW2, 1);
        mbar_init(bars + kBarL, 1);
        asm volatile("fence.proxy.async.shared::cta;" ::: "memory");
        mbar_expect_tx(bars + kBarW, kTileBytes >> WSPLIT);
        if (WSPLIT) mbar_expect_tx(bars + kBarW2, kTileBytes >> WSPLIT);
        for (int c = 0; c < 2; c++) tma_load_2d(sbase + (kSlotW + 3 * c) * kChunk, &tm_wout, (blockIdx.x & 1) * kColR + rot * kColG, c * 192, bars + (c ? kBarW2 : kBarW));
        prefetch_tm(&tm_coarse);
        if (npc) {
            mbar_expect_tx(bars + kBarL, 6 * 2048);
            tma_load_3d(sbase + kSlotL * kChunk, &tm_wlat, pj * 16, bars + kBarL);
        }
        asm volatile("fence.mbarrier_init.release.cluster;" ::: "memory");
        CURVE_REC(1, 47);
    }
    {
        constexpr int kWw = (36 * WR + 31) / 32;
        const uint32_t t = threadIdx.x - 32, b = blockIdx.x, c = (t >> 5) - kWw, l = ((b >> 1) % (64 / WR)) * (36 * WR) + t;
        const uint32_t row = ((kPos0 + kRankC * (b & 1) + ((t >> 4) & 1)) * kGroup + (b >> 1)) * kSeg + (t & 15);
        const char* p = t >= 32 * kWw ? coarse + row * 768 + c * 128 : (b & 1 ? wlat : wout) + l * 128;
        if (t < 36 * WR || c < TOPPF) prefetch_l2(p);
    }
    const int warp_id = __shfl_sync(0xffffffffu, (int)(threadIdx.x >> 5), 0);
    const int lane = threadIdx.x & 31;
    const int wg = warp_id >> 2;
    const int rank = blockIdx.x & 1;
    const int cid = blockIdx.x >> 1;
    const int pat = cid % NPAT, ci = cid / NPAT;
    const Tile* const tiles = sched.tile[pat];

    if (wg == 3) {
        asm volatile("setmaxnreg.dec.sync.aligned.u32 32;");
        const int j = warp_id & 3;
        const bool lead = elect_one();
        if (j == 3) {
            uint32_t c0;
            asm volatile("mov.u32 %0, %clock;" : "=r"(c0));
            if (lead) CURVE_REC(1, 46);
            if (lead) {
                mbar_init(bars + kBarW + 8, 1);
                mbar_init(bars + kBarW + 16, 1);
                if (WSPLIT) mbar_init(bars + kBarW2 + 8, 1), mbar_init(bars + kBarW2 + 16, 1);
                asm volatile("fence.mbarrier_init.release.cluster;" ::: "memory");
                asm volatile("fence.proxy.async.shared::cta;" ::: "memory");
            }
            __syncwarp();
            CLUSTER_ARRIVE();
            if (lead) {
                for (int g = 1; g < 3; g++) {
                    mbar_expect_tx(bars + kBarW + 8 * g, kTileBytes >> WSPLIT);
                    if (WSPLIT) mbar_expect_tx(bars + kBarW2 + 8 * g, kTileBytes >> WSPLIT);
                }
                for (int g = 2; g < 2 + W_PRE; g++) tma_load_2d(sbase + (kSlotW + 3 * g) * kChunk, &tm_wout, rank * kColR + slice(g >> 1) * kColG, (g & 1) * 192, bars + (g & 1 ? kBarW2 : kBarW) + 8 * (g >> 1));
            }
            __syncwarp();
            CLUSTER_WAIT();
            if (lead) {
                int g = 2 + W_PRE;
#pragma unroll 1
                for (int c = 0; c < 6; c++) {
                    mbar_expect_tx(bars + kBarFull + 8 * c, kChunk);
                    tma_load_5d_mc<false>(sbase + rank * 4096 + c * kChunk, &tm_coarse, c * 64, ci * (kSeg / 8), kPos0 + kRankC * rank, bars + kBarFull + 8 * c, 0);
                    CURVE_REC(1, 52 + c);
                    if ((W_MIX >> c & 1) && g < 6) {
                        tma_load_2d(sbase + (kSlotW + 3 * g) * kChunk, &tm_wout, rank * kColR + slice(g >> 1) * kColG, (g & 1) * 192, bars + (g & 1 ? kBarW2 : kBarW) + 8 * (g >> 1));
                        g++;
                    }
                }
#pragma unroll 1
                for (; g < 6; g++) {
                    tma_load_2d(sbase + (kSlotW + 3 * g) * kChunk, &tm_wout, rank * kColR + slice(g >> 1) * kColG, (g & 1) * 192, bars + (g & 1 ? kBarW2 : kBarW) + 8 * (g >> 1));
                    CURVE_REC(1, 47 + (g >> 1));
                }
            }
            __syncwarp();
            uint32_t cur = sched.pf_from, u = 0, pw = sched.pw_ev[0] == 1;
            const char* p = nullptr;
            bool ok = false;
#pragma unroll 1
            for (uint32_t n = 0; cur < 6 * kTiles; n++) {
                uint32_t v;
                asm volatile("ld.volatile.shared.u32 %0, [%1];" : "=r"(v) : "r"(bars + kStarted) : "memory");
                uint32_t tgt = sched.tgt[v];
                if (cur < sched.t_max) {
                    uint32_t c;
                    asm volatile("mov.u32 %0, %clock;" : "=r"(c));
                    if ((int)(c - c0) >= (int)(sched.t_a + cur * sched.t_d)) tgt = max(tgt, cur + 1);
                }
#pragma unroll 1
                for (; cur < tgt; cur++) {
                    if (u == 0) {
                        const uint32_t pos = tiles[cur / 6].pos;
                        const bool f = pos & 0x8000;
                        const uint32_t row = f ? (fine_group(pos, ci) + kRankF * rank) * 32 + lane : (((pos & 0xFFF) + kRankC * rank + (lane >> 4)) * kGroup + ci) * kSeg + (lane & 15);
                        p = (f ? fine : coarse) + (size_t)row * 768;
                        ok = row < (f ? kFinePix : kCoarsePix);
                    }
                    if (ok) prefetch_l2(p);
                    p += 128;
                    u = u == 5 ? 0 : u + 1;
                }
                if (pw < 2 && v >= sched.pw_ev[pw]) {
                    const char* q = (const char*)&g_wfrag[pw][rank][0][0][0] + lane * 128;
#pragma unroll 1
                    for (int l = ci % sched.pw_div; l < 36; l += sched.pw_div) prefetch_l2(q + l * 4096);
                    pw++;
                }
                if (n == 0x1000000) __trap();
                __nanosleep(sched.fsleep);
            }
        } else if (j == 2) {
            if (lead) CURVE_REC(1, 58);
            CLUSTER_ARRIVE();
            if (lead) {
                uint32_t v;
                asm volatile("ld.relaxed.gpu.global.u32 %0, [%1];" : "=r"(v) : "l"(&g_ready) : "memory");
            }
            if (lead) {
                CURVE_REC(1, 59);
                prefetch_tm(&tm_fine);
                prefetch_tm(&tm_coarse2);
                prefetch_tm(&tm_out);
            }
            __syncwarp();
            CLUSTER_WAIT();
            if (lead) {
                if (npc) {
                    mbar_wait(bars + kBarPiece, 0);
                    asm volatile("fence.proxy.async.shared::cta;" ::: "memory");
                    for (int i = 0; i < 2 * npc; i++)
                        asm volatile("cp.async.bulk.global.shared::cta.bulk_group [%0], [%1], 2048;"
                                     ::"l"(&g_wfrag[i & 1][rank][slice(i >> 1)][pj][0]), "r"(sbase + pub_slot(i >> 1) * kChunk + 4096 + (i & 1) * 2048) : "memory");
                    asm volatile("cp.async.bulk.commit_group;" ::: "memory");
                    asm volatile("cp.async.bulk.wait_group.read 0;" ::: "memory");
                    for (int i = 0; i < 2 * npc; i++) {
                        uint32_t b;
                        asm("mapa.shared::cluster.u32 %0, %1, %2;" : "=r"(b) : "r"(bars + kBarEmpty + 8 * pub_slot(i >> 1)), "r"(i & 1));
                        asm volatile("mbarrier.arrive.shared::cluster.b64 _, [%0], %1;" ::"r"(b), "r"(i < 2 ? 1 : 3) : "memory");
                    }
                    asm volatile("cp.async.bulk.wait_group 0;" ::: "memory");
                    asm volatile("red.relaxed.gpu.global.add.u32 [%0], 1;" ::"l"(&g_ready) : "memory");
                    CURVE_REC(2, 61);
                }
                uint32_t v, n = 0;
                for (;;) {
                    asm volatile("ld.acquire.gpu.global.u32 %0, [%1];" : "=r"(v) : "l"(&g_ready) : "memory");
                    if (v >= (2 * kPieces << ROT)) break;
                    if (++n == 0x100000) __trap();
                    __nanosleep(50);
                }
                CURVE_REC(2, 62);
                mbar_arrive(bars + kBarReady);
                asm volatile("fence.proxy.async.global;" ::: "memory");
                mbar_arrive(bars + kBarReady2);
                if (atomicAdd(&g_done, 1) == gridDim.x - 1) {
                    g_ready = 0;
                    g_done = 0;
                }
                asm volatile("st.volatile.shared.u32 [%0], %1;" ::"r"(bars + kAllowed), "r"(rank == 0 || sched.gate1 ? sched.pace_from : kTiles) : "memory");
                if (rank == 0 || sched.gate1) {
                    const uint16_t* vt = sched.vt[pat];
                    uint32_t* const ctr = g_progress[sched.pgroup * pat];
                    const int last = sched.pace_to - 1;
                    asm volatile("ld.relaxed.gpu.global.u32 %0, [%1];" : "=r"(v) : "l"(ctr) : "memory");
                    const uint32_t base = v & ~0xFFFFu;
                    if (blockIdx.x == 0) asm volatile("red.relaxed.gpu.global.add.u32 [%0], %1;" ::"l"(ctr), "r"(65536 - kVt * kClusters) : "memory");
                    int counted = rank == 0 ? sched.pace_from - 1 : last, allowed = sched.pace_from;
#pragma unroll 1
                    for (n = 0; n < 0x10000 && (allowed <= last || counted < last); n++) {
                        int started;
                        asm volatile("ld.volatile.shared.u32 %0, [%1];" : "=r"(started) : "r"(bars + kStarted) : "memory");
                        started = (started + EV - 1) / EV;
                        if (counted < last && counted < started) {
                            const int upto = min(started, last);
                            asm volatile("red.relaxed.gpu.global.add.u32 [%0], %1;" ::"l"(ctr), "r"(vt[upto] - vt[counted]) : "memory");
                            counted = upto;
                        }
                        if (allowed <= last && started + 1 >= allowed) {
                            asm volatile("ld.relaxed.gpu.global.u32 %0, [%1];" : "=r"(v) : "l"(ctr) : "memory");
                            while (allowed <= last && (int)(v - base) >= sched.need[pat][allowed]) allowed++;
                            asm volatile("st.volatile.shared.u32 [%0], %1;" ::"r"(bars + kAllowed), "r"(allowed > last ? kTiles : allowed) : "memory");
                        }
                        __nanosleep(sched.psleep);
                    }
                    asm volatile("st.volatile.shared.u32 [%0], %1;" ::"r"(bars + kAllowed), "r"(kTiles) : "memory");
                    if (counted < last) asm volatile("red.relaxed.gpu.global.add.u32 [%0], %1;" ::"l"(ctr), "r"(vt[last] - vt[counted]) : "memory");
                }
            }
        } else if (j == 1) {
            if (lead) CURVE_REC(3, 51);
            if (sbase & 1023) __trap();
            if (lead) {
                asm volatile("st.shared.u32 [%0], %1;" ::"r"(bars + kStarted), "r"(0) : "memory");
                asm volatile("st.shared.u32 [%0], %1;" ::"r"(bars + kAllowed), "r"(8) : "memory");
                if (kSlots > 24) {
                    mbar_init(bars + kBarFull + 8 * 24, 1);
                    mbar_init(bars + kBarEmpty + 8 * 24, 6);
                }
                mbar_init(bars + kBarPiece, max(4 * npc, 1));
                mbar_init(bars + kBarReady, 1);
                for (int i = 0; i < 3; i++) mbar_init(bars + kBarEmpty + 8 * (kSlots + i), 1);
                for (int i = 24; i < kSlots + 3; i++) mbar_init(bars + kBarStaged + 8 * i, 4);
                asm volatile("fence.acq_rel.cta;" ::: "memory");
                asm volatile("fence.mbarrier_init.release.cluster;" ::: "memory");
                CURVE_REC(3, 52);
            }
            __syncwarp();
            CLUSTER_ARRIVE();
            CLUSTER_WAIT();
            if (lead) {
                const uint32_t t0 = now_ns();
                uint32_t last[3] = {t0, t0, t0}, peer;
                asm("mapa.shared::cluster.u32 %0, %1, %2;" : "=r"(peer) : "r"(bars + kBarEmpty), "r"(rank ^ 1));
                auto release = [&](uint32_t o) {
                    const uint32_t s8 = o & 0xF8;
                    if (s8 >= 8 * kSlots) mbar_arrive(bars + kBarEmpty + s8);
                    else {
                        asm volatile("mbarrier.arrive.shared::cta.b64 _, [%0], 3;" ::"r"(bars + kBarEmpty + s8) : "memory");
                        mbar_arrive_cluster<3>(peer + s8);
                    }
                };
                uint64_t pol_normal = 0;
                if (STPOL) asm volatile("createpolicy.fractional.L2::evict_normal.b64 %0, 1.0;" : "=l"(pol_normal));
#pragma unroll 1
                for (int t = 0; t < kTiles; t++) {
                    const uint32_t pos = tiles[t].pos, gap = sched.gap[t];
                    if (!(pos & 0x8000)) continue;
                    const int row = fine_group(pos, ci);
                    uint32_t prev = 0;
                    if (tiles[t].pw) {
#pragma unroll 1
                        for (uint32_t n = 0, v = 0; n < 4096 && v < tiles[t].pw; n++) {
                            __nanosleep(20);
                            asm volatile("ld.volatile.shared.u32 %0, [%1];" : "=r"(v) : "r"(bars + kStarted) : "memory");
                        }
                        const uint32_t c = now_ns();
                        const uint32_t stag = sched.stag[t];
                        last[0] = c, last[1] = c + stag, last[2] = c + 2 * stag;
                    }
#pragma unroll
                    for (int g = 0; g < 3; g++) {
                        const uint32_t o = sched.po[t][g] >> 8, s8 = o & 0xF8;
                        mbar_wait1(bars + kBarStaged + s8, o & 1);
                        if (g == 2) CURVE_REC(1, t);
                        if (t < sched.gap_to) {
                            uint32_t c;
                            last[g] += gap;
#pragma unroll 1
                            for (int n = 0; n < 4096; n++) {
                                c = now_ns();
                                if ((int)(c - last[g]) >= 0) break;
                                __nanosleep(20);
                            }
                            if ((int)(c - last[g]) > sched.gslack) last[g] = c - sched.gslack;
                        }
                        asm volatile("fence.proxy.async.shared::cta;" ::: "memory");
                        tma_store_4d(&tm_out, sbase + s8 * 1024, rank * kColR + slice(g) * kColG, row, pol_normal);
                        asm volatile("cp.async.bulk.commit_group;" ::: "memory");
                        if (prev & 4) {
                            asm volatile("cp.async.bulk.wait_group.read 1;" ::: "memory");
                            release(prev);
                        }
                        prev = o;
                    }
                    if (prev & 4) {
                        asm volatile("cp.async.bulk.wait_group.read 0;" ::: "memory");
                        release(prev);
                    }
                    CURVE_REC(3, t);
                }
                asm volatile("cp.async.bulk.wait_group.read 0;" ::: "memory");
            }
        } else {
            if (lead) CURVE_REC(1, 50);
            CLUSTER_ARRIVE();
            uint4 e = *(const uint4*)&tiles[1];
            asm volatile("" : "+r"(e.x), "+r"(e.y), "+r"(e.w));
            CLUSTER_WAIT();
            if (lead) CURVE_REC(1, 51);
            if (lead) {
                uint32_t dst0 = sbase + rank * 4096, bar0 = bars;
                asm volatile("" : "+r"(dst0), "+r"(bar0));
                uint32_t wk = 0, wi = 0;
                int allowed = 0;
                uint64_t pol_first, pol_normal;
                asm volatile("createpolicy.fractional.L2::evict_first.b64 %0, 1.0;" : "=l"(pol_first));
                asm volatile("createpolicy.fractional.L2::evict_normal.b64 %0, 1.0;" : "=l"(pol_normal));
#pragma unroll 1
                for (int t = EARLY ? 1 : 0; t < kTiles; t++) {
                    if (t > 1) e = *(const uint4*)&tiles[t];
                    const bool f = e.w & 0x8000;
                    const CUtensorMap* tm = f ? &tm_fine : ci < kFull ? &tm_coarse : &tm_coarse2;
                    const int c3 = f ? 0 : ci * (kSeg / 8), c4 = f ? fine_group(e.w, ci) + kRankF * rank : (e.w & 0xFFF) + kRankC * rank;
                    for (uint32_t n = 0; t >= allowed; n++) {
                        asm volatile("ld.volatile.shared.u32 %0, [%1];" : "=r"(allowed) : "r"(bar0 + kAllowed) : "memory");
                        if (n == 0x4000000) __trap();
                        if (n) __nanosleep(20);
                    }
                    if (t) CURVE_REC(0, t);
#pragma unroll
                    for (int c = 0; c < 6; c++) {
                        if (c % (6 / EV) == 0) asm volatile("st.volatile.shared.u32 [%0], %1;" ::"r"(bar0 + kStarted), "r"(EV * t + 1 + c / (6 / EV)) : "memory");
                        const uint32_t x = c < 4 ? e.x >> (8 * c) : e.y >> (8 * (c - 4)), s8 = x & 0xF8;
                        mbar_wait1(bar0 + kBarEmpty + s8, (x >> 1) & 1);
                        mbar_expect_tx(bar0 + kBarFull + s8, kChunk);
                        tma_load_5d_mc<LD_EF>(dst0 + s8 * 1024, tm, c * 64, c3, c4, bar0 + kBarFull + s8, x & 4 ? pol_first : pol_normal);
#pragma unroll 1
                        for (uint32_t n = (e.w >> (16 + 2 * c)) & 3; n; n--) {
                            if (wk == 0) mbar_wait(bar0 + kBarReady2, 0);
                            const uint32_t o = sched.worder[wk], y = (&sched.wslot[pat][wi][0][0])[o];
                            mbar_wait1(bar0 + kBarEmpty + (y & 0xF8), (y >> 1) & 1);
                            mbar_expect_tx(bar0 + kBarSwap + 8 * o, kChunk);
                            bulk_load(sbase + (y & 0xF8) * 1024, (const char*)&g_wfrag[0][rank][0][0][0] + (6 * slice(o >> 3) + (o & 7)) * kChunk, bar0 + kBarSwap + 8 * o);
                            if (++wk == 3 * NSTG) wk = 0, wi++;
                        }
                    }
                }
            }
        }
        __syncwarp();
    } else {
        if (elect_one()) {
            for (int i = 2 * warp_id; i < 2 * warp_id + 2; i++) {
                mbar_init(bars + kBarSwap + 8 * i, 1);
                if (i >= kSlots) continue;
                mbar_init(bars + kBarFull + 8 * i, 1);
                mbar_init(bars + kBarEmpty + 8 * i, 6);
                mbar_init(bars + kBarStaged + 8 * i, 4);
            }
            asm volatile("fence.mbarrier_init.release.cluster;" ::: "memory");
        }
        __syncwarp();
        CLUSTER_ARRIVE();
        asm volatile("setmaxnreg.inc.sync.aligned.u32 160;");
        const int tid = threadIdx.x & 127;
        const int warp = tid >> 5;
        const bool rel = tid < 2;
        uint32_t rel_bar;
        asm("mapa.shared::cluster.u32 %0, %1, %2;" : "=r"(rel_bar) : "r"(bars + kBarEmpty), "r"(tid & 1));
        const uint32_t b_lo0 = ((sbase & 0x3FFFF) >> 4) | 0x10000u;
        const uint32_t frag_off = ((lane >> 4) * 8 + (lane & 7)) * 128 + (((2 * warp + ((lane >> 3) & 1)) ^ (lane & 7)) << 4);
        uint32_t st_addr = sbase + frag_off, tid16 = tid * 16;
        asm volatile("" : "+r"(st_addr), "+r"(tid16));
        uint4* const wf = &g_wfrag[0][rank][slice(wg)][pj][tid];
        constexpr int kSet = 2 * 3 * 24 * 128;

        float acc[32];
        uint32_t w[96], p[16];

        auto load_w = [&]() {
        mbar_wait(bars + kBarW + 8 * wg, 0);
        if (tid == 0) CURVE_REC(3, 48 + wg);
        const uint32_t w_addr = sbase + (kSlotW + 6 * wg) * kChunk + frag_off;
#pragma unroll
        for (int s = 0; s < 24; s++) {
            if (WSPLIT && s == 12) mbar_wait(bars + kBarW2 + 8 * wg, 0);
            asm volatile("ldmatrix.sync.aligned.m8n8.x4.trans.shared.b16 {%0,%1,%2,%3}, [%4];"
                         : "=r"(w[4 * s]), "=r"(w[4 * s + 1]), "=r"(w[4 * s + 2]), "=r"(w[4 * s + 3]) : "r"(w_addr + s * 2048) : "memory");
        }
        if (wg < npc) {
            asm volatile("ldmatrix.sync.aligned.m8n8.x4.trans.shared.b16 {%0,%1,%2,%3}, [%4];"
                         : "=r"(p[0]), "=r"(p[1]), "=r"(p[2]), "=r"(p[3]) : "r"(w_addr + pj * 2048) : "memory");
            if (!PUBTMA) wf[0] = make_uint4(p[0], p[1], p[2], p[3]);
        }
        asm volatile("bar.sync %0, 128;" ::"r"(4 + wg) : "memory");
        {
            const uint32_t m = (wg == 2 ? 0x3F : 0xFFF) & ~(PUBTMA && wg && wg < npc ? 3u << 2 * (pub_slot(wg) - kSlotW - 6 * wg) : 0u);
            asm volatile("{\n.reg .pred p;\nsetp.ne.u32 p, %1, 0;\n@p mbarrier.arrive.shared::cluster.b64 _, [%0], 3;\n}\n"
                         ::"r"(rel_bar + 8 * (kSlotW + 6 * wg + (tid >> 1))), "r"(tid < 12 ? m >> tid & 1 : 0) : "memory");
        }
        if (threadIdx.x == 0) CURVE_REC(2, 59);
        if (wg < npc) {
            mbar_wait(bars + kBarL, 0);
            if (threadIdx.x == 0) CURVE_REC(3, 61);
            WG_FENCE();
            piece_steps<0>(acc, w, b_lo0 + kSlotL * 512);
            WG_COMMIT();
            WG_WAIT(0);
#pragma unroll
            for (int i = 0; i < 8; i++) {
                asm volatile("" : "+f"(acc[i]), "+f"(acc[8 + i]), "+f"(acc[16 + i]), "+f"(acc[24 + i]));
                if (CHAINS == 2) acc[i] += acc[8 + i];
                if (CHAINS == 4) acc[i] = (acc[i] + acc[8 + i]) + (acc[16 + i] + acc[24 + i]);
            }
            const uint32_t a = sbase + pub_slot(wg) * kChunk + 4096 + tid16;
            asm volatile("st.shared.v4.u32 [%0], {%1,%2,%3,%4};" ::"r"(a), "r"(p[0]), "r"(p[1]), "r"(p[2]), "r"(p[3]) : "memory");
            asm volatile("st.shared.v4.u32 [%0], {%1,%2,%3,%4};" ::"r"(a + 2048), "r"(pack_bf16(acc[0], acc[1])), "r"(pack_bf16(acc[2], acc[3])),
                         "r"(pack_bf16(acc[4], acc[5])), "r"(pack_bf16(acc[6], acc[7])) : "memory");
            __syncwarp();
            if (threadIdx.x == 0) CURVE_REC(3, 62);
            if (lane == 0) mbar_arrive(bars + kBarPiece);
        }
        if (tid < (PUBTMA && wg == 0 && npc ? 2 : 4)) mbar_arrive_cluster<1>(rel_bar + 8 * (kSlotL + (tid >> 1)));
        if (threadIdx.x == 256) CURVE_REC(2, 60);
        };
        if (tid == 0) CURVE_REC(3, 46);
        CLUSTER_WAIT();
        if (tid == 0) CURVE_REC(3, 47);
#pragma unroll
        for (int i = 0; i < 16; i++) p[i] = 0;

        const int tok_in = 1 + wg, tok_out = wg == 2 ? 1 : wg + 2;
#pragma unroll 1
        for (int t = 0; t < kTiles; t++) {
            const uint2 e = *(const uint2*)&tiles[t];
            const uint32_t fl = e.y >> 24, pe = sched.po[t][wg];
            const uint32_t p_addr = sbase + (pe & 0xF8) * 1024 + tid16;
            if ((~fl & (F_FINE | F_P)) == 0) {
#pragma unroll
                for (int q = 0; q < 4; q++)
                    asm volatile("ld.shared.v4.u32 {%0,%1,%2,%3}, [%4];" : "=r"(p[4 * q]), "=r"(p[4 * q + 1]), "=r"(p[4 * q + 2]), "=r"(p[4 * q + 3])
                                 : "r"(p_addr + q * 2048) : "memory");
            }
            const char* swap = (const char*)&g_wfrag[1][rank][slice(wg)][0][0];
            auto init = [&](auto quarter) {
                constexpr int Q = decltype(quarter)::value;
#pragma unroll
                for (int i = 0; i < 8; i++)
                    asm volatile("shl.b32 %0, %4, 16;\nshl.b32 %1, %4, 16;\nand.b32 %2, %4, 0xffff0000;\nand.b32 %3, %4, 0xffff0000;"
                                 : "=f"(acc[4 * i]), "=f"(acc[4 * i + 1]), "=f"(acc[4 * i + 2]), "=f"(acc[4 * i + 3]) : "r"(p[4 * Q + (i & 3)]));
            };
            if (fl & F_FINE) {
                if (fl & F_Q2) {
                    if (fl & F_Q1) init(std::integral_constant<int, 3>());
                    else init(std::integral_constant<int, 2>());
                } else {
                    if (fl & F_Q1) init(std::integral_constant<int, 1>());
                    else {
                        if (DEFER >= 3) reload_w<3>(w, swap, tid16, ~fl & F_P);
                        if (DEFER >= 2) reload_w<4>(w, swap, tid16, ~fl & F_P);
                        if (DEFER >= 1) reload_w<5>(w, swap, tid16, ~fl & F_P);
                        init(std::integral_constant<int, 0>());
                    }
                }
            }
            if (fl & F_READY) {
                if (INLOOP && t == 0) load_w();
                else mbar_wait(bars + kBarReady, 0);
            }
            mbar_wait(bars + kBarFull + (e.x & 0xF8), e.x & 1);
            asm volatile("{\n.reg .pred p;\nsetp.eq.u32 p, %1, 0;\n@p bar.sync %0, 256;\n}\n" ::"r"(tok_in), "r"(pe & 1) : "memory");
            auto body = [&](auto mode) {
                constexpr int M = decltype(mode)::value;
                if (M == 1 && DEFER) asm volatile("{\n.reg .pred p;\nsetp.ne.u32 p, %0, 0;\n@p trap;\n}\n" ::"r"(w[95] & e.y & 0x40000));
                bool rdy = issue_chunk<0>(acc, w, e, bars, b_lo0, true);
                CREC0(0);
                rdy = issue_chunk<1>(acc, w, e, bars, b_lo0, rdy);
                CREC0(1);
                if (TOKEN_K == 2) asm volatile("{\n.reg .pred p;\nsetp.eq.u32 p, %1, 0;\n@p bar.arrive %0, 256;\n}\n" ::"r"(tok_out), "r"(pe & 4) : "memory");
                retire_chunk<0, 1, M>(w, e, sched.wslot[pat], wg, sbase, rel_bar, rel, swap, tid16);
                if (M == 0 && rel && (~fl & (F_FINE | F_P)) == 0) mbar_arrive_cluster<3>(rel_bar + (pe & 0xF8));
                rdy = issue_chunk<2>(acc, w, e, bars, b_lo0, rdy);
                CREC0(2);
                if (TOKEN_K == 3) asm volatile("{\n.reg .pred p;\nsetp.eq.u32 p, %1, 0;\n@p bar.arrive %0, 256;\n}\n" ::"r"(tok_out), "r"(pe & 4) : "memory");
                retire_chunk<1, 1, M>(w, e, sched.wslot[pat], wg, sbase, rel_bar, rel, swap, tid16);
                rdy = issue_chunk<3>(acc, w, e, bars, b_lo0, rdy);
                CREC0(3);
                retire_chunk<2, 1, M>(w, e, sched.wslot[pat], wg, sbase, rel_bar, rel, swap, tid16);
                rdy = issue_chunk<4>(acc, w, e, bars, b_lo0, rdy);
                CREC0(4);
                retire_chunk<3, 1, M>(w, e, sched.wslot[pat], wg, sbase, rel_bar, rel, swap, tid16);
                rdy = issue_chunk<5>(acc, w, e, bars, b_lo0, rdy);
                CREC0(5);
                retire_chunk<4, 1, M>(w, e, sched.wslot[pat], wg, sbase, rel_bar, rel, swap, tid16);
                if (M != 1) mbar_wait(bars + kBarEmpty + (pe >> 11) * 8, (pe >> 9) & 1);
                retire_chunk<5, 0, M>(w, e, sched.wslot[pat], wg, sbase, rel_bar, rel, swap, tid16);
            };
            if (!(fl & F_SWAP)) body(std::integral_constant<int, 0>());
            else if (fl & F_STAGED) body(std::integral_constant<int, 2>());
            else body(std::integral_constant<int, 1>());
            if (fl & F_FINE) {
#pragma unroll
                for (int q = 0; q < 4; q++)
                    asm volatile("stmatrix.sync.aligned.m8n8.x4.trans.shared.b16 [%0], {%1,%2,%3,%4};" ::"r"(st_addr + (pe >> 11) * kChunk + q * 2048),
                                 "r"(pack_bf16(acc[8 * q], acc[8 * q + 1])), "r"(pack_bf16(acc[8 * q + 2], acc[8 * q + 3])),
                                 "r"(pack_bf16(acc[8 * q + 4], acc[8 * q + 5])), "r"(pack_bf16(acc[8 * q + 6], acc[8 * q + 7])) : "memory");
                __syncwarp();
                asm volatile("{\n.reg .pred p;\nelect.sync _|p, 0xffffffff;\n@p mbarrier.arrive.shared::cta.b64 _, [%0];\n}\n" ::"r"(bars + kBarStaged + (pe >> 11) * 8) : "memory");
            } else {
#pragma unroll
                for (int q = 0; q < 4; q++) {
                    p[4 * q] = pack_bf16(acc[8 * q], acc[8 * q + 2]);
                    p[4 * q + 1] = pack_bf16(acc[8 * q + 1], acc[8 * q + 3]);
                    p[4 * q + 2] = pack_bf16(acc[8 * q + 4], acc[8 * q + 6]);
                    p[4 * q + 3] = pack_bf16(acc[8 * q + 5], acc[8 * q + 7]);
                    if (fl & F_P)
                        asm volatile("st.shared.v4.u32 [%0], {%1,%2,%3,%4};" ::"r"(p_addr + q * 2048),
                                     "r"(p[4 * q]), "r"(p[4 * q + 1]), "r"(p[4 * q + 2]), "r"(p[4 * q + 3]) : "memory");
                }
            }
        }
        if (warp_id == 11 && (sched.fin[0] >> lane & 1)) mbar_wait(bars + kBarEmpty + 8 * lane, sched.fin[1] >> lane & 1);
        __syncwarp();
    }
    CLUSTER_ARRIVE();
    CLUSTER_WAIT();
    if (threadIdx.x == 0) CURVE_REC(0, 63);
}

int digit(char ch) { return ch >= 'a' ? ch - 'a' + 10 : ch >= 'A' ? ch - 'A' + 36 : ch - '0'; }
void build_schedule(int pat, Tile* tl, uint16_t (*po)[4], uint32_t* fin, uint8_t (*wslot)[3][8], uint8_t* worder, const int* gs) {
    const char* park = envs("OUT", "000000000000000000000000000000000446708zzz55");
    uint8_t out[kTiles][3] = {};
    int parked[kSlots] = {}, nth[kTiles][3];
    const int take[3] = {TAKE}, give[3] = {GIVE};
    const int staged = envi("STAGED", 1), wadv = envi("WADV", 0), wrel = envi("WREL", 1), wslack = envi("WSLACK", 0), wmax = envi("WMAX", 3);
    const char* depth = envs("DEPTH", "zzzzzzzzzzzzzhzzzzzhhdzzzzddzgggggcbehhhhhe9");
    int coarse_of[16];
    int n = 0, nsw = 0, swt[2] = {};
    int units[kTiles];
    auto unit = [&](int t) { return units[t]; };
    for (int g = 0, i0 = 0; gs[g]; i0 += gs[g], g++) {
        for (int i = 1; i <= gs[g]; i++, n++) {
            units[n] = i0 + i % gs[g];
            tl[n].pos = (units[n] * NPAT + pat) * (SHAPE ? 4 : 2);
            tl[n].flags = i < gs[g] ? F_P : F_SWAP | (g == 0 ? F_READY : 0);
            coarse_of[unit(n)] = n;
        }
        for (int i = 0; i < 4 * gs[g] && n < kTiles; i++, n++) {
            units[n] = i0 + i / 4;
            tl[n].pos = 0x8000 + (SHAPE ? ((units[n] * NPAT + pat) * 4 + (i & 3)) * kGroup : ((units[n] * NPAT + pat) * 2 + (i & 3) / 2) * kGroup + (i & 1) * 0x1000);
            tl[n].flags = F_FINE | (i >= 4 && (i & 3) == 0 ? F_P : 0) | (i & 1 ? F_Q1 : 0) | (i & 2 ? F_Q2 : 0);
            if (i == 4 * gs[g] - 1 && gs[g + 1]) {
                tl[n].flags |= staged ? F_SWAP | F_STAGED | (nsw ? F_SW1 : 0) : F_SWAP;
                if (staged) swt[nsw++] = n;
            }
        }
    }
    int nwo = 0;
    for (int need = -4; need < 6; need++)
        for (int g = 0; g < 3; g++) {
            const int c = need - give[g];
            if (c < 6 - NSTG || c > 5) continue;
            worder[nwo++] = g * 8 + c;
            for (int i = 0; i < nsw && !wslack; i++) {
                const int j = 6 * swt[i] + need + 4 - wadv;
                tl[j / 6].wcnt += 1 << (2 * (j % 6));
            }
        }
    int uses[kSlots], loads[kSlots], queue[512], head = 0, tail = 0, slot_of[6 * kTiles];
    for (int s = 0; s < kSlots; s++) uses[s] = s >= kSlotL, loads[s] = 0;
    auto take_p = [&](int t, int w, int s) { tl[t].p[w] = s * 8 + ((uses[s] + 1) & 1) * 2; uses[s]++; };
    bool taken[kSlots] = {};
    for (int w = 0; w < 3; w++)
        if (take[w] < 0 && (tl[0].flags & F_P)) take_p(0, w, kSlotW + 6 * w + 2), taken[kSlotW + 6 * w + 2] = true;
    for (int s = 0; s < kSlotL; s++) queue[tail++] = s;
    for (int s = kSlotW; s < kSlots; s++) if (!taken[s]) queue[tail++] = s;
    for (int s = kSlotL; s < kSlotW; s++) queue[tail++] = s;
    int r = 0, wk = 0, wi = 0;
    int rel[512];
    for (int i = 0; i < tail; i++) rel[i] = -1;
    auto get_slot = [&](int from) {
        for (; r < 6 * kTiles; r++) {
            for (int i = head; i < tail; i++)
                if (rel[i] >= from) {
                    const int s = queue[i];
                    for (; i > head; i--) queue[i] = queue[i - 1], rel[i] = rel[i - 1];
                    head++;
                    return s;
                }
            for (int i = tail; i < tail + 16; i++) rel[i] = r;
            bool to_p = false;
            for (int w = 0; w < 3; w++) {
                int x = r - take[w];
                if (x >= 0 && x % 6 == 0 && x / 6 < kTiles && (tl[x / 6].flags & (F_FINE | F_P)) == F_P) take_p(x / 6, w, slot_of[r]), to_p = true;
                if (x >= 0 && x % 6 == 0 && x / 6 < kTiles && (tl[x / 6].flags & F_FINE) && park[x / 6] != '0') {
                    if (head == tail) to_p = true;
                    const int s = to_p ? slot_of[r] : queue[head++];
                    out[x / 6][w] = s * 8 + ((uses[s] + 1) & 1) * 2 + (parked[s] & 1);
                    nth[x / 6][w] = ++uses[s], parked[s]++;
                }
                for (int t = 0; t < kTiles; t++)
                    if ((tl[t].flags & F_FINE) && park[t] != '0' && r == 6 * t + 4 + give[w] + 2 * digit(park[t])) queue[tail++] = out[t][w] >> 3;
            }
            if (!to_p) queue[tail++] = slot_of[r];
            for (int w = 0; w < 3; w++) {
                int x = r - give[w];
                if (x >= 0 && x % 6 == 0 && x / 6 < kTiles && (tl[x / 6].flags & (F_FINE | F_P)) == (F_FINE | F_P)) {
                    tl[x / 6].p[w] = tl[coarse_of[unit(x / 6)]].p[w];
                    queue[tail++] = tl[x / 6].p[w] >> 3;
                }
                x -= wrel;
                if (x >= 0 && x / 6 < kTiles && (tl[x / 6].flags & F_STAGED) && x % 6 >= 6 - NSTG) queue[tail++] = wslot[tl[x / 6].flags >> 7][w][x % 6] >> 3;
            }
        }
        return 0;
    };
    for (int c = 0; c < 6 * kTiles; c++) {
        const char dp = depth[c / 6];
        int s = get_slot(dp == 'z' ? -1 : c - 4 - (dp > '9' ? dp - 'a' + 10 : dp - '0'));
        slot_of[c] = s;
        tl[c / 6].chunk[c % 6] = s * 8 + ((uses[s] + 1) & 1) * 2 + (loads[s] & 1);
        if (c % 6 == 0 && c) tl[c / 6 - 1].chunk[6] = tl[c / 6].chunk[0];
        uses[s]++, loads[s]++;
        for (int k = wslack ? wmax : (tl[c / 6].wcnt >> (2 * (c % 6))) & 3; k; k--) {
            if (wslack) {
                if (wi == nsw || 6 * swt[wi] + (worder[wk] & 7) + give[worder[wk] >> 3] - r > wslack) break;
                tl[c / 6].wcnt += 1 << (2 * (c % 6));
            }
            s = get_slot(-1);
            (&wslot[wi][0][0])[worder[wk]] = s * 8 + ((uses[s] + 1) & 1) * 2;
            uses[s]++;
            if (++wk == 3 * NSTG) wk = 0, wi++;
        }
    }
    get_slot(6 * kTiles);
    fin[0] = (1u << kSlots) - 1, fin[1] = 0;
    for (int s = 0; s < kSlots; s++) fin[1] |= ((uses[s] + 1) & 1) << s;
    for (int t = 0, k = 1; t < kTiles; t++)
        if (!(tl[t].flags & F_FINE)) memcpy(out[t], tl[t].p, 3);
        else if (park[t] == '0') {
            for (int w = 0; w < 3; w++) out[t][w] = (kSlots + w) * 8 + (strchr(park + t + 1, '0') ? 4 : 0) + (k & 1) * 2 + (~k & 1);
            k++;
        } else
            for (int w = 0; w < 3; w++) {
                if (uses[out[t][w] >> 3] > nth[t][w]) out[t][w] |= 4;
                else fin[0] &= ~(1u << (out[t][w] >> 3));
            }
    if (INLOOP) tl[0].flags |= F_READY;
    const char* free_run = envs("NOTOK", "710000000000000000000000000000000000000000071");
    for (int t = 0; t <= kTiles; t++)
        for (int w = 0; w < 3; w++)
            if ((free_run[t] - '0') >> w & 1) {
                tl[t].p[w] |= 1;
                if (w) tl[t].p[w - 1] |= 4;
                else if (t) tl[t - 1].p[2] |= 4;
            }
    for (int t = 0; t < kTiles; t++)
        for (int w = 0; w < 3; w++) po[t][w] = tl[t].p[w] + 256 * out[t][w];
}

typedef CUresult (*EncodeFn)(CUtensorMap*, CUtensorMapDataType, cuuint32_t, void*, const cuuint64_t*, const cuuint64_t*,
                             const cuuint32_t*, const cuuint32_t*, CUtensorMapInterleave, CUtensorMapSwizzle,
                             CUtensorMapL2promotion, CUtensorMapFloatOOBfill);

void encode_2d(EncodeFn enc, CUtensorMap* tm, const void* ptr, uint64_t rows, uint32_t box_rows, CUtensorMapL2promotion promo) {
    cuuint64_t dims[2] = {(cuuint64_t)kC, rows};
    cuuint64_t strides[1] = {(cuuint64_t)kC * 2};
    cuuint32_t box[2] = {64, box_rows};
    cuuint32_t es[2] = {1, 1};
    enc(tm, CU_TENSOR_MAP_DATA_TYPE_BFLOAT16, 2, const_cast<void*>(ptr), dims, strides, box, es, CU_TENSOR_MAP_INTERLEAVE_NONE,
        CU_TENSOR_MAP_SWIZZLE_128B, promo, CU_TENSOR_MAP_FLOAT_OOB_FILL_NONE);
}

}

extern "C" void kernel_launch(void* const* d_in, const int* in_sizes, int n_in, void* d_out, int out_size) {
    (void)in_sizes; (void)n_in; (void)out_size;
    static EncodeFn enc = nullptr;
    static Schedule sched;
    static Scratch* scr;
    if (!enc) {
        cudaGetSymbolAddress((void**)&scr, g_scratch);
        void* fn = nullptr;
        cudaDriverEntryPointQueryResult qr;
        cudaGetDriverEntryPoint("cuTensorMapEncodeTiled", &fn, cudaEnableDefault, &qr);
        enc = (EncodeFn)fn;
        cudaFuncSetAttribute(fpn_lateral_kernel, cudaFuncAttributeMaxDynamicSharedMemorySize, kSmemBytes);
        if (envi("CARVE", 0)) cudaFuncSetAttribute(fpn_lateral_kernel, cudaFuncAttributePreferredSharedMemoryCarveout, envi("CARVE", 0));
        cudaLaunchConfig_t cfg = {};
        cfg.gridDim = dim3(2);
        cfg.blockDim = dim3(512);
        cfg.dynamicSmemBytes = kSmemBytes;
        cudaLaunchAttribute at;
        at.id = cudaLaunchAttributeClusterDimension;
        at.val.clusterDim.x = 2; at.val.clusterDim.y = 1; at.val.clusterDim.z = 1;
        cfg.attrs = &at; cfg.numAttrs = 1;
        int ncl = 0;
        if (cudaOccupancyMaxActiveClusters(&ncl, fpn_lateral_kernel, &cfg) != cudaSuccess) { (void)cudaGetLastError(); ncl = 0; }
        const char* pn[4] = {"PATA", "PATB", "PATC", "PATD"};
        const char* pd[4] = {"45", "45", "36", "63"};
        sched.pgroup = envi("PGROUP", 0), sched.members = sched.pgroup ? kGroup : kClusters;
        for (int q = 0; q < NPAT; q++) {
            int gs[8] = {};
            const char* sa = envs(pn[q], pd[q]);
            for (int i = 0; sa[i]; i++) gs[i] = sa[i] - '0';
            build_schedule(q, sched.tile[q], sched.po, sched.fin, sched.wslot[q], sched.worder, gs);
        }
        {
            const char* gaps = envs("GAPS", "00000lmjonnlnomm0011occkkk0r4009981401000000");
            const char* lef = envs("LEF", "60000000000000000000000000000000025666666666");
            const uint8_t masks[7] = {0, 1, 9, 0x15, 0x1B, 0x1F, 0x3F};
            for (int t = 0; t < kTiles; t++) {
                const int tr = digit(envs("TRIG", "0000000000000000007d0000000050a009a8dg000000")[t]);
                sched.tile[0][t].pw = tr ? min(EV * t + tr, EV * kTiles) : 0;
                sched.stag[t] = digit(envs("STG", "55555555555555555500555555556648345975555555")[t]) * 100;
                const int d = digit(gaps[t]);
                sched.gap[t] = (d > 36 ? 3 * d - 72 : d) * envi("GUNIT", 75);
                if (gaps[t] != '0' || envi("GALL", 0)) sched.gap_to = t + 1;
                for (int c = 0; c < 6; c++) sched.tile[0][t].chunk[c] |= (masks[lef[t] - '0'] >> c & 1) * 4;
            }
            sched.gslack = envi("GSLACK", 0);
            const char* lead = envs("LEAD3", "00044000013267hhfnnbakglfnmpnnoommgkifjdcefefbb7ca888888368cbba78aa8799994cb8cddaa9b99579ba88c47447986756687667977666666666157chgf77");
            sched.pf_from = envi("PFFROM", 24);
            int pos = sched.pf_from + envi("PF0", 0);
            sched.tgt[0] = pos;
            for (int e = 0; e < EV * kTiles; e++) {
                const int x = (e + 1) * (6 / EV) + digit(lead[e]);
                if (pos < x) pos = x;
                if (pos > 6 * kTiles) pos = 6 * kTiles;
                sched.tgt[e + 1] = pos;
            }
            sched.pw_ev[0] = envi("PW0", 0) * EV / 6 + 1, sched.pw_ev[1] = envi("PW1", 144) * EV / 6 + 1, sched.pw_div = envi("PWDIV", 4);
            sched.t_a = envi("TA", 0), sched.t_d = envi("TD", 290), sched.t_max = envi("TMAX", 0), sched.fsleep = envi("FSLEEP", 40);
        }
        sched.gate1 = envi("GATE1", 1), sched.psleep = envi("PSLEEP", 20);
        sched.pace_from = envi("PACE_FROM", 18), sched.pace_to = envi("PACE_TO", 44);
        const char* v5 = envs("VTA", "55555555555577799664465555532213166878668669");
        const char* vts[4] = {v5, envs("VTB", v5), envs("VTC", v5), envs("VTD", v5)};
        int total = 0;
        for (int q = 0; q < NPAT; q++) {
            int sum[kTiles + 1] = {};
            for (int t = sched.pace_from; t < sched.pace_to; t++) sum[t] = sum[t - 1] + vts[q][t] - '0';
            total = sum[sched.pace_to - 1];
            for (int t = sched.pace_from; t < sched.pace_to; t++) {
                sched.vt[q][t] = sum[t] * kVt / total;
                const int slack = digit(envs("SLK", "000000000jlonpzzmihskfe7eg95fhda56ag6dehhd7x")[t]) * 8;
                sched.need[q][t] = ncl >= kClusters ? 65536 - kVt * kClusters + sched.vt[q][t] * sched.members - slack * 5 * kVt / total * sched.members / 64 : -1;
            }
        }
    }
    CUtensorMap tm_fine, tm_coarse, tm_coarse2, tm_wlat, tm_wout, tm_out;
    const cuuint32_t ones[5] = {1, 1, 1, 1, 1};
    {
        cuuint64_t dims[5] = {(cuuint64_t)kC, 2, 4, 4, (cuuint64_t)kFinePix / 32};
        cuuint64_t strides[4] = {768, 2 * 768, 8 * 768, 32 * 768};
        cuuint32_t box[5] = {64, 2, 4, 4, 1};
        enc(&tm_fine, CU_TENSOR_MAP_DATA_TYPE_BFLOAT16, 5, d_in[0], dims, strides, box, ones, CU_TENSOR_MAP_INTERLEAVE_NONE,
            CU_TENSOR_MAP_SWIZZLE_128B, CU_TENSOR_MAP_L2_PROMOTION_L2_128B, CU_TENSOR_MAP_FLOAT_OOB_FILL_NONE);
    }
    {
        cuuint64_t dims[3] = {64, (cuuint64_t)kC, 6};
        cuuint64_t strides[2] = {768, 128};
        cuuint32_t box[3] = {64, 16, 6};
        cuuint32_t es[3] = {1, 1, 1};
        enc(&tm_wlat, CU_TENSOR_MAP_DATA_TYPE_BFLOAT16, 3, d_in[2], dims, strides, box, es, CU_TENSOR_MAP_INTERLEAVE_NONE,
            CU_TENSOR_MAP_SWIZZLE_128B, CU_TENSOR_MAP_L2_PROMOTION_L2_256B, CU_TENSOR_MAP_FLOAT_OOB_FILL_NONE);
    }
    encode_2d(enc, &tm_wout, d_in[3], kC, 192, CU_TENSOR_MAP_L2_PROMOTION_L2_256B);
    {
        cuuint64_t dims[4] = {(cuuint64_t)kC, 32, 2, (cuuint64_t)kFinePix / 32 - kRankF};
        cuuint64_t strides[3] = {768, kRankF * 32 * 768, 32 * 768};
        cuuint32_t box[4] = {64, 32, 2, 1};
        enc(&tm_out, CU_TENSOR_MAP_DATA_TYPE_BFLOAT16, 4, d_out, dims, strides, box, ones, CU_TENSOR_MAP_INTERLEAVE_NONE,
            CU_TENSOR_MAP_SWIZZLE_128B, CU_TENSOR_MAP_L2_PROMOTION_NONE, CU_TENSOR_MAP_FLOAT_OOB_FILL_NONE);
    }
    {
        cuuint64_t dims[5] = {(cuuint64_t)kC, 2, 4, kGroup * kSeg / 8, 35};
        cuuint64_t strides[4] = {4 * 768, 768, 8 * 768, kGroup * kSeg * 768};
        cuuint32_t box[5] = {64, 2, 4, kSeg / 8, 32 / kSeg};
        enc(&tm_coarse, CU_TENSOR_MAP_DATA_TYPE_BFLOAT16, 5, d_in[1], dims, strides, box, ones, CU_TENSOR_MAP_INTERLEAVE_NONE,
            CU_TENSOR_MAP_SWIZZLE_128B, CU_TENSOR_MAP_L2_PROMOTION_L2_128B, CU_TENSOR_MAP_FLOAT_OOB_FILL_NONE);
        dims[4] = 34;
        enc(&tm_coarse2, CU_TENSOR_MAP_DATA_TYPE_BFLOAT16, 5, d_in[1], dims, strides, box, ones, CU_TENSOR_MAP_INTERLEAVE_NONE,
            CU_TENSOR_MAP_SWIZZLE_128B, CU_TENSOR_MAP_L2_PROMOTION_L2_128B, CU_TENSOR_MAP_FLOAT_OOB_FILL_NONE);
    }
    fpn_lateral_kernel<<<2 * kClusters, 512, kSmemBytes>>>(scr, (const char*)d_in[0], (const char*)d_in[1], (const char*)d_in[2], (const char*)d_in[3],
                                                          tm_fine, tm_coarse, tm_coarse2, tm_wlat, tm_wout, tm_out, sched);
}
```

```cpp
#include <cuda_runtime.h>
#include <cuda_bf16.h>
#include <cuda.h>
#include <stdint.h>
#include <string.h>
#include <type_traits>
#include <stdlib.h>

#define TOKEN_K 3
#define TAKE -2, 0, 2
#define GIVE -4, -2, 0
#define L_POS 0
#define NSTG 6
#define EV 3
#define STPOL 0
#define NO_MMA 0
#define EARLY 1
#define EARLY_T 0
#define W_PRE 0
#define TOPPF 1
#define TLBW 1
#define W_MIX 0x1E
#define WR 1
#define CHAINS 1
#define ROT 0
#define PUBTMA 1
#define DEFER 2
#define INLOOP 1
#define WSPLIT 1
#define TPF_N 0
#define TPF_A 400
#define TPF_D 300
#define FIN 2
#define ENDBAR 1
#define NPAT 1
#define SHAPE 1
#define OBUF 1
#define LD_EF 1
#define CURVE_REC(k, i) do {} while (0)

#define CREC0(c) do {} while (0)
namespace {

constexpr int kC = 384;
constexpr int kFinePix = 384 * 384;
constexpr int kCoarsePix = 192 * 192;
constexpr int kClusters = 66;
constexpr int kTiles = 44;
constexpr int kFull = 2304 - 34 * kClusters;
constexpr int kVt = 65536 / kClusters;
#define SLOTS (28 - 3 * OBUF)
constexpr int kSlots = SLOTS;
#define GT 1
#define ILV 0
constexpr int kColR = ILV ? 64 : 192, kColG = ILV ? 128 : 64;
constexpr int kChunk = 8192;
constexpr int kTileBytes = 6 * kChunk;
constexpr int kOffOut = kSlots * kChunk;
constexpr int kOffBar = kOffOut + 3 * OBUF * kChunk;
constexpr int kSmemBytes = kOffBar + 1024;
constexpr int kSlotL = kSlots + 3 * OBUF - 20;
constexpr int kSlotW = kSlots + 3 * OBUF - 18;
constexpr int kBarFull = 0, kBarEmpty = 8 * kSlots, kBarStaged = kBarEmpty + 8 * (kSlots + 3), kBarW = kBarStaged + 8 * (kSlots + 3), kBarL = kBarW + 24;
constexpr int kBarPiece = kBarL + 8, kBarReady = kBarPiece + 8;
constexpr int kBarSwap = kBarReady + 8;
constexpr int kBarReady2 = kBarSwap + 56;
constexpr int kStarted = kBarSwap + 192, kAllowed = kStarted + 4;
constexpr int kBarW2 = WSPLIT ? kStarted + 8 : kBarW;
constexpr int kPos0 = 4;
constexpr int kPieces = 24;

enum : uint32_t { F_FINE = 1, F_P = 2, F_Q1 = 4, F_SWAP = 8, F_READY = 16, F_Q2 = 32, F_STAGED = 64, F_SW1 = 128 };
struct alignas(16) Tile {
    uint8_t chunk[7];
    uint8_t flags;
    uint8_t p[3];
    uint8_t pw;
    uint16_t pos;
    uint16_t wcnt;
};
constexpr int kGroup = kClusters / NPAT;
struct Schedule {
    Tile tile[NPAT][kTiles + 1];
    uint16_t tgt[EV * kTiles + 2];
    alignas(8) uint8_t wslot[NPAT][2][3][8];
    uint8_t worder[24];
    uint16_t po[kTiles][4];
    uint32_t fin[2];
    uint16_t stag[48];
    uint16_t gap[48];
    int members, pgroup, gslack, gap_to;
    int pace_from, pace_to, gate1, psleep, pf_from, pw_ev[2], pw_div, t_a, t_d, t_max, fsleep;
    int need[NPAT][kTiles + 1];
    uint16_t vt[NPAT][kTiles + 1];
};
static int envi(const char*, int d) { return d; }
static const char* envs(const char*, const char* d) { return d; }

struct Scratch {
    uint4 wfrag[2][2][3][24][128];
    uint32_t ready, pad0[31];
    uint32_t done, pad1[31];
    uint32_t progress[4][32];
};
__device__ Scratch g_scratch;
#define g_wfrag scr->wfrag
#define g_ready scr->ready
#define g_done scr->done
#define g_progress scr->progress

__device__ __forceinline__ uint32_t smem_u32(const void* p) { return (uint32_t)__cvta_generic_to_shared(p); }

__device__ __forceinline__ void mbar_init(uint32_t bar, uint32_t count) {
    asm volatile("mbarrier.init.shared::cta.b64 [%0], %1;" ::"r"(bar), "r"(count) : "memory");
}
__device__ __forceinline__ void mbar_expect_tx(uint32_t bar, uint32_t bytes) {
    asm volatile("mbarrier.arrive.expect_tx.shared::cta.b64 _, [%0], %1;" ::"r"(bar), "r"(bytes) : "memory");
}
__device__ __forceinline__ void mbar_wait(uint32_t bar, uint32_t parity) {
    asm volatile(
        "{\n"
        ".reg .pred p;\n"
        ".reg .u32 n;\n"
        "mov.u32 n, 0;\n"
        "WAIT_LOOP:\n"
        "mbarrier.try_wait.parity.shared::cta.b64 p, [%0], %1;\n"
        "@p bra WAIT_DONE;\n"
        "add.u32 n, n, 1;\n"
        "setp.lt.u32 p, n, 0x400000;\n"
        "@p bra WAIT_LOOP;\n"
        "trap;\n"
        "WAIT_DONE:\n"
        "}\n" ::"r"(bar), "r"(parity) : "memory");
}
__device__ __forceinline__ void mbar_wait1(uint32_t bar, uint32_t parity) {
    uint32_t r;
    asm volatile("{\n.reg .pred p;\nmbarrier.try_wait.parity.shared::cta.b64 p, [%1], %2;\nselp.u32 %0, 1, 0, p;\n}\n" : "=r"(r) : "r"(bar), "r"(parity) : "memory");
    if (!r) mbar_wait(bar, parity);
}
__device__ __forceinline__ bool mbar_test(uint32_t bar, uint32_t parity) {
    uint32_t r;
    asm volatile("{\n.reg .pred p;\nmbarrier.test_wait.parity.shared::cta.b64 p, [%1], %2;\nselp.u32 %0, 1, 0, p;\n}\n" : "=r"(r) : "r"(bar), "r"(parity) : "memory");
    return r != 0;
}
__device__ __forceinline__ void mbar_arrive(uint32_t bar) {
    asm volatile("mbarrier.arrive.shared::cta.b64 _, [%0];" ::"r"(bar) : "memory");
}
template <int N>
__device__ __forceinline__ void mbar_arrive_cluster(uint32_t bar) {
    if (N == 1) asm volatile("mbarrier.arrive.shared::cluster.b64 _, [%0];" ::"r"(bar) : "memory");
    else asm volatile("mbarrier.arrive.shared::cluster.b64 _, [%0], %1;" ::"r"(bar), "n"(N) : "memory");
}
__device__ __forceinline__ void bulk_load(uint32_t dst, const void* src, uint32_t bar) {
    asm volatile("cp.async.bulk.shared::cluster.global.mbarrier::complete_tx::bytes [%0], [%1], %2, [%3];"
                 ::"r"(dst), "l"(src), "n"(kChunk), "r"(bar) : "memory");
}
__device__ __forceinline__ void tma_load_2d(uint32_t dst, const CUtensorMap* tm, int c0, int c1, uint32_t bar) {
    asm volatile("cp.async.bulk.tensor.2d.shared::cluster.global.mbarrier::complete_tx::bytes [%0], [%1, {%2, %3}], [%4];"
                 ::"r"(dst), "l"(tm), "r"(c0), "r"(c1), "r"(bar) : "memory");
}
__device__ __forceinline__ void tma_load_3d(uint32_t dst, const CUtensorMap* tm, int c1, uint32_t bar) {
    asm volatile("cp.async.bulk.tensor.3d.shared::cluster.global.mbarrier::complete_tx::bytes [%0], [%1, {%2, %3, %2}], [%4];"
                 ::"r"(dst), "l"(tm), "r"(0), "r"(c1), "r"(bar) : "memory");
}
template <bool HINT>
__device__ __forceinline__ void tma_load_5d_mc(uint32_t dst, const CUtensorMap* tm, int c0, int c3, int c4, uint32_t bar, uint64_t pol) {
    if (HINT) asm volatile("cp.async.bulk.tensor.5d.shared::cluster.global.mbarrier::complete_tx::bytes.multicast::cluster.L2::cache_hint [%0], [%1, {%2, %3, %3, %4, %5}], [%6], %7, %8;"
                 ::"r"(dst), "l"(tm), "r"(c0), "r"(0), "r"(c3), "r"(c4), "r"(bar), "h"((uint16_t)3), "l"(pol) : "memory");
    else asm volatile("cp.async.bulk.tensor.5d.shared::cluster.global.mbarrier::complete_tx::bytes.multicast::cluster [%0], [%1, {%2, %3, %3, %4, %5}], [%6], %7;"
                 ::"r"(dst), "l"(tm), "r"(c0), "r"(0), "r"(c3), "r"(c4), "r"(bar), "h"((uint16_t)3) : "memory");
}
__device__ __forceinline__ void tma_store_4d(const CUtensorMap* tm, uint32_t src, int c0, int c3, uint64_t pol) {
    if (STPOL) asm volatile("cp.async.bulk.tensor.4d.global.shared::cta.bulk_group.L2::cache_hint [%0, {%2, %3, %3, %4}], [%1], %5;"
                 ::"l"(tm), "r"(src), "r"(c0), "r"(0), "r"(c3), "l"(pol) : "memory");
    else asm volatile("cp.async.bulk.tensor.4d.global.shared::cta.bulk_group [%0, {%2, %3, %3, %4}], [%1];"
                 ::"l"(tm), "r"(src), "r"(c0), "r"(0), "r"(c3) : "memory");
}
__device__ __forceinline__ void prefetch_l2(const void* p) {
    asm volatile("prefetch.global.L2 [%0];" ::"l"(p) : "memory");
}
__device__ __forceinline__ void prefetch_tm(const CUtensorMap* tm) {
    asm volatile("prefetch.tensormap [%0];" ::"l"(tm) : "memory");
}
__device__ __forceinline__ uint32_t now_ns() {
    uint32_t t;
    asm volatile("mov.u32 %0, %globaltimer_lo;" : "=r"(t));
    return t;
}
__device__ __forceinline__ bool elect_one() {
    uint32_t p;
    asm volatile("{\n.reg .pred p;\nelect.sync _|p, 0xffffffff;\nselp.u32 %0, 1, 0, p;\n}\n" : "=r"(p));
    return p != 0;
}
#define CLUSTER_ARRIVE() asm volatile("barrier.cluster.arrive.relaxed.aligned;" ::: "memory")
#define CLUSTER_WAIT() asm volatile("barrier.cluster.wait.acquire.aligned;" ::: "memory")

#define WG_FENCE() asm volatile("wgmma.fence.sync.aligned;" ::: "memory")
#define WG_COMMIT() asm volatile("wgmma.commit_group.sync.aligned;" ::: "memory")
#define WG_WAIT(n) asm volatile("wgmma.wait_group.sync.aligned %0;" ::"n"(n) : "memory")

#define ACC32 "{%0,%1,%2,%3,%4,%5,%6,%7,%8,%9,%10,%11,%12,%13,%14,%15,%16,%17,%18,%19,%20,%21,%22,%23,%24,%25,%26,%27,%28,%29,%30,%31}"
#define ACC8(b) "+f"(d[b]), "+f"(d[b + 1]), "+f"(d[b + 2]), "+f"(d[b + 3]), "+f"(d[b + 4]), "+f"(d[b + 5]), "+f"(d[b + 6]), "+f"(d[b + 7])

#define DESC_HI "0x40000040"
template <int BOFF>
__device__ __forceinline__ void wgmma_rs(float (&d)[32], const uint32_t* a, uint32_t b_lo) {
    asm volatile("{\n.reg .b32 tb;\n.reg .b64 db;\nadd.u32 tb, %36, %37;\nmov.b64 db, {tb, " DESC_HI "};\n"
                 "wgmma.mma_async.sync.aligned.m64n64k16.f32.bf16.bf16 " ACC32 ", {%32,%33,%34,%35}, db, 1, 1, 1, 0;\n}\n"
                 : ACC8(0), ACC8(8), ACC8(16), ACC8(24)
                 : "r"(a[0]), "r"(a[1]), "r"(a[2]), "r"(a[3]), "r"(b_lo), "n"(BOFF));
}
__device__ __forceinline__ void wgmma_rs_first(float (&d)[32], const uint32_t* a, uint32_t b_lo, uint32_t accum) {
    asm volatile("{\n.reg .pred p;\n.reg .b64 db;\nsetp.ne.u32 p, %37, 0;\nmov.b64 db, {%36, " DESC_HI "};\n"
                 "wgmma.mma_async.sync.aligned.m64n64k16.f32.bf16.bf16 " ACC32 ", {%32,%33,%34,%35}, db, p, 1, 1, 0;\n}\n"
                 : ACC8(0), ACC8(8), ACC8(16), ACC8(24)
                 : "r"(a[0]), "r"(a[1]), "r"(a[2]), "r"(a[3]), "r"(b_lo), "r"(accum));
}
template <int ACCUM, int BOFF, int D>
__device__ __forceinline__ void wgmma_rs16(float (&d)[32], const uint32_t* a, uint32_t b_lo) {
    asm volatile("{\n.reg .b32 tb;\n.reg .b64 db;\nadd.u32 tb, %12, %13;\nmov.b64 db, {tb, " DESC_HI "};\n"
                 "wgmma.mma_async.sync.aligned.m64n16k16.f32.bf16.bf16 {%0,%1,%2,%3,%4,%5,%6,%7}, {%8,%9,%10,%11}, db, %14, 1, 1, 0;\n}\n"
                 : ACC8(D)
                 : "r"(a[0]), "r"(a[1]), "r"(a[2]), "r"(a[3]), "r"(b_lo), "n"(BOFF), "n"(ACCUM));
}
template <int S>
__device__ __forceinline__ void piece_steps(float (&d)[32], const uint32_t (&w)[96], uint32_t b_lo) {
    if constexpr (S < 24) {
        wgmma_rs16<(S >= CHAINS), (S >> 2) * 128 + (S & 3) * 2, S % CHAINS * 8>(d, &w[4 * S], b_lo);
        piece_steps<S + 1>(d, w, b_lo);
    }
}

__device__ __forceinline__ uint32_t pack_bf16(float lo, float hi) {
    uint32_t r;
    asm("cvt.rn.bf16x2.f32 %0, %1, %2;" : "=r"(r) : "f"(hi), "f"(lo));
    return r;
}

template <int C>
__device__ __forceinline__ void reload_w(uint32_t (&w)[96], const char* base, uint32_t tid16, uint32_t on) {
#define W4(i) "+r"(w[16 * C + 4 * i]), "+r"(w[16 * C + 4 * i + 1]), "+r"(w[16 * C + 4 * i + 2]), "+r"(w[16 * C + 4 * i + 3])
    asm volatile("{\n.reg .pred p;\n.reg .b64 a;\nsetp.ne.u32 p, %19, 0;\ncvt.u64.u32 a, %18;\nadd.u64 a, a, %16;\n"
                 "@p ld.global.cg.v4.u32 {%0,%1,%2,%3}, [a + %17];\n"
                 "@p ld.global.cg.v4.u32 {%4,%5,%6,%7}, [a + %17 + 2048];\n"
                 "@p ld.global.cg.v4.u32 {%8,%9,%10,%11}, [a + %17 + 4096];\n"
                 "@p ld.global.cg.v4.u32 {%12,%13,%14,%15}, [a + %17 + 6144];\n}\n"
                 : W4(0), W4(1), W4(2), W4(3)
                 : "l"(base), "n"(C * 8192), "r"(tid16), "r"(on) : "memory");
#undef W4
}

template <int C>
__device__ __forceinline__ uint32_t entry(uint2 e) { return C < 4 ? e.x >> (8 * C) : e.y >> (8 * (C - 4)); }

template <int C>
__device__ __forceinline__ bool issue_chunk(float (&acc)[32], const uint32_t (&w)[96], uint2 e, uint32_t bars, uint32_t b_lo0, bool ready) {
    if (!ready) mbar_wait(bars + kBarFull + (entry<C>(e) & 0xF8), entry<C>(e) & 1);
    const bool next = C < 5 && mbar_test(bars + kBarFull + (entry<C + 1>(e) & 0xF8), entry<C + 1>(e) & 1);
    const uint32_t b_lo = b_lo0 + (entry<C>(e) & 0xF8) * 64;
    if (!NO_MMA) {
        WG_FENCE();
        if (C == 0) wgmma_rs_first(acc, &w[0], b_lo, e.y & (F_FINE << 24));
        else wgmma_rs<0>(acc, &w[16 * C], b_lo);
        wgmma_rs<2>(acc, &w[16 * C + 4], b_lo);
        wgmma_rs<4>(acc, &w[16 * C + 8], b_lo);
        wgmma_rs<6>(acc, &w[16 * C + 12], b_lo);
        WG_COMMIT();
    }
    return next;
}
template <int C, int PENDING, int MODE>
__device__ __forceinline__ void retire_chunk(uint32_t (&w)[96], uint2 e, const uint8_t (*ws)[3][8], int wg, uint32_t sbase, uint32_t rel_bar, bool rel, const char* swap, uint32_t tid16) {
    if (!NO_MMA) WG_WAIT(PENDING);
    if (rel) mbar_arrive_cluster<1>(rel_bar + (entry<C>(e) & 0xF8));
    if (MODE == 1 && C < 6 - DEFER) reload_w<C>(w, swap, tid16, 1);
    if (MODE == 2 && C >= 6 - NSTG) {
        const uint32_t x = ws[e.y >> 31][wg][C];
        mbar_wait(sbase + kOffBar + kBarSwap + 64 * wg + 8 * C, e.y >> 31);
        const uint32_t a = sbase + (x & 0xF8) * 1024 + tid16;
#pragma unroll
        for (int q = 0; q < 4; q++)
            asm volatile("ld.shared.v4.u32 {%0,%1,%2,%3}, [%4];" : "=r"(w[16 * C + 4 * q]), "=r"(w[16 * C + 4 * q + 1]), "=r"(w[16 * C + 4 * q + 2]), "=r"(w[16 * C + 4 * q + 3])
                         : "r"(a + q * 2048) : "memory");
        asm volatile("bar.sync %0, 128;" ::"r"(4 + wg + ((w[16 * C] | w[16 * C + 4] | w[16 * C + 8] | w[16 * C + 12]) & x & 1)) : "memory");
        if (rel) mbar_arrive_cluster<3>(rel_bar + (x & 0xF8));
    }
}

__device__ __forceinline__ int pub_slot(int g) { return g == 0 ? kSlotL + 1 : g == 1 ? kSlotW + 11 : kSlotW + 14; }
__device__ __forceinline__ int fine_group(uint32_t pos, int ci) {
    const uint32_t q = (pos & 0xFFF) + ci;
    return SHAPE ? q + q / 12 * 12 : 2 * q + (q / 6 + ((pos >> 12) & 1)) * 12;
}
constexpr int kRankF = SHAPE ? 12 : 1, kRankC = SHAPE ? 2 : 1, kSeg = SHAPE ? 16 : 32;
template <int L0, int L1>
__device__ __forceinline__ void prefetch_tile(uint32_t pos, int ci, int rank, int lane, const char* fine, const char* coarse) {
    const bool f = pos & 0x8000;
    const uint32_t row = f ? (fine_group(pos, ci) + kRankF * rank) * 32 : (((pos & 0xFFF) + kRankC * rank) * kGroup + ci) * kSeg;
    const char* p = (f ? fine : coarse) + (size_t)row * 768 + lane * 128;
    const char* q = SHAPE && !f ? p + (kGroup - 1) * kSeg * 768 : p;
#pragma unroll
    for (int l = L0; l < L1; l++) prefetch_l2((l < 3 ? p : q) + l * 4096);
}

__global__ void __cluster_dims__(2, 1, 1) __launch_bounds__(512, 1)
fpn_lateral_kernel(Scratch* const scr, const char* __restrict__ fine, const char* __restrict__ coarse,
                   const char* __restrict__ wlat, const char* __restrict__ wout,
                   const __grid_constant__ CUtensorMap tm_fine, const __grid_constant__ CUtensorMap tm_coarse, const __grid_constant__ CUtensorMap tm_coarse2,
                   const __grid_constant__ CUtensorMap tm_wlat, const __grid_constant__ CUtensorMap tm_wout,
                   const __grid_constant__ CUtensorMap tm_out, const __grid_constant__ Schedule sched) {
    extern __shared__ __align__(1024) unsigned char smem_raw[];
    if (threadIdx.x == 0) CURVE_REC(0, 0);
    uint32_t t_start;
    asm volatile("mov.u32 %0, %clock;" : "=r"(t_start));
    const uint32_t sbase = smem_u32(smem_raw);
    const uint32_t bars = sbase + kOffBar;
    const int rot = !ROT ? 0 : blockIdx.x < 4 * kPieces ? blockIdx.x & 2 : 1;
    const int npc = !ROT ? (blockIdx.x < 2 * kPieces ? 3 : 0) : blockIdx.x < 4 * kPieces ? 2 - (rot >> 1) : 0;
    const int pj = blockIdx.x >> (1 + ROT);
    auto slice = [&](int g) { return g + rot >= 3 ? g + rot - 3 : g + rot; };
    if (threadIdx.x == EARLY_T) {
        mbar_init(bars + kBarW, 1);
        if (WSPLIT) mbar_init(bars + kBarW2, 1);
        mbar_init(bars + kBarL, 1);
        asm volatile("fence.proxy.async.shared::cta;" ::: "memory");
        mbar_expect_tx(bars + kBarW, kTileBytes >> WSPLIT);
        if (WSPLIT) mbar_expect_tx(bars + kBarW2, kTileBytes >> WSPLIT);
        for (int c = 0; c < 2; c++) tma_load_2d(sbase + (kSlotW + 3 * c) * kChunk, &tm_wout, (blockIdx.x & 1) * kColR + rot * kColG, c * 192, bars + (c ? kBarW2 : kBarW));
        prefetch_tm(&tm_coarse);
        if (npc) {
            mbar_expect_tx(bars + kBarL, 6 * 2048);
            tma_load_3d(sbase + kSlotL * kChunk, &tm_wlat, pj * 16, bars + kBarL);
        }
        asm volatile("fence.mbarrier_init.release.cluster;" ::: "memory");
        CURVE_REC(1, 47);
    }
    {
        constexpr int kWw = (36 * WR + 31) / 32;
        const uint32_t t = threadIdx.x - 32, b = blockIdx.x, c = (t >> 5) - kWw, l = ((b >> 1) % (64 / WR)) * (36 * WR) + t;
        const uint32_t row = ((kPos0 + kRankC * (b & 1) + ((t >> 4) & 1)) * kGroup + (b >> 1)) * kSeg + (t & 15);
        const char* p = t >= 32 * kWw ? coarse + row * 768 + c * 128 : (b & 1 ? wlat : wout) + l * 128;
        if (t < 36 * WR || c < TOPPF) prefetch_l2(p);
    }
    const int warp_id = __shfl_sync(0xffffffffu, (int)(threadIdx.x >> 5), 0);
    const int lane = threadIdx.x & 31;
    const int wg = warp_id >> 2;
    const int rank = blockIdx.x & 1;
    const int cid = blockIdx.x >> 1;
    const int pat = cid % NPAT, ci = cid / NPAT;
    const Tile* const tiles = sched.tile[pat];

    if (wg == 3) {
        asm volatile("setmaxnreg.dec.sync.aligned.u32 32;");
        const int j = warp_id & 3;
        const bool lead = elect_one();
        if (j == 3) {
            uint32_t c0;
            asm volatile("mov.u32 %0, %clock;" : "=r"(c0));
            if (lead) CURVE_REC(1, 46);
            if (lead) {
                mbar_init(bars + kBarW + 8, 1);
                mbar_init(bars + kBarW + 16, 1);
                if (WSPLIT) mbar_init(bars + kBarW2 + 8, 1), mbar_init(bars + kBarW2 + 16, 1);
                asm volatile("fence.mbarrier_init.release.cluster;" ::: "memory");
                asm volatile("fence.proxy.async.shared::cta;" ::: "memory");
            }
            __syncwarp();
            CLUSTER_ARRIVE();
            if (lead) {
                for (int g = 1; g < 3; g++) {
                    mbar_expect_tx(bars + kBarW + 8 * g, kTileBytes >> WSPLIT);
                    if (WSPLIT) mbar_expect_tx(bars + kBarW2 + 8 * g, kTileBytes >> WSPLIT);
                }
                for (int g = 2; g < 2 + W_PRE; g++) tma_load_2d(sbase + (kSlotW + 3 * g) * kChunk, &tm_wout, rank * kColR + slice(g >> 1) * kColG, (g & 1) * 192, bars + (g & 1 ? kBarW2 : kBarW) + 8 * (g >> 1));
            }
            __syncwarp();
            CLUSTER_WAIT();
            if (lead) {
                int g = 2 + W_PRE;
#pragma unroll 1
                for (int c = 0; c < 6; c++) {
                    mbar_expect_tx(bars + kBarFull + 8 * c, kChunk);
                    tma_load_5d_mc<false>(sbase + rank * 4096 + c * kChunk, &tm_coarse, c * 64, ci * (kSeg / 8), kPos0 + kRankC * rank, bars + kBarFull + 8 * c, 0);
                    CURVE_REC(1, 52 + c);
                    if ((W_MIX >> c & 1) && g < 6) {
                        tma_load_2d(sbase + (kSlotW + 3 * g) * kChunk, &tm_wout, rank * kColR + slice(g >> 1) * kColG, (g & 1) * 192, bars + (g & 1 ? kBarW2 : kBarW) + 8 * (g >> 1));
                        g++;
                    }
                }
#pragma unroll 1
                for (; g < 6; g++) {
                    tma_load_2d(sbase + (kSlotW + 3 * g) * kChunk, &tm_wout, rank * kColR + slice(g >> 1) * kColG, (g & 1) * 192, bars + (g & 1 ? kBarW2 : kBarW) + 8 * (g >> 1));
                    CURVE_REC(1, 47 + (g >> 1));
                }
            }
            __syncwarp();
            uint32_t cur = sched.pf_from, u = 0, pw = sched.pw_ev[0] == 1;
            const char* p = nullptr;
            bool ok = false;
#pragma unroll 1
            for (uint32_t n = 0; cur < 6 * kTiles; n++) {
                uint32_t v;
                asm volatile("ld.volatile.shared.u32 %0, [%1];" : "=r"(v) : "r"(bars + kStarted) : "memory");
                uint32_t tgt = sched.tgt[v];
                if (cur < sched.t_max) {
                    uint32_t c;
                    asm volatile("mov.u32 %0, %clock;" : "=r"(c));
                    if ((int)(c - c0) >= (int)(sched.t_a + cur * sched.t_d)) tgt = max(tgt, cur + 1);
                }
#pragma unroll 1
                for (; cur < tgt; cur++) {
                    if (u == 0) {
                        const uint32_t pos = tiles[cur / 6].pos;
                        const bool f = pos & 0x8000;
                        const uint32_t row = f ? (fine_group(pos, ci) + kRankF * rank) * 32 + lane : (((pos & 0xFFF) + kRankC * rank + (lane >> 4)) * kGroup + ci) * kSeg + (lane & 15);
                        p = (f ? fine : coarse) + (size_t)row * 768;
                        ok = row < (f ? kFinePix : kCoarsePix);
                    }
                    if (ok) prefetch_l2(p);
                    p += 128;
                    u = u == 5 ? 0 : u + 1;
                }
                if (pw < 2 && v >= sched.pw_ev[pw]) {
                    const char* q = (const char*)&g_wfrag[pw][rank][0][0][0] + lane * 128;
#pragma unroll 1
                    for (int l = ci % sched.pw_div; l < 36; l += sched.pw_div) prefetch_l2(q + l * 4096);
                    pw++;
                }
                if (n == 0x1000000) __trap();
                __nanosleep(sched.fsleep);
            }
        } else if (j == 2) {
            if (lead) CURVE_REC(1, 58);
            CLUSTER_ARRIVE();
            if (lead) {
                uint32_t v;
                asm volatile("ld.relaxed.gpu.global.u32 %0, [%1];" : "=r"(v) : "l"(&g_ready) : "memory");
            }
            if (lead) {
                CURVE_REC(1, 59);
                prefetch_tm(&tm_fine);
                prefetch_tm(&tm_coarse2);
                prefetch_tm(&tm_out);
            }
            __syncwarp();
            CLUSTER_WAIT();
            if (lead) {
                if (npc) {
                    mbar_wait(bars + kBarPiece, 0);
                    asm volatile("fence.proxy.async.shared::cta;" ::: "memory");
                    for (int i = 0; i < 2 * npc; i++)
                        asm volatile("cp.async.bulk.global.shared::cta.bulk_group [%0], [%1], 2048;"
                                     ::"l"(&g_wfrag[i & 1][rank][slice(i >> 1)][pj][0]), "r"(sbase + pub_slot(i >> 1) * kChunk + 4096 + (i & 1) * 2048) : "memory");
                    asm volatile("cp.async.bulk.commit_group;" ::: "memory");
                    asm volatile("cp.async.bulk.wait_group.read 0;" ::: "memory");
                    for (int i = 0; i < 2 * npc; i++) {
                        uint32_t b;
                        asm("mapa.shared::cluster.u32 %0, %1, %2;" : "=r"(b) : "r"(bars + kBarEmpty + 8 * pub_slot(i >> 1)), "r"(i & 1));
                        asm volatile("mbarrier.arrive.shared::cluster.b64 _, [%0], %1;" ::"r"(b), "r"(i < 2 ? 1 : 3) : "memory");
                    }
                    asm volatile("cp.async.bulk.wait_group 0;" ::: "memory");
                    asm volatile("red.relaxed.gpu.global.add.u32 [%0], 1;" ::"l"(&g_ready) : "memory");
                    CURVE_REC(2, 61);
                }
                uint32_t v, n = 0;
                for (;;) {
                    asm volatile("ld.acquire.gpu.global.u32 %0, [%1];" : "=r"(v) : "l"(&g_ready) : "memory");
                    if (v >= (2 * kPieces << ROT)) break;
                    if (++n == 0x100000) __trap();
                    __nanosleep(50);
                }
                CURVE_REC(2, 62);
                mbar_arrive(bars + kBarReady);
                asm volatile("fence.proxy.async.global;" ::: "memory");
                mbar_arrive(bars + kBarReady2);
                if (atomicAdd(&g_done, 1) == gridDim.x - 1) {
                    g_ready = 0;
                    g_done = 0;
                }
                asm volatile("st.volatile.shared.u32 [%0], %1;" ::"r"(bars + kAllowed), "r"(rank == 0 || sched.gate1 ? sched.pace_from : kTiles) : "memory");
                if (rank == 0 || sched.gate1) {
                    const uint16_t* vt = sched.vt[pat];
                    uint32_t* const ctr = g_progress[sched.pgroup * pat];
                    const int last = sched.pace_to - 1;
                    asm volatile("ld.relaxed.gpu.global.u32 %0, [%1];" : "=r"(v) : "l"(ctr) : "memory");
                    const uint32_t base = v & ~0xFFFFu;
                    if (blockIdx.x == 0) asm volatile("red.relaxed.gpu.global.add.u32 [%0], %1;" ::"l"(ctr), "r"(65536 - kVt * kClusters) : "memory");
                    int counted = rank == 0 ? sched.pace_from - 1 : last, allowed = sched.pace_from;
#pragma unroll 1
                    for (n = 0; n < 0x10000 && (allowed <= last || counted < last); n++) {
                        int started;
                        asm volatile("ld.volatile.shared.u32 %0, [%1];" : "=r"(started) : "r"(bars + kStarted) : "memory");
                        started = (started + EV - 1) / EV;
                        if (counted < last && counted < started) {
                            const int upto = min(started, last);
                            asm volatile("red.relaxed.gpu.global.add.u32 [%0], %1;" ::"l"(ctr), "r"(vt[upto] - vt[counted]) : "memory");
                            counted = upto;
                        }
                        if (allowed <= last && started + 1 >= allowed) {
                            asm volatile("ld.relaxed.gpu.global.u32 %0, [%1];" : "=r"(v) : "l"(ctr) : "memory");
                            while (allowed <= last && (int)(v - base) >= sched.need[pat][allowed]) allowed++;
                            asm volatile("st.volatile.shared.u32 [%0], %1;" ::"r"(bars + kAllowed), "r"(allowed > last ? kTiles : allowed) : "memory");
                        }
                        __nanosleep(sched.psleep);
                    }
                    asm volatile("st.volatile.shared.u32 [%0], %1;" ::"r"(bars + kAllowed), "r"(kTiles) : "memory");
                    if (counted < last) asm volatile("red.relaxed.gpu.global.add.u32 [%0], %1;" ::"l"(ctr), "r"(vt[last] - vt[counted]) : "memory");
                }
            }
        } else if (j == 1) {
            if (lead) CURVE_REC(3, 51);
            if (sbase & 1023) __trap();
            if (lead) {
                asm volatile("st.shared.u32 [%0], %1;" ::"r"(bars + kStarted), "r"(0) : "memory");
                asm volatile("st.shared.u32 [%0], %1;" ::"r"(bars + kAllowed), "r"(8) : "memory");
                if (kSlots > 24) {
                    mbar_init(bars + kBarFull + 8 * 24, 1);
                    mbar_init(bars + kBarEmpty + 8 * 24, 6);
                }
                mbar_init(bars + kBarPiece, max(4 * npc, 1));
                mbar_init(bars + kBarReady, 1);
                for (int i = 0; i < 3; i++) mbar_init(bars + kBarEmpty + 8 * (kSlots + i), 1);
                for (int i = 24; i < kSlots + 3; i++) mbar_init(bars + kBarStaged + 8 * i, 4);
                asm volatile("fence.acq_rel.cta;" ::: "memory");
                asm volatile("fence.mbarrier_init.release.cluster;" ::: "memory");
                CURVE_REC(3, 52);
            }
            __syncwarp();
            CLUSTER_ARRIVE();
            CLUSTER_WAIT();
            if (lead) {
                const uint32_t t0 = now_ns();
                uint32_t last[3] = {t0, t0, t0}, peer;
                asm("mapa.shared::cluster.u32 %0, %1, %2;" : "=r"(peer) : "r"(bars + kBarEmpty), "r"(rank ^ 1));
                auto release = [&](uint32_t o) {
                    const uint32_t s8 = o & 0xF8;
                    if (s8 >= 8 * kSlots) mbar_arrive(bars + kBarEmpty + s8);
                    else {
                        asm volatile("mbarrier.arrive.shared::cta.b64 _, [%0], 3;" ::"r"(bars + kBarEmpty + s8) : "memory");
                        mbar_arrive_cluster<3>(peer + s8);
                    }
                };
                uint64_t pol_normal = 0;
                if (STPOL) asm volatile("createpolicy.fractional.L2::evict_normal.b64 %0, 1.0;" : "=l"(pol_normal));
#pragma unroll 1
                for (int t = 0; t < kTiles; t++) {
                    const uint32_t pos = tiles[t].pos, gap = sched.gap[t];
                    if (!(pos & 0x8000)) continue;
                    const int row = fine_group(pos, ci);
                    uint32_t prev = 0;
                    if (tiles[t].pw) {
#pragma unroll 1
                        for (uint32_t n = 0, v = 0; n < 4096 && v < tiles[t].pw; n++) {
                            __nanosleep(20);
                            asm volatile("ld.volatile.shared.u32 %0, [%1];" : "=r"(v) : "r"(bars + kStarted) : "memory");
                        }
                        const uint32_t c = now_ns();
                        const uint32_t stag = sched.stag[t];
                        last[0] = c, last[1] = c + stag, last[2] = c + 2 * stag;
                    }
#pragma unroll
                    for (int g = 0; g < 3; g++) {
                        const uint32_t o = sched.po[t][g] >> 8, s8 = o & 0xF8;
                        mbar_wait1(bars + kBarStaged + s8, o & 1);
                        if (g == 2) CURVE_REC(1, t);
                        if (t < sched.gap_to) {
                            uint32_t c;
                            last[g] += gap;
#pragma unroll 1
                            for (int n = 0; n < 4096; n++) {
                                c = now_ns();
                                if ((int)(c - last[g]) >= 0) break;
                                __nanosleep(20);
                            }
                            if ((int)(c - last[g]) > sched.gslack) last[g] = c - sched.gslack;
                        }
                        asm volatile("fence.proxy.async.shared::cta;" ::: "memory");
                        tma_store_4d(&tm_out, sbase + s8 * 1024, rank * kColR + slice(g) * kColG, row, pol_normal);
                        asm volatile("cp.async.bulk.commit_group;" ::: "memory");
                        if (prev & 4) {
                            asm volatile("cp.async.bulk.wait_group.read 1;" ::: "memory");
                            release(prev);
                        }
                        prev = o;
                    }
                    if (prev & 4) {
                        asm volatile("cp.async.bulk.wait_group.read 0;" ::: "memory");
                        release(prev);
                    }
                    CURVE_REC(3, t);
                }
                asm volatile("cp.async.bulk.wait_group.read 0;" ::: "memory");
            }
        } else {
            if (lead) CURVE_REC(1, 50);
            CLUSTER_ARRIVE();
            uint4 e = *(const uint4*)&tiles[1];
            asm volatile("" : "+r"(e.x), "+r"(e.y), "+r"(e.w));
            CLUSTER_WAIT();
            if (lead) CURVE_REC(1, 51);
            if (lead) {
                uint32_t dst0 = sbase + rank * 4096, bar0 = bars;
                asm volatile("" : "+r"(dst0), "+r"(bar0));
                uint32_t wk = 0, wi = 0;
                int allowed = 0;
                uint64_t pol_first, pol_normal;
                asm volatile("createpolicy.fractional.L2::evict_first.b64 %0, 1.0;" : "=l"(pol_first));
                asm volatile("createpolicy.fractional.L2::evict_normal.b64 %0, 1.0;" : "=l"(pol_normal));
#pragma unroll 1
                for (int t = EARLY ? 1 : 0; t < kTiles; t++) {
                    if (t > 1) e = *(const uint4*)&tiles[t];
                    const bool f = e.w & 0x8000;
                    const CUtensorMap* tm = f ? &tm_fine : ci < kFull ? &tm_coarse : &tm_coarse2;
                    const int c3 = f ? 0 : ci * (kSeg / 8), c4 = f ? fine_group(e.w, ci) + kRankF * rank : (e.w & 0xFFF) + kRankC * rank;
                    for (uint32_t n = 0; t >= allowed; n++) {
                        asm volatile("ld.volatile.shared.u32 %0, [%1];" : "=r"(allowed) : "r"(bar0 + kAllowed) : "memory");
                        if (n == 0x4000000) __trap();
                        if (n) __nanosleep(20);
                    }
                    if (t) CURVE_REC(0, t);
#pragma unroll
                    for (int c = 0; c < 6; c++) {
                        if (c % (6 / EV) == 0) asm volatile("st.volatile.shared.u32 [%0], %1;" ::"r"(bar0 + kStarted), "r"(EV * t + 1 + c / (6 / EV)) : "memory");
                        const uint32_t x = c < 4 ? e.x >> (8 * c) : e.y >> (8 * (c - 4)), s8 = x & 0xF8;
                        mbar_wait1(bar0 + kBarEmpty + s8, (x >> 1) & 1);
                        mbar_expect_tx(bar0 + kBarFull + s8, kChunk);
                        tma_load_5d_mc<LD_EF>(dst0 + s8 * 1024, tm, c * 64, c3, c4, bar0 + kBarFull + s8, x & 4 ? pol_first : pol_normal);
#pragma unroll 1
                        for (uint32_t n = (e.w >> (16 + 2 * c)) & 3; n; n--) {
                            if (wk == 0) mbar_wait(bar0 + kBarReady2, 0);
                            const uint32_t o = sched.worder[wk], y = (&sched.wslot[pat][wi][0][0])[o];
                            mbar_wait1(bar0 + kBarEmpty + (y & 0xF8), (y >> 1) & 1);
                            mbar_expect_tx(bar0 + kBarSwap + 8 * o, kChunk);
                            bulk_load(sbase + (y & 0xF8) * 1024, (const char*)&g_wfrag[0][rank][0][0][0] + (6 * slice(o >> 3) + (o & 7)) * kChunk, bar0 + kBarSwap + 8 * o);
                            if (++wk == 3 * NSTG) wk = 0, wi++;
                        }
                    }
                }
            }
        }
        __syncwarp();
    } else {
        if (elect_one()) {
            for (int i = 2 * warp_id; i < 2 * warp_id + 2; i++) {
                mbar_init(bars + kBarSwap + 8 * i, 1);
                if (i >= kSlots) continue;
                mbar_init(bars + kBarFull + 8 * i, 1);
                mbar_init(bars + kBarEmpty + 8 * i, 6);
                mbar_init(bars + kBarStaged + 8 * i, 4);
            }
            asm volatile("fence.mbarrier_init.release.cluster;" ::: "memory");
        }
        __syncwarp();
        CLUSTER_ARRIVE();
        asm volatile("setmaxnreg.inc.sync.aligned.u32 160;");
        const int tid = threadIdx.x & 127;
        const int warp = tid >> 5;
        const bool rel = tid < 2;
        uint32_t rel_bar;
        asm("mapa.shared::cluster.u32 %0, %1, %2;" : "=r"(rel_bar) : "r"(bars + kBarEmpty), "r"(tid & 1));
        const uint32_t b_lo0 = ((sbase & 0x3FFFF) >> 4) | 0x10000u;
        const uint32_t frag_off = ((lane >> 4) * 8 + (lane & 7)) * 128 + (((2 * warp + ((lane >> 3) & 1)) ^ (lane & 7)) << 4);
        uint32_t st_addr = sbase + frag_off, tid16 = tid * 16;
        asm volatile("" : "+r"(st_addr), "+r"(tid16));
        uint4* const wf = &g_wfrag[0][rank][slice(wg)][pj][tid];
        constexpr int kSet = 2 * 3 * 24 * 128;

        float acc[32];
        uint32_t w[96], p[16];

        auto load_w = [&]() {
        mbar_wait(bars + kBarW + 8 * wg, 0);
        if (tid == 0) CURVE_REC(3, 48 + wg);
        const uint32_t w_addr = sbase + (kSlotW + 6 * wg) * kChunk + frag_off;
#pragma unroll
        for (int s = 0; s < 24; s++) {
            if (WSPLIT && s == 12) mbar_wait(bars + kBarW2 + 8 * wg, 0);
            asm volatile("ldmatrix.sync.aligned.m8n8.x4.trans.shared.b16 {%0,%1,%2,%3}, [%4];"
                         : "=r"(w[4 * s]), "=r"(w[4 * s + 1]), "=r"(w[4 * s + 2]), "=r"(w[4 * s + 3]) : "r"(w_addr + s * 2048) : "memory");
        }
        if (wg < npc) {
            asm volatile("ldmatrix.sync.aligned.m8n8.x4.trans.shared.b16 {%0,%1,%2,%3}, [%4];"
                         : "=r"(p[0]), "=r"(p[1]), "=r"(p[2]), "=r"(p[3]) : "r"(w_addr + pj * 2048) : "memory");
            if (!PUBTMA) wf[0] = make_uint4(p[0], p[1], p[2], p[3]);
        }
        asm volatile("bar.sync %0, 128;" ::"r"(4 + wg) : "memory");
        {
            const uint32_t m = (wg == 2 ? 0x3F : 0xFFF) & ~(PUBTMA && wg && wg < npc ? 3u << 2 * (pub_slot(wg) - kSlotW - 6 * wg) : 0u);
            asm volatile("{\n.reg .pred p;\nsetp.ne.u32 p, %1, 0;\n@p mbarrier.arrive.shared::cluster.b64 _, [%0], 3;\n}\n"
                         ::"r"(rel_bar + 8 * (kSlotW + 6 * wg + (tid >> 1))), "r"(tid < 12 ? m >> tid & 1 : 0) : "memory");
        }
        if (threadIdx.x == 0) CURVE_REC(2, 59);
        if (wg < npc) {
            mbar_wait(bars + kBarL, 0);
            if (threadIdx.x == 0) CURVE_REC(3, 61);
            WG_FENCE();
            piece_steps<0>(acc, w, b_lo0 + kSlotL * 512);
            WG_COMMIT();
            WG_WAIT(0);
#pragma unroll
            for (int i = 0; i < 8; i++) {
                asm volatile("" : "+f"(acc[i]), "+f"(acc[8 + i]), "+f"(acc[16 + i]), "+f"(acc[24 + i]));
                if (CHAINS == 2) acc[i] += acc[8 + i];
                if (CHAINS == 4) acc[i] = (acc[i] + acc[8 + i]) + (acc[16 + i] + acc[24 + i]);
            }
            const uint32_t a = sbase + pub_slot(wg) * kChunk + 4096 + tid16;
            asm volatile("st.shared.v4.u32 [%0], {%1,%2,%3,%4};" ::"r"(a), "r"(p[0]), "r"(p[1]), "r"(p[2]), "r"(p[3]) : "memory");
            asm volatile("st.shared.v4.u32 [%0], {%1,%2,%3,%4};" ::"r"(a + 2048), "r"(pack_bf16(acc[0], acc[1])), "r"(pack_bf16(acc[2], acc[3])),
                         "r"(pack_bf16(acc[4], acc[5])), "r"(pack_bf16(acc[6], acc[7])) : "memory");
            __syncwarp();
            if (threadIdx.x == 0) CURVE_REC(3, 62);
            if (lane == 0) mbar_arrive(bars + kBarPiece);
        }
        if (tid < (PUBTMA && wg == 0 && npc ? 2 : 4)) mbar_arrive_cluster<1>(rel_bar + 8 * (kSlotL + (tid >> 1)));
        if (threadIdx.x == 256) CURVE_REC(2, 60);
        };
        if (tid == 0) CURVE_REC(3, 46);
        CLUSTER_WAIT();
        if (tid == 0) CURVE_REC(3, 47);
#pragma unroll
        for (int i = 0; i < 16; i++) p[i] = 0;

        const int tok_in = 1 + wg, tok_out = wg == 2 ? 1 : wg + 2;
#pragma unroll 1
        for (int t = 0; t < kTiles; t++) {
            const uint2 e = *(const uint2*)&tiles[t];
            const uint32_t fl = e.y >> 24, pe = sched.po[t][wg];
            const uint32_t p_addr = sbase + (pe & 0xF8) * 1024 + tid16;
            if ((~fl & (F_FINE | F_P)) == 0) {
#pragma unroll
                for (int q = 0; q < 4; q++)
                    asm volatile("ld.shared.v4.u32 {%0,%1,%2,%3}, [%4];" : "=r"(p[4 * q]), "=r"(p[4 * q + 1]), "=r"(p[4 * q + 2]), "=r"(p[4 * q + 3])
                                 : "r"(p_addr + q * 2048) : "memory");
            }
            const char* swap = (const char*)&g_wfrag[1][rank][slice(wg)][0][0];
            auto init = [&](auto quarter) {
                constexpr int Q = decltype(quarter)::value;
#pragma unroll
                for (int i = 0; i < 8; i++)
                    asm volatile("shl.b32 %0, %4, 16;\nshl.b32 %1, %4, 16;\nand.b32 %2, %4, 0xffff0000;\nand.b32 %3, %4, 0xffff0000;"
                                 : "=f"(acc[4 * i]), "=f"(acc[4 * i + 1]), "=f"(acc[4 * i + 2]), "=f"(acc[4 * i + 3]) : "r"(p[4 * Q + (i & 3)]));
            };
            if (fl & F_FINE) {
                if (fl & F_Q2) {
                    if (fl & F_Q1) init(std::integral_constant<int, 3>());
                    else init(std::integral_constant<int, 2>());
                } else {
                    if (fl & F_Q1) init(std::integral_constant<int, 1>());
                    else {
                        if (DEFER >= 3) reload_w<3>(w, swap, tid16, ~fl & F_P);
                        if (DEFER >= 2) reload_w<4>(w, swap, tid16, ~fl & F_P);
                        if (DEFER >= 1) reload_w<5>(w, swap, tid16, ~fl & F_P);
                        init(std::integral_constant<int, 0>());
                    }
                }
            }
            if (fl & F_READY) {
                if (INLOOP && t == 0) load_w();
                else mbar_wait(bars + kBarReady, 0);
            }
            mbar_wait(bars + kBarFull + (e.x & 0xF8), e.x & 1);
            asm volatile("{\n.reg .pred p;\nsetp.eq.u32 p, %1, 0;\n@p bar.sync %0, 256;\n}\n" ::"r"(tok_in), "r"(pe & 1) : "memory");
            auto body = [&](auto mode) {
                constexpr int M = decltype(mode)::value;
                if (M == 1 && DEFER) asm volatile("{\n.reg .pred p;\nsetp.ne.u32 p, %0, 0;\n@p trap;\n}\n" ::"r"(w[95] & e.y & 0x40000));
                bool rdy = issue_chunk<0>(acc, w, e, bars, b_lo0, true);
                CREC0(0);
                rdy = issue_chunk<1>(acc, w, e, bars, b_lo0, rdy);
                CREC0(1);
                if (TOKEN_K == 2) asm volatile("{\n.reg .pred p;\nsetp.eq.u32 p, %1, 0;\n@p bar.arrive %0, 256;\n}\n" ::"r"(tok_out), "r"(pe & 4) : "memory");
                retire_chunk<0, 1, M>(w, e, sched.wslot[pat], wg, sbase, rel_bar, rel, swap, tid16);
                if (M == 0 && rel && (~fl & (F_FINE | F_P)) == 0) mbar_arrive_cluster<3>(rel_bar + (pe & 0xF8));
                rdy = issue_chunk<2>(acc, w, e, bars, b_lo0, rdy);
                CREC0(2);
                if (TOKEN_K == 3) asm volatile("{\n.reg .pred p;\nsetp.eq.u32 p, %1, 0;\n@p bar.arrive %0, 256;\n}\n" ::"r"(tok_out), "r"(pe & 4) : "memory");
                retire_chunk<1, 1, M>(w, e, sched.wslot[pat], wg, sbase, rel_bar, rel, swap, tid16);
                rdy = issue_chunk<3>(acc, w, e, bars, b_lo0, rdy);
                CREC0(3);
                retire_chunk<2, 1, M>(w, e, sched.wslot[pat], wg, sbase, rel_bar, rel, swap, tid16);
                rdy = issue_chunk<4>(acc, w, e, bars, b_lo0, rdy);
                CREC0(4);
                retire_chunk<3, 1, M>(w, e, sched.wslot[pat], wg, sbase, rel_bar, rel, swap, tid16);
                rdy = issue_chunk<5>(acc, w, e, bars, b_lo0, rdy);
                CREC0(5);
                retire_chunk<4, 1, M>(w, e, sched.wslot[pat], wg, sbase, rel_bar, rel, swap, tid16);
                if (M != 1) mbar_wait(bars + kBarEmpty + (pe >> 11) * 8, (pe >> 9) & 1);
                retire_chunk<5, 0, M>(w, e, sched.wslot[pat], wg, sbase, rel_bar, rel, swap, tid16);
            };
            if (!(fl & F_SWAP)) body(std::integral_constant<int, 0>());
            else if (fl & F_STAGED) body(std::integral_constant<int, 2>());
            else body(std::integral_constant<int, 1>());
            if (fl & F_FINE) {
#pragma unroll
                for (int q = 0; q < 4; q++)
                    asm volatile("stmatrix.sync.aligned.m8n8.x4.trans.shared.b16 [%0], {%1,%2,%3,%4};" ::"r"(st_addr + (pe >> 11) * kChunk + q * 2048),
                                 "r"(pack_bf16(acc[8 * q], acc[8 * q + 1])), "r"(pack_bf16(acc[8 * q + 2], acc[8 * q + 3])),
                                 "r"(pack_bf16(acc[8 * q + 4], acc[8 * q + 5])), "r"(pack_bf16(acc[8 * q + 6], acc[8 * q + 7])) : "memory");
                __syncwarp();
                asm volatile("{\n.reg .pred p;\nelect.sync _|p, 0xffffffff;\n@p mbarrier.arrive.shared::cta.b64 _, [%0];\n}\n" ::"r"(bars + kBarStaged + (pe >> 11) * 8) : "memory");
            } else {
#pragma unroll
                for (int q = 0; q < 4; q++) {
                    p[4 * q] = pack_bf16(acc[8 * q], acc[8 * q + 2]);
                    p[4 * q + 1] = pack_bf16(acc[8 * q + 1], acc[8 * q + 3]);
                    p[4 * q + 2] = pack_bf16(acc[8 * q + 4], acc[8 * q + 6]);
                    p[4 * q + 3] = pack_bf16(acc[8 * q + 5], acc[8 * q + 7]);
                    if (fl & F_P)
                        asm volatile("st.shared.v4.u32 [%0], {%1,%2,%3,%4};" ::"r"(p_addr + q * 2048),
                                     "r"(p[4 * q]), "r"(p[4 * q + 1]), "r"(p[4 * q + 2]), "r"(p[4 * q + 3]) : "memory");
                }
            }
        }
        if (warp_id == 11 && (sched.fin[0] >> lane & 1)) mbar_wait(bars + kBarEmpty + 8 * lane, sched.fin[1] >> lane & 1);
        __syncwarp();
    }
    CLUSTER_ARRIVE();
    CLUSTER_WAIT();
    if (threadIdx.x == 0) CURVE_REC(0, 63);
}

int digit(char ch) { return ch >= 'a' ? ch - 'a' + 10 : ch >= 'A' ? ch - 'A' + 36 : ch - '0'; }
void build_schedule(int pat, Tile* tl, uint16_t (*po)[4], uint32_t* fin, uint8_t (*wslot)[3][8], uint8_t* worder, const int* gs) {
    const char* park = envs("OUT", "000000000000000000099000000000000446708zzz55");
    uint8_t out[kTiles][3] = {};
    int parked[kSlots] = {}, nth[kTiles][3];
    const int take[3] = {TAKE}, give[3] = {GIVE};
    const int staged = envi("STAGED", 1), wadv = envi("WADV", 0), wrel = envi("WREL", 1), wslack = envi("WSLACK", 0), wmax = envi("WMAX", 3);
    const char* depth = envs("DEPTH", "zzzzzzzzzzzzzhzzzzzhhdzzzzzzzddgfgcbggggghe9");
    int coarse_of[16];
    int n = 0, nsw = 0, swt[2] = {};
    int units[kTiles];
    auto unit = [&](int t) { return units[t]; };
    for (int g = 0, i0 = 0; gs[g]; i0 += gs[g], g++) {
        for (int i = 1; i <= gs[g]; i++, n++) {
            units[n] = i0 + i % gs[g];
            tl[n].pos = (units[n] * NPAT + pat) * (SHAPE ? 4 : 2);
            tl[n].flags = i < gs[g] ? F_P : F_SWAP | (g == 0 ? F_READY : 0);
            coarse_of[unit(n)] = n;
        }
        for (int i = 0; i < 4 * gs[g] && n < kTiles; i++, n++) {
            units[n] = i0 + i / 4;
            tl[n].pos = 0x8000 + (SHAPE ? ((units[n] * NPAT + pat) * 4 + (i & 3)) * kGroup : ((units[n] * NPAT + pat) * 2 + (i & 3) / 2) * kGroup + (i & 1) * 0x1000);
            tl[n].flags = F_FINE | (i >= 4 && (i & 3) == 0 ? F_P : 0) | (i & 1 ? F_Q1 : 0) | (i & 2 ? F_Q2 : 0);
            if (i == 4 * gs[g] - 1 && gs[g + 1]) {
                tl[n].flags |= staged ? F_SWAP | F_STAGED | (nsw ? F_SW1 : 0) : F_SWAP;
                if (staged) swt[nsw++] = n;
            }
        }
    }
    int nwo = 0;
    for (int need = -4; need < 6; need++)
        for (int g = 0; g < 3; g++) {
            const int c = need - give[g];
            if (c < 6 - NSTG || c > 5) continue;
            worder[nwo++] = g * 8 + c;
            for (int i = 0; i < nsw && !wslack; i++) {
                const int j = 6 * swt[i] + need + 4 - wadv;
                tl[j / 6].wcnt += 1 << (2 * (j % 6));
            }
        }
    int uses[kSlots], loads[kSlots], queue[512], head = 0, tail = 0, slot_of[6 * kTiles];
    for (int s = 0; s < kSlots; s++) uses[s] = s >= kSlotL, loads[s] = 0;
    auto take_p = [&](int t, int w, int s) { tl[t].p[w] = s * 8 + ((uses[s] + 1) & 1) * 2; uses[s]++; };
    bool taken[kSlots] = {};
    for (int w = 0; w < 3; w++)
        if (take[w] < 0 && (tl[0].flags & F_P)) take_p(0, w, kSlotW + 6 * w + 2), taken[kSlotW + 6 * w + 2] = true;
    for (int s = 0; s < kSlotL; s++) queue[tail++] = s;
    for (int s = kSlotW; s < kSlots; s++) if (!taken[s]) queue[tail++] = s;
    for (int s = kSlotL; s < kSlotW; s++) queue[tail++] = s;
    int r = 0, wk = 0, wi = 0;
    int rel[512];
    for (int i = 0; i < tail; i++) rel[i] = -1;
    auto get_slot = [&](int from) {
        for (; r < 6 * kTiles; r++) {
            for (int i = head; i < tail; i++)
                if (rel[i] >= from) {
                    const int s = queue[i];
                    for (; i > head; i--) queue[i] = queue[i - 1], rel[i] = rel[i - 1];
                    head++;
                    return s;
                }
            for (int i = tail; i < tail + 16; i++) rel[i] = r;
            bool to_p = false;
            for (int w = 0; w < 3; w++) {
                int x = r - take[w];
                if (x >= 0 && x % 6 == 0 && x / 6 < kTiles && (tl[x / 6].flags & (F_FINE | F_P)) == F_P) take_p(x / 6, w, slot_of[r]), to_p = true;
                if (x >= 0 && x % 6 == 0 && x / 6 < kTiles && (tl[x / 6].flags & F_FINE) && park[x / 6] != '0') {
                    if (head == tail) to_p = true;
                    const int s = to_p ? slot_of[r] : queue[head++];
                    out[x / 6][w] = s * 8 + ((uses[s] + 1) & 1) * 2 + (parked[s] & 1);
                    nth[x / 6][w] = ++uses[s], parked[s]++;
                }
                for (int t = 0; t < kTiles; t++)
                    if ((tl[t].flags & F_FINE) && park[t] != '0' && r == 6 * t + 4 + give[w] + 2 * digit(park[t])) queue[tail++] = out[t][w] >> 3;
            }
            if (!to_p) queue[tail++] = slot_of[r];
            for (int w = 0; w < 3; w++) {
                int x = r - give[w];
                if (x >= 0 && x % 6 == 0 && x / 6 < kTiles && (tl[x / 6].flags & (F_FINE | F_P)) == (F_FINE | F_P)) {
                    tl[x / 6].p[w] = tl[coarse_of[unit(x / 6)]].p[w];
                    queue[tail++] = tl[x / 6].p[w] >> 3;
                }
                x -= wrel;
                if (x >= 0 && x / 6 < kTiles && (tl[x / 6].flags & F_STAGED) && x % 6 >= 6 - NSTG) queue[tail++] = wslot[tl[x / 6].flags >> 7][w][x % 6] >> 3;
            }
        }
        return 0;
    };
    for (int c = 0; c < 6 * kTiles; c++) {
        const char dp = depth[c / 6];
        int s = get_slot(dp == 'z' ? -1 : c - 4 - (dp > '9' ? dp - 'a' + 10 : dp - '0'));
        slot_of[c] = s;
        tl[c / 6].chunk[c % 6] = s * 8 + ((uses[s] + 1) & 1) * 2 + (loads[s] & 1);
        if (c % 6 == 0 && c) tl[c / 6 - 1].chunk[6] = tl[c / 6].chunk[0];
        uses[s]++, loads[s]++;
        for (int k = wslack ? wmax : (tl[c / 6].wcnt >> (2 * (c % 6))) & 3; k; k--) {
            if (wslack) {
                if (wi == nsw || 6 * swt[wi] + (worder[wk] & 7) + give[worder[wk] >> 3] - r > wslack) break;
                tl[c / 6].wcnt += 1 << (2 * (c % 6));
            }
            s = get_slot(-1);
            (&wslot[wi][0][0])[worder[wk]] = s * 8 + ((uses[s] + 1) & 1) * 2;
            uses[s]++;
            if (++wk == 3 * NSTG) wk = 0, wi++;
        }
    }
    get_slot(6 * kTiles);
    fin[0] = (1u << kSlots) - 1, fin[1] = 0;
    for (int s = 0; s < kSlots; s++) fin[1] |= ((uses[s] + 1) & 1) << s;
    for (int t = 0, k = 1; t < kTiles; t++)
        if (!(tl[t].flags & F_FINE)) memcpy(out[t], tl[t].p, 3);
        else if (park[t] == '0') {
            for (int w = 0; w < 3; w++) out[t][w] = (kSlots + w) * 8 + (strchr(park + t + 1, '0') ? 4 : 0) + (k & 1) * 2 + (~k & 1);
            k++;
        } else
            for (int w = 0; w < 3; w++) {
                if (uses[out[t][w] >> 3] > nth[t][w]) out[t][w] |= 4;
                else fin[0] &= ~(1u << (out[t][w] >> 3));
            }
    if (INLOOP) tl[0].flags |= F_READY;
    const char* free_run = envs("NOTOK", "710000000000000000000000000000000000000000071");
    for (int t = 0; t <= kTiles; t++)
        for (int w = 0; w < 3; w++)
            if ((free_run[t] - '0') >> w & 1) {
                tl[t].p[w] |= 1;
                if (w) tl[t].p[w - 1] |= 4;
                else if (t) tl[t - 1].p[2] |= 4;
            }
    for (int t = 0; t < kTiles; t++)
        for (int w = 0; w < 3; w++) po[t][w] = tl[t].p[w] + 256 * out[t][w];
}

typedef CUresult (*EncodeFn)(CUtensorMap*, CUtensorMapDataType, cuuint32_t, void*, const cuuint64_t*, const cuuint64_t*,
                             const cuuint32_t*, const cuuint32_t*, CUtensorMapInterleave, CUtensorMapSwizzle,
                             CUtensorMapL2promotion, CUtensorMapFloatOOBfill);

void encode_2d(EncodeFn enc, CUtensorMap* tm, const void* ptr, uint64_t rows, uint32_t box_rows, CUtensorMapL2promotion promo) {
    cuuint64_t dims[2] = {(cuuint64_t)kC, rows};
    cuuint64_t strides[1] = {(cuuint64_t)kC * 2};
    cuuint32_t box[2] = {64, box_rows};
    cuuint32_t es[2] = {1, 1};
    enc(tm, CU_TENSOR_MAP_DATA_TYPE_BFLOAT16, 2, const_cast<void*>(ptr), dims, strides, box, es, CU_TENSOR_MAP_INTERLEAVE_NONE,
        CU_TENSOR_MAP_SWIZZLE_128B, promo, CU_TENSOR_MAP_FLOAT_OOB_FILL_NONE);
}

}

extern "C" void kernel_launch(void* const* d_in, const int* in_sizes, int n_in, void* d_out, int out_size) {
    (void)in_sizes; (void)n_in; (void)out_size;
    static EncodeFn enc = nullptr;
    static Schedule sched;
    static Scratch* scr;
    if (!enc) {
        cudaGetSymbolAddress((void**)&scr, g_scratch);
        void* fn = nullptr;
        cudaDriverEntryPointQueryResult qr;
        cudaGetDriverEntryPoint("cuTensorMapEncodeTiled", &fn, cudaEnableDefault, &qr);
        enc = (EncodeFn)fn;
        cudaFuncSetAttribute(fpn_lateral_kernel, cudaFuncAttributeMaxDynamicSharedMemorySize, kSmemBytes);
        if (envi("CARVE", 0)) cudaFuncSetAttribute(fpn_lateral_kernel, cudaFuncAttributePreferredSharedMemoryCarveout, envi("CARVE", 0));
        cudaLaunchConfig_t cfg = {};
        cfg.gridDim = dim3(2);
        cfg.blockDim = dim3(512);
        cfg.dynamicSmemBytes = kSmemBytes;
        cudaLaunchAttribute at;
        at.id = cudaLaunchAttributeClusterDimension;
        at.val.clusterDim.x = 2; at.val.clusterDim.y = 1; at.val.clusterDim.z = 1;
        cfg.attrs = &at; cfg.numAttrs = 1;
        int ncl = 0;
        if (cudaOccupancyMaxActiveClusters(&ncl, fpn_lateral_kernel, &cfg) != cudaSuccess) { (void)cudaGetLastError(); ncl = 0; }
        const char* pn[4] = {"PATA", "PATB", "PATC", "PATD"};
        const char* pd[4] = {"45", "45", "36", "63"};
        sched.pgroup = envi("PGROUP", 0), sched.members = sched.pgroup ? kGroup : kClusters;
        for (int q = 0; q < NPAT; q++) {
            int gs[8] = {};
            const char* sa = envs(pn[q], pd[q]);
            for (int i = 0; sa[i]; i++) gs[i] = sa[i] - '0';
            build_schedule(q, sched.tile[q], sched.po, sched.fin, sched.wslot[q], sched.worder, gs);
        }
        {
            const char* gaps = envs("GAPS", "00000lmjonnlnomm0011occ4kl0r4009581401000000");
            const char* lef = envs("LEF", "60000000000000000000000000200000025666666666");
            const uint8_t masks[7] = {0, 1, 9, 0x15, 0x1B, 0x1F, 0x3F};
            for (int t = 0; t < kTiles; t++) {
                const int tr = digit(envs("TRIG", "0000000000000000007d000a000050a009a8dg000000")[t]);
                sched.tile[0][t].pw = tr ? min(EV * t + tr, EV * kTiles) : 0;
                sched.stag[t] = digit(envs("STG", "55555555555555555500555555556648345975555555")[t]) * 100;
                const int d = digit(gaps[t]);
                sched.gap[t] = (d > 36 ? 3 * d - 72 : d) * envi("GUNIT", 75);
                if (gaps[t] != '0' || envi("GALL", 0)) sched.gap_to = t + 1;
                for (int c = 0; c < 6; c++) sched.tile[0][t].chunk[c] |= (masks[lef[t] - '0'] >> c & 1) * 4;
            }
            sched.gslack = envi("GSLACK", 0);
            const char* lead = envs("LEAD3", "00044000013267hhfnnbakglfnmpnnoommgkifjdcefefbb7ca888888368baaa78aaa8a9994cb8ceeaa9b99579ba88c47447986756687667977666888866157chgf77");
            sched.pf_from = envi("PFFROM", 24);
            int pos = sched.pf_from + envi("PF0", 0);
            sched.tgt[0] = pos;
            for (int e = 0; e < EV * kTiles; e++) {
                const int x = (e + 1) * (6 / EV) + digit(lead[e]);
                if (pos < x) pos = x;
                if (pos > 6 * kTiles) pos = 6 * kTiles;
                sched.tgt[e + 1] = pos;
            }
            sched.pw_ev[0] = envi("PW0", 0) * EV / 6 + 1, sched.pw_ev[1] = envi("PW1", 144) * EV / 6 + 1, sched.pw_div = envi("PWDIV", 4);
            sched.t_a = envi("TA", 0), sched.t_d = envi("TD", 290), sched.t_max = envi("TMAX", 0), sched.fsleep = envi("FSLEEP", 40);
        }
        sched.gate1 = envi("GATE1", 1), sched.psleep = envi("PSLEEP", 20);
        sched.pace_from = envi("PACE_FROM", 18), sched.pace_to = envi("PACE_TO", 44);
        const char* v5 = envs("VTA", "55555555555577799664465555411113165978668689");
        const char* vts[4] = {v5, envs("VTB", v5), envs("VTC", v5), envs("VTD", v5)};
        int total = 0;
        for (int q = 0; q < NPAT; q++) {
            int sum[kTiles + 1] = {};
            for (int t = sched.pace_from; t < sched.pace_to; t++) sum[t] = sum[t - 1] + vts[q][t] - '0';
            total = sum[sched.pace_to - 1];
            for (int t = sched.pace_from; t < sched.pace_to; t++) {
                sched.vt[q][t] = sum[t] * kVt / total;
                const int slack = digit(envs("SLK", "000000000jlonpzzmggvojg8fha6ghfgb6ah7cdgie8y")[t]) * 8;
                sched.need[q][t] = ncl >= kClusters ? 65536 - kVt * kClusters + sched.vt[q][t] * sched.members - slack * 5 * kVt / total * sched.members / 64 : -1;
            }
        }
    }
    CUtensorMap tm_fine, tm_coarse, tm_coarse2, tm_wlat, tm_wout, tm_out;
    const cuuint32_t ones[5] = {1, 1, 1, 1, 1};
    {
        cuuint64_t dims[5] = {(cuuint64_t)kC, 2, 4, 4, (cuuint64_t)kFinePix / 32};
        cuuint64_t strides[4] = {768, 2 * 768, 8 * 768, 32 * 768};
        cuuint32_t box[5] = {64, 2, 4, 4, 1};
        enc(&tm_fine, CU_TENSOR_MAP_DATA_TYPE_BFLOAT16, 5, d_in[0], dims, strides, box, ones, CU_TENSOR_MAP_INTERLEAVE_NONE,
            CU_TENSOR_MAP_SWIZZLE_128B, CU_TENSOR_MAP_L2_PROMOTION_L2_128B, CU_TENSOR_MAP_FLOAT_OOB_FILL_NONE);
    }
    {
        cuuint64_t dims[3] = {64, (cuuint64_t)kC, 6};
        cuuint64_t strides[2] = {768, 128};
        cuuint32_t box[3] = {64, 16, 6};
        cuuint32_t es[3] = {1, 1, 1};
        enc(&tm_wlat, CU_TENSOR_MAP_DATA_TYPE_BFLOAT16, 3, d_in[2], dims, strides, box, es, CU_TENSOR_MAP_INTERLEAVE_NONE,
            CU_TENSOR_MAP_SWIZZLE_128B, CU_TENSOR_MAP_L2_PROMOTION_L2_256B, CU_TENSOR_MAP_FLOAT_OOB_FILL_NONE);
    }
    encode_2d(enc, &tm_wout, d_in[3], kC, 192, CU_TENSOR_MAP_L2_PROMOTION_L2_256B);
    {
        cuuint64_t dims[4] = {(cuuint64_t)kC, 32, 2, (cuuint64_t)kFinePix / 32 - kRankF};
        cuuint64_t strides[3] = {768, kRankF * 32 * 768, 32 * 768};
        cuuint32_t box[4] = {64, 32, 2, 1};
        enc(&tm_out, CU_TENSOR_MAP_DATA_TYPE_BFLOAT16, 4, d_out, dims, strides, box, ones, CU_TENSOR_MAP_INTERLEAVE_NONE,
            CU_TENSOR_MAP_SWIZZLE_128B, CU_TENSOR_MAP_L2_PROMOTION_NONE, CU_TENSOR_MAP_FLOAT_OOB_FILL_NONE);
    }
    {
        cuuint64_t dims[5] = {(cuuint64_t)kC, 2, 4, kGroup * kSeg / 8, 35};
        cuuint64_t strides[4] = {4 * 768, 768, 8 * 768, kGroup * kSeg * 768};
        cuuint32_t box[5] = {64, 2, 4, kSeg / 8, 32 / kSeg};
        enc(&tm_coarse, CU_TENSOR_MAP_DATA_TYPE_BFLOAT16, 5, d_in[1], dims, strides, box, ones, CU_TENSOR_MAP_INTERLEAVE_NONE,
            CU_TENSOR_MAP_SWIZZLE_128B, CU_TENSOR_MAP_L2_PROMOTION_L2_128B, CU_TENSOR_MAP_FLOAT_OOB_FILL_NONE);
        dims[4] = 34;
        enc(&tm_coarse2, CU_TENSOR_MAP_DATA_TYPE_BFLOAT16, 5, d_in[1], dims, strides, box, ones, CU_TENSOR_MAP_INTERLEAVE_NONE,
            CU_TENSOR_MAP_SWIZZLE_128B, CU_TENSOR_MAP_L2_PROMOTION_L2_128B, CU_TENSOR_MAP_FLOAT_OOB_FILL_NONE);
    }
    fpn_lateral_kernel<<<2 * kClusters, 512, kSmemBytes>>>(scr, (const char*)d_in[0], (const char*)d_in[1], (const char*)d_in[2], (const char*)d_in[3],
                                                          tm_fine, tm_coarse, tm_coarse2, tm_wlat, tm_wout, tm_out, sched);
}
```
